```python
import torch

def _softmax(x, axis=-1):
    return torch.softmax(x, dim=axis)
def _gelu(x):
    return torch.nn.functional.gelu(x, approximate="tanh")
def _silu(x):
    return torch.nn.functional.silu(x)
def _sigmoid(x):
    return torch.sigmoid(x)
def _layernorm(x, axis=-1, eps=1e-5):
    m = x.mean(dim=axis, keepdim=True)
    v = x.var(dim=axis, keepdim=True, unbiased=False)
    return (x - m) / torch.sqrt(v + eps)
def _scatter_add(tgt, idx, src, axis=0):
    return tgt.clone().index_add_(axis, idx, src)
def _segment_sum(src, seg, n):
    out = torch.zeros((n,) + src.shape[1:], dtype=src.dtype)
    return out.index_add_(0, seg, src)
def _pad(x, pw):
    flat = tuple(v for pair in reversed(pw) for v in pair)
    return torch.nn.functional.pad(x, flat)

kernel_name = 'recurrent_scan__spectral_fnet__geglu_ffn__prompt'

def setup_inputs():

    _w = (lambda a: (lambda t: t.to(torch.bfloat16) if t.is_floating_point() else t)(torch.as_tensor(a)))
    def _A_setup():
        B, S, D = 1, 2048, 448
        ns = torch.arange(S)[:, None] * torch.arange(S)[None, :]
        nd = torch.arange(D)[:, None] * torch.arange(D)[None, :]
        Ws_re = torch.cos(-2.0 * torch.pi * ns / S).to(float)
        Ws_im = torch.sin(-2.0 * torch.pi * ns / S).to(float)
        Wd_re = torch.cos(-2.0 * torch.pi * nd / D).to(float)
        Wd_im = torch.sin(-2.0 * torch.pi * nd / D).to(float)
        return {
            "x": _w((lambda *s: torch.randn(*s, dtype=torch.bfloat16) * 0.05)(B, S, D)),
            "dft_seq_re": _w(Ws_re),
            "dft_seq_im": _w(Ws_im),
            "dft_hid_re": _w(Wd_re),
            "dft_hid_im": _w(Wd_im),
        }
    _A_in = _A_setup()

    def _B_setup():
        B, S, D, F = 1, 2048, 448, 1792
        return {
            "x": _w((lambda *s: torch.randn(*s, dtype=torch.bfloat16) * 0.05)(B, S, D)),
            "w_gate": _w((lambda *s: torch.randn(*s, dtype=torch.bfloat16) * 0.05)(D, F)),
            "w_up": _w((lambda *s: torch.randn(*s, dtype=torch.bfloat16) * 0.05)(D, F)),
            "w_down": _w((lambda *s: torch.randn(*s, dtype=torch.bfloat16) * 0.05)(F, D)),
        }
    _B_in = _B_setup()

    return {
        "A_x": _A_in["x"],
        "A_dft_seq_re": _A_in["dft_seq_re"],
        "A_dft_seq_im": _A_in["dft_seq_im"],
        "A_dft_hid_re": _A_in["dft_hid_re"],
        "A_dft_hid_im": _A_in["dft_hid_im"],
        "B_x": _B_in["x"],
        "B_w_gate": _B_in["w_gate"],
        "B_w_up": _B_in["w_up"],
        "B_w_down": _B_in["w_down"],
    }

def reference(A_x, A_dft_seq_re, A_dft_seq_im, A_dft_hid_re, A_dft_hid_im, B_x, B_w_gate, B_w_up, B_w_down):
    def _A_ref(x, dft_seq_re, dft_seq_im, dft_hid_re, dft_hid_im):
        a = torch.einsum("bsd,ed->bse", x, dft_hid_re)
        b = torch.einsum("bsd,ed->bse", x, dft_hid_im)
        y = torch.einsum("ts,bse->bte", dft_seq_re, a) - torch.einsum("ts,bse->bte", dft_seq_im, b)
        return y

    def _B_ref(x, w_gate, w_up, w_down):
        return (_gelu(x @ w_gate) * (x @ w_up)) @ w_down

    x = A_x
    xn = _layernorm(x, axis=-1)
    s = _A_ref(xn, A_dft_seq_re, A_dft_seq_im, A_dft_hid_re, A_dft_hid_im)
    g = _silu(_B_ref(xn, B_w_gate, B_w_up, B_w_down))
    return x + s * g
```

```cpp
#include <cuda_runtime.h>
#include <cuda_bf16.h>
#include <cuda.h>
#include <stdint.h>

namespace {

constexpr int S_ = 2048, D_ = 448, F_ = 1792;

__device__ __nv_bfloat16 g_ab[4096 * 448];
__device__ __nv_bfloat16 g_h[2048 * 1792];
__device__ float2 g_part[32 * 5 * 4 * 14 * 256];
__device__ unsigned int g_flags[32];

__device__ __forceinline__ uint32_t s2u(const void* p) { return (uint32_t)__cvta_generic_to_shared(p); }
__device__ __forceinline__ void mbar_init(uint32_t b, int c) { asm volatile("mbarrier.init.shared::cta.b64 [%0], %1;" ::"r"(b), "r"(c)); }
__device__ __forceinline__ void mbar_expect(uint32_t b, uint32_t bytes) {
  asm volatile("mbarrier.arrive.expect_tx.shared::cta.b64 _, [%0], %1;" ::"r"(b), "r"(bytes) : "memory");
}
__device__ __forceinline__ void mbar_wait(uint32_t b, uint32_t ph) {
  uint32_t done = 0;
  int it = 0;
  while (true) {
    asm volatile("{.reg .pred p; mbarrier.try_wait.parity.shared::cta.b64 p, [%1], %2; selp.u32 %0,1,0,p;}" : "=r"(done) : "r"(b), "r"(ph) : "memory");
    if (done) break;
    if (++it > (1 << 22)) __trap();
  }
}
__device__ __forceinline__ void mbar_wait_cluster(uint32_t b, uint32_t ph) {
  uint32_t done = 0;
  int it = 0;
  while (true) {
    asm volatile("{.reg .pred p; mbarrier.try_wait.parity.acquire.cluster.shared::cta.b64 p, [%1], %2; selp.u32 %0,1,0,p;}" : "=r"(done) : "r"(b), "r"(ph) : "memory");
    if (done) break;
    if (++it > (1 << 22)) __trap();
  }
}
__device__ __forceinline__ void mbar_arrive_cluster(uint32_t b, uint32_t cta) {
  uint32_t r;
  asm volatile("mapa.shared::cluster.u32 %0, %1, %2;" : "=r"(r) : "r"(b), "r"(cta));
  asm volatile("mbarrier.arrive.shared::cluster.b64 _, [%0];" ::"r"(r) : "memory");
}
__device__ __forceinline__ void tma2d(uint32_t dst, const CUtensorMap* m, int c0, int c1, uint32_t bar) {
  asm volatile("cp.async.bulk.tensor.2d.shared::cluster.global.mbarrier::complete_tx::bytes [%0], [%1, {%3,%4}], [%2];" ::"r"(dst), "l"(m), "r"(bar), "r"(c0), "r"(c1) : "memory");
}
__device__ __forceinline__ void tma2d_mc(uint32_t dst, const CUtensorMap* m, int c0, int c1, uint32_t bar, uint16_t mask) {
  asm volatile("cp.async.bulk.tensor.2d.shared::cluster.global.mbarrier::complete_tx::bytes.multicast::cluster [%0], [%1, {%3,%4}], [%2], %5;" ::"r"(dst), "l"(m), "r"(bar), "r"(c0), "r"(c1), "h"(mask) : "memory");
}
__device__ __forceinline__ void tma3d_mc(uint32_t dst, const CUtensorMap* m, int c0, int c1, int c2, uint32_t bar, uint16_t mask) {
  asm volatile("cp.async.bulk.tensor.3d.shared::cluster.global.mbarrier::complete_tx::bytes.multicast::cluster [%0], [%1, {%3,%4,%5}], [%2], %6;" ::"r"(dst), "l"(m), "r"(bar), "r"(c0), "r"(c1), "r"(c2), "h"(mask) : "memory");
}
__device__ __forceinline__ void prefetch_tmap(const CUtensorMap* m) { asm volatile("prefetch.tensormap [%0];" ::"l"(m) : "memory"); }
__device__ __forceinline__ void cluster_sync_all() {
  asm volatile("barrier.cluster.arrive.release.aligned;\nbarrier.cluster.wait.acquire.aligned;" ::: "memory");
}
__device__ __forceinline__ void wg_fence() { asm volatile("wgmma.fence.sync.aligned;" ::: "memory"); }
__device__ __forceinline__ void wg_commit() { asm volatile("wgmma.commit_group.sync.aligned;" ::: "memory"); }
template <int N> __device__ __forceinline__ void wg_wait() { asm volatile("wgmma.wait_group.sync.aligned %0;" ::"n"(N) : "memory"); }
__device__ __forceinline__ void named_bar(int id, int n) { asm volatile("bar.sync %0, %1;" ::"r"(id), "r"(n) : "memory"); }
template <int N> __device__ __forceinline__ void reg_inc() { asm volatile("setmaxnreg.inc.sync.aligned.u32 %0;" ::"n"(N)); }
template <int N> __device__ __forceinline__ void reg_dec() { asm volatile("setmaxnreg.dec.sync.aligned.u32 %0;" ::"n"(N)); }

__device__ __forceinline__ uint64_t make_desc(uint32_t addr, uint32_t lbo, uint32_t sbo) {
  return (uint64_t)((addr & 0x3FFFF) >> 4) | ((uint64_t)(lbo >> 4) << 16) | ((uint64_t)(sbo >> 4) << 32) | (1ull << 62);
}
__device__ __forceinline__ void stmatrix_x4(uint32_t addr, uint32_t r0, uint32_t r1, uint32_t r2, uint32_t r3) {
  asm volatile("stmatrix.sync.aligned.m8n8.x4.shared.b16 [%0], {%1,%2,%3,%4};" ::"r"(addr), "r"(r0), "r"(r1), "r"(r2), "r"(r3) : "memory");
}
__device__ __forceinline__ uint4 lds128(uint32_t a) {
  uint4 v;
  asm volatile("ld.shared.v4.u32 {%0,%1,%2,%3}, [%4];" : "=r"(v.x), "=r"(v.y), "=r"(v.z), "=r"(v.w) : "r"(a) : "memory");
  return v;
}
__device__ __forceinline__ void sts128(uint32_t a, uint4 v) {
  asm volatile("st.shared.v4.u32 [%0], {%1,%2,%3,%4};" ::"r"(a), "r"(v.x), "r"(v.y), "r"(v.z), "r"(v.w) : "memory");
}
__device__ __forceinline__ uint32_t pack_bf16(float lo, float hi) {
  uint32_t r;
  asm("cvt.rn.bf16x2.f32 %0, %1, %2;" : "=r"(r) : "f"(hi), "f"(lo));
  return r;
}
__device__ __forceinline__ float bf_lo(uint32_t w) { return __uint_as_float(w << 16); }
__device__ __forceinline__ float bf_hi(uint32_t w) { return __uint_as_float(w & 0xffff0000u); }
__device__ __forceinline__ float rbf(float x) { return __bfloat162float(__float2bfloat16_rn(x)); }
__device__ __forceinline__ float ex2f(float x) { float r; asm("ex2.approx.ftz.f32 %0, %1;" : "=f"(r) : "f"(x)); return r; }
__device__ __forceinline__ float gelu_tanh(float x) {
  const float c1 = 2.0f * 0.7978845608028654f * 1.4426950408889634f;
  const float c2 = c1 * 0.044715f;
  float e = ex2f(-x * fmaf(c2, x * x, c1));
  return __fdividef(x, 1.0f + e);
}
__device__ __forceinline__ float silu_f(float x) {
  float e = ex2f(-1.4426950408889634f * x);
  return __fdividef(x, 1.0f + e);
}

__device__ __forceinline__ void wgmma_n128_tb(float (&d)[64], uint64_t da, uint64_t db, int scale_d) {
  asm volatile(
    "{\n.reg .pred p;\nsetp.ne.b32 p, %66, 0;\n"
    "wgmma.mma_async.sync.aligned.m64n128k16.f32.bf16.bf16 {%0, %1, %2, %3, %4, %5, %6, %7, %8, %9, %10, %11, %12, %13, %14, %15, %16, %17, %18, %19, %20, %21, %22, %23, %24, %25, %26, %27, %28, %29, %30, %31, %32, %33, %34, %35, %36, %37, %38, %39, %40, %41, %42, %43, %44, %45, %46, %47, %48, %49, %50, %51, %52, %53, %54, %55, %56, %57, %58, %59, %60, %61, %62, %63}, %64, %65, p, 1, 1, 0, 1;\n}\n"
    : "+f"(d[0]), "+f"(d[1]), "+f"(d[2]), "+f"(d[3]), "+f"(d[4]), "+f"(d[5]), "+f"(d[6]), "+f"(d[7]), "+f"(d[8]), "+f"(d[9]), "+f"(d[10]), "+f"(d[11]), "+f"(d[12]), "+f"(d[13]), "+f"(d[14]), "+f"(d[15]), "+f"(d[16]), "+f"(d[17]), "+f"(d[18]), "+f"(d[19]), "+f"(d[20]), "+f"(d[21]), "+f"(d[22]), "+f"(d[23]), "+f"(d[24]), "+f"(d[25]), "+f"(d[26]), "+f"(d[27]), "+f"(d[28]), "+f"(d[29]), "+f"(d[30]), "+f"(d[31]), "+f"(d[32]), "+f"(d[33]), "+f"(d[34]), "+f"(d[35]), "+f"(d[36]), "+f"(d[37]), "+f"(d[38]), "+f"(d[39]), "+f"(d[40]), "+f"(d[41]), "+f"(d[42]), "+f"(d[43]), "+f"(d[44]), "+f"(d[45]), "+f"(d[46]), "+f"(d[47]), "+f"(d[48]), "+f"(d[49]), "+f"(d[50]), "+f"(d[51]), "+f"(d[52]), "+f"(d[53]), "+f"(d[54]), "+f"(d[55]), "+f"(d[56]), "+f"(d[57]), "+f"(d[58]), "+f"(d[59]), "+f"(d[60]), "+f"(d[61]), "+f"(d[62]), "+f"(d[63])
    : "l"(da), "l"(db), "r"(scale_d));
}
__device__ __forceinline__ void wgmma_n112(float (&d)[56], uint64_t da, uint64_t db, int scale_d) {
  asm volatile(
    "{\n.reg .pred p;\nsetp.ne.b32 p, %58, 0;\n"
    "wgmma.mma_async.sync.aligned.m64n112k16.f32.bf16.bf16 {%0, %1, %2, %3, %4, %5, %6, %7, %8, %9, %10, %11, %12, %13, %14, %15, %16, %17, %18, %19, %20, %21, %22, %23, %24, %25, %26, %27, %28, %29, %30, %31, %32, %33, %34, %35, %36, %37, %38, %39, %40, %41, %42, %43, %44, %45, %46, %47, %48, %49, %50, %51, %52, %53, %54, %55}, %56, %57, p, 1, 1, 0, 0;\n}\n"
    : "+f"(d[0]), "+f"(d[1]), "+f"(d[2]), "+f"(d[3]), "+f"(d[4]), "+f"(d[5]), "+f"(d[6]), "+f"(d[7]), "+f"(d[8]), "+f"(d[9]), "+f"(d[10]), "+f"(d[11]), "+f"(d[12]), "+f"(d[13]), "+f"(d[14]), "+f"(d[15]), "+f"(d[16]), "+f"(d[17]), "+f"(d[18]), "+f"(d[19]), "+f"(d[20]), "+f"(d[21]), "+f"(d[22]), "+f"(d[23]), "+f"(d[24]), "+f"(d[25]), "+f"(d[26]), "+f"(d[27]), "+f"(d[28]), "+f"(d[29]), "+f"(d[30]), "+f"(d[31]), "+f"(d[32]), "+f"(d[33]), "+f"(d[34]), "+f"(d[35]), "+f"(d[36]), "+f"(d[37]), "+f"(d[38]), "+f"(d[39]), "+f"(d[40]), "+f"(d[41]), "+f"(d[42]), "+f"(d[43]), "+f"(d[44]), "+f"(d[45]), "+f"(d[46]), "+f"(d[47]), "+f"(d[48]), "+f"(d[49]), "+f"(d[50]), "+f"(d[51]), "+f"(d[52]), "+f"(d[53]), "+f"(d[54]), "+f"(d[55])
    : "l"(da), "l"(db), "r"(scale_d));
}
__device__ __forceinline__ void wgmma_n224_tb(float (&d)[112], uint64_t da, uint64_t db, int scale_d) {
  asm volatile(
    "{\n.reg .pred p;\nsetp.ne.b32 p, %114, 0;\n"
    "wgmma.mma_async.sync.aligned.m64n224k16.f32.bf16.bf16 {%0, %1, %2, %3, %4, %5, %6, %7, %8, %9, %10, %11, %12, %13, %14, %15, %16, %17, %18, %19, %20, %21, %22, %23, %24, %25, %26, %27, %28, %29, %30, %31, %32, %33, %34, %35, %36, %37, %38, %39, %40, %41, %42, %43, %44, %45, %46, %47, %48, %49, %50, %51, %52, %53, %54, %55, %56, %57, %58, %59, %60, %61, %62, %63, %64, %65, %66, %67, %68, %69, %70, %71, %72, %73, %74, %75, %76, %77, %78, %79, %80, %81, %82, %83, %84, %85, %86, %87, %88, %89, %90, %91, %92, %93, %94, %95, %96, %97, %98, %99, %100, %101, %102, %103, %104, %105, %106, %107, %108, %109, %110, %111}, %112, %113, p, 1, 1, 0, 1;\n}\n"
    : "+f"(d[0]), "+f"(d[1]), "+f"(d[2]), "+f"(d[3]), "+f"(d[4]), "+f"(d[5]), "+f"(d[6]), "+f"(d[7]), "+f"(d[8]), "+f"(d[9]), "+f"(d[10]), "+f"(d[11]), "+f"(d[12]), "+f"(d[13]), "+f"(d[14]), "+f"(d[15]), "+f"(d[16]), "+f"(d[17]), "+f"(d[18]), "+f"(d[19]), "+f"(d[20]), "+f"(d[21]), "+f"(d[22]), "+f"(d[23]), "+f"(d[24]), "+f"(d[25]), "+f"(d[26]), "+f"(d[27]), "+f"(d[28]), "+f"(d[29]), "+f"(d[30]), "+f"(d[31]), "+f"(d[32]), "+f"(d[33]), "+f"(d[34]), "+f"(d[35]), "+f"(d[36]), "+f"(d[37]), "+f"(d[38]), "+f"(d[39]), "+f"(d[40]), "+f"(d[41]), "+f"(d[42]), "+f"(d[43]), "+f"(d[44]), "+f"(d[45]), "+f"(d[46]), "+f"(d[47]), "+f"(d[48]), "+f"(d[49]), "+f"(d[50]), "+f"(d[51]), "+f"(d[52]), "+f"(d[53]), "+f"(d[54]), "+f"(d[55]), "+f"(d[56]), "+f"(d[57]), "+f"(d[58]), "+f"(d[59]), "+f"(d[60]), "+f"(d[61]), "+f"(d[62]), "+f"(d[63]), "+f"(d[64]), "+f"(d[65]), "+f"(d[66]), "+f"(d[67]), "+f"(d[68]), "+f"(d[69]), "+f"(d[70]), "+f"(d[71]), "+f"(d[72]), "+f"(d[73]), "+f"(d[74]), "+f"(d[75]), "+f"(d[76]), "+f"(d[77]), "+f"(d[78]), "+f"(d[79]), "+f"(d[80]), "+f"(d[81]), "+f"(d[82]), "+f"(d[83]), "+f"(d[84]), "+f"(d[85]), "+f"(d[86]), "+f"(d[87]), "+f"(d[88]), "+f"(d[89]), "+f"(d[90]), "+f"(d[91]), "+f"(d[92]), "+f"(d[93]), "+f"(d[94]), "+f"(d[95]), "+f"(d[96]), "+f"(d[97]), "+f"(d[98]), "+f"(d[99]), "+f"(d[100]), "+f"(d[101]), "+f"(d[102]), "+f"(d[103]), "+f"(d[104]), "+f"(d[105]), "+f"(d[106]), "+f"(d[107]), "+f"(d[108]), "+f"(d[109]), "+f"(d[110]), "+f"(d[111])
    : "l"(da), "l"(db), "r"(scale_d));
}


constexpr int K1_NS = 6;
constexpr int K1_A_BYTES = 7 * 16384;
constexpr int K1_B_OFF = K1_A_BYTES;
constexpr int K1_STG_OFF = K1_B_OFF + K1_NS * 16384;
constexpr int K1_BAR_OFF = K1_STG_OFF + 8 * 2048;
constexpr int K1_SMEM = K1_BAR_OFF + 256 + 1024;


__device__ __forceinline__ void k1_release(uint32_t bar_empty, int s, int lane) {
  if (lane == 0) { const int ps = s % K1_NS; mbar_arrive_cluster(bar_empty + 8 * ps, 0); mbar_arrive_cluster(bar_empty + 8 * ps, 1); }
}

__device__ __forceinline__ void k1_unit_ab(uint32_t sb, uint32_t bar_full, uint32_t bar_empty, int warp, int lane, int mt, int j) {
  const uint32_t stg = sb + K1_STG_OFF + warp * 2048;
  const int wq = warp & 3;
  const int st_row = (lane & 7) + 8 * ((lane >> 3) & 1);
  const int st_chunk = lane >> 4;
  float acc[2][56];
#pragma unroll 1
  for (int kb = 0; kb < 7; kb++) {
    const int s = kb;
    const int slot = s % K1_NS; const uint32_t ph = (s / K1_NS) & 1;
    mbar_wait(bar_full + 8 * slot, ph);
    wg_fence();
    const uint64_t da = make_desc(sb + kb * 16384, 16, 1024);
    const uint64_t db = make_desc(sb + K1_B_OFF + slot * 16384, 16, 1024);
#pragma unroll
    for (int k = 0; k < 4; k++) {
      wgmma_n112(acc[0], da + k * 2, db + k * 2, (kb | k) != 0);
      wgmma_n112(acc[1], da + 512 + k * 2, db + k * 2, (kb | k) != 0);
    }
    wg_commit();
    if (kb > 0) { wg_wait<1>(); k1_release(bar_empty, s - 1, lane); }
  }
  wg_wait<0>();
  k1_release(bar_empty, 6, lane);
  const float sgn = (j < 4) ? 1.0f : -1.0f;
  __nv_bfloat16* outp = g_ab + (size_t)((j < 4 ? 0 : 2048) + mt * 128) * 448 + (j & 3) * 112;
#pragma unroll
  for (int h = 0; h < 2; h++) {
    const int row0 = h * 64 + wq * 16;
#pragma unroll
    for (int g = 0; g < 8; g += 2) {
      const float* a = &acc[h][4 * g];
      stmatrix_x4(stg + st_row * 128 + (((g + st_chunk) ^ (st_row & 7)) * 16),
                  pack_bf16(sgn * a[0], sgn * a[1]), pack_bf16(sgn * a[2], sgn * a[3]),
                  pack_bf16(sgn * a[4], sgn * a[5]), pack_bf16(sgn * a[6], sgn * a[7]));
    }
    __syncwarp();
#pragma unroll
    for (int t = 0; t < 4; t++) {
      const int idx = t * 32 + lane, row = idx >> 3, ch = idx & 7;
      uint4 v = lds128(stg + row * 128 + ((ch ^ (row & 7)) * 16));
      *reinterpret_cast<uint4*>(outp + (size_t)(row0 + row) * 448 + ch * 8) = v;
    }
    __syncwarp();
#pragma unroll
    for (int g = 8; g < 14; g += 2) {
      const float* a = &acc[h][4 * g];
      stmatrix_x4(stg + st_row * 128 + (((g - 8 + st_chunk) ^ (st_row & 7)) * 16),
                  pack_bf16(sgn * a[0], sgn * a[1]), pack_bf16(sgn * a[2], sgn * a[3]),
                  pack_bf16(sgn * a[4], sgn * a[5]), pack_bf16(sgn * a[6], sgn * a[7]));
    }
    __syncwarp();
#pragma unroll
    for (int t = 0; t < 4; t++) {
      const int idx = t * 32 + lane, row = idx >> 3, ch = idx & 7;
      if (ch < 6) {
        uint4 v = lds128(stg + row * 128 + ((ch ^ (row & 7)) * 16));
        *reinterpret_cast<uint4*>(outp + (size_t)(row0 + row) * 448 + 64 + ch * 8) = v;
      }
    }
    __syncwarp();
  }
}

template <bool HALF>
__device__ __forceinline__ void k1_unit_gu(uint32_t sb, uint32_t bar_full, uint32_t bar_empty, int warp, int lane, int mt, int unit, int fb, int hsel) {
  const uint32_t stg = sb + K1_STG_OFF + warp * 2048;
  const int wq = warp & 3;
  const int st_row = (lane & 7) + 8 * ((lane >> 3) & 1);
  const int st_chunk = lane >> 4;
  constexpr int NH = HALF ? 1 : 2;
  float acc[NH][64];
#pragma unroll 1
  for (int kb = 0; kb < 7; kb++) {
    const int s = unit * 7 + kb;
    const int slot = s % K1_NS; const uint32_t ph = (s / K1_NS) & 1;
    mbar_wait(bar_full + 8 * slot, ph);
    wg_fence();
    const uint64_t da = make_desc(sb + kb * 16384 + (HALF ? hsel * 8192 : 0), 16, 1024);
    const uint64_t db = make_desc(sb + K1_B_OFF + slot * 16384, 8192, 1024);
#pragma unroll
    for (int k = 0; k < 4; k++) {
#pragma unroll
      for (int h = 0; h < NH; h++) wgmma_n128_tb(acc[h], da + h * 512 + k * 2, db + k * 128, (kb | k) != 0);
    }
    wg_commit();
    if (kb > 0) { wg_wait<1>(); k1_release(bar_empty, s - 1, lane); }
  }
  wg_wait<0>();
  k1_release(bar_empty, unit * 7 + 6, lane);
  __nv_bfloat16* outp = g_h + (size_t)(mt * 128) * 1792 + fb * 64;
#pragma unroll
  for (int h = 0; h < NH; h++) {
    const int row0 = (HALF ? hsel : h) * 64 + wq * 16;
#pragma unroll
    for (int g = 0; g < 8; g += 2) {
      uint32_t pk[4];
#pragma unroll
      for (int q = 0; q < 4; q++) {
        const int i = 4 * g + 2 * q;
        float h0 = rbf(gelu_tanh(rbf(acc[h][i]))) * rbf(acc[h][32 + i]);
        float h1 = rbf(gelu_tanh(rbf(acc[h][i + 1]))) * rbf(acc[h][32 + i + 1]);
        pk[q] = pack_bf16(h0, h1);
      }
      stmatrix_x4(stg + st_row * 128 + (((g + st_chunk) ^ (st_row & 7)) * 16), pk[0], pk[1], pk[2], pk[3]);
    }
    __syncwarp();
#pragma unroll
    for (int t = 0; t < 4; t++) {
      const int idx = t * 32 + lane, row = idx >> 3, ch = idx & 7;
      uint4 v = lds128(stg + row * 128 + ((ch ^ (row & 7)) * 16));
      *reinterpret_cast<uint4*>(outp + (size_t)(row0 + row) * 1792 + ch * 8) = v;
    }
    __syncwarp();
  }
}

__global__ void __cluster_dims__(2, 1, 1) __launch_bounds__(384, 1)
k1_kernel(const __grid_constant__ CUtensorMap tm_x, const __grid_constant__ CUtensorMap tm_wr, const __grid_constant__ CUtensorMap tm_wi,
          const __grid_constant__ CUtensorMap tm_wg, const __grid_constant__ CUtensorMap tm_wu) {
  extern __shared__ uint8_t smem_raw[];
  const uint32_t sb = (s2u(smem_raw) + 1023) & ~1023u;
  const int tid = threadIdx.x, warp = tid >> 5, lane = tid & 31;
  uint32_t rank;
  asm volatile("mov.u32 %0, %%cluster_ctarank;" : "=r"(rank));
  const int cid = blockIdx.x >> 1;
  const int p = cid >> 3, j = cid & 7;
  const int mt = 2 * p + (int)rank;
  const uint32_t bar_x = sb + K1_BAR_OFF;
  const uint32_t bar_full = bar_x + 8;
  const uint32_t bar_empty = bar_full + 8 * K1_NS;
  const int fb_base = 7 * (j >> 1);
  const int fb0 = fb_base + ((j & 1) ? 4 : 0);
  const int fbh = fb_base + 3;

  if (tid == 0) {
    mbar_init(bar_x, 1);
    for (int i = 0; i < K1_NS; i++) { mbar_init(bar_full + 8 * i, 1); mbar_init(bar_empty + 8 * i, 8); }
    asm volatile("fence.mbarrier_init.release.cluster;" ::: "memory");
    if (blockIdx.x < 32) g_flags[blockIdx.x] = 0;
  }
  __syncthreads();
  cluster_sync_all();

  if (warp >= 8) {
    reg_dec<40>();
    if (tid == 256) {
      mbar_expect(bar_x, K1_A_BYTES);
      for (int b = 0; b < 7; b++) tma2d(sb + b * 16384, &tm_x, b * 64, mt * 128, bar_x);
      const CUtensorMap* tw = (j < 4) ? &tm_wr : &tm_wi;
      const CUtensorMap* tgu = rank ? &tm_wu : &tm_wg;
      int slot = 0; uint32_t ph = 0;
      for (int s = 0; s < 35; s++) {
        const int unit = s / 7, kb = s - unit * 7;
        if (s >= K1_NS) mbar_wait(bar_empty + 8 * slot, ph ^ 1);
        const uint32_t dst = sb + K1_B_OFF + slot * 16384;
        if (unit == 0) {
          mbar_expect(bar_full + 8 * slot, 14336);
          tma2d_mc(dst + rank * 7168, tw, kb * 64, (j & 3) * 112 + rank * 56, bar_full + 8 * slot, 3);
        } else {
          const int fb = (unit == 4) ? fbh : (fb0 + unit - 1);
          mbar_expect(bar_full + 8 * slot, 16384);
          tma2d_mc(dst + rank * 8192, tgu, fb * 64, kb * 64, bar_full + 8 * slot, 3);
        }
        if (++slot == K1_NS) { slot = 0; ph ^= 1; }
      }
    }
  } else {
    reg_inc<232>();
    const int wg = warp >> 2;
    mbar_wait(bar_x, 0);
#pragma unroll 1
    for (int pass = 0; pass < 4; pass++) {
      const int r = warp * 16 + pass * 4 + (lane >> 3);
      const uint32_t a0 = sb + r * 128 + (lane & 7) * 16;
      uint4 v[7];
#pragma unroll
      for (int b = 0; b < 7; b++) v[b] = lds128(a0 + b * 16384);
      float sum = 0.f;
#pragma unroll
      for (int b = 0; b < 7; b++) {
        sum += bf_lo(v[b].x) + bf_hi(v[b].x); sum += bf_lo(v[b].y) + bf_hi(v[b].y);
        sum += bf_lo(v[b].z) + bf_hi(v[b].z); sum += bf_lo(v[b].w) + bf_hi(v[b].w);
      }
      sum += __shfl_xor_sync(0xffffffffu, sum, 1);
      sum += __shfl_xor_sync(0xffffffffu, sum, 2);
      sum += __shfl_xor_sync(0xffffffffu, sum, 4);
      const float mean = sum * (1.0f / 448.0f);
      float sq = 0.f;
#pragma unroll
      for (int b = 0; b < 7; b++) {
        const uint32_t w4[4] = {v[b].x, v[b].y, v[b].z, v[b].w};
#pragma unroll
        for (int q = 0; q < 4; q++) {
          float d0 = bf_lo(w4[q]) - mean, d1 = bf_hi(w4[q]) - mean;
          sq = fmaf(d0, d0, sq); sq = fmaf(d1, d1, sq);
        }
      }
      sq += __shfl_xor_sync(0xffffffffu, sq, 1);
      sq += __shfl_xor_sync(0xffffffffu, sq, 2);
      sq += __shfl_xor_sync(0xffffffffu, sq, 4);
      const float var_b = rbf(sq * (1.0f / 448.0f));
      const float den = rbf(sqrtf(rbf(var_b + 1e-5f)));
      const float rinv = 1.0f / den;
      const __nv_bfloat162 m2 = __float2bfloat162_rn(mean);
#pragma unroll
      for (int b = 0; b < 7; b++) {
        uint32_t w4[4] = {v[b].x, v[b].y, v[b].z, v[b].w};
#pragma unroll
        for (int q = 0; q < 4; q++) {
          __nv_bfloat162 x2 = *reinterpret_cast<__nv_bfloat162*>(&w4[q]);
          __nv_bfloat162 d2 = __hsub2(x2, m2);
          uint32_t dw = *reinterpret_cast<uint32_t*>(&d2);
          w4[q] = pack_bf16(bf_lo(dw) * rinv, bf_hi(dw) * rinv);
        }
        sts128(a0 + b * 16384, make_uint4(w4[0], w4[1], w4[2], w4[3]));
      }
    }
    asm volatile("fence.proxy.async.shared::cta;" ::: "memory");
    named_bar(1, 256);

    if (wg == 0) {
      k1_unit_ab(sb, bar_full, bar_empty, warp, lane, mt, j);
      k1_unit_gu<false>(sb, bar_full, bar_empty, warp, lane, mt, 2, fb0 + 1, 0);
      k1_unit_gu<true>(sb, bar_full, bar_empty, warp, lane, mt, 4, fbh, j & 1);
    } else {
      k1_unit_gu<false>(sb, bar_full, bar_empty, warp, lane, mt, 1, fb0, 0);
      k1_unit_gu<false>(sb, bar_full, bar_empty, warp, lane, mt, 3, fb0 + 2, 0);
    }
  }
  cluster_sync_all();
}

constexpr int K2_NS = 4;
constexpr int K2_STAGE = 16384 + 32768;
constexpr int K2_BAR_OFF = K2_NS * K2_STAGE;
constexpr int K2_SMEM = K2_BAR_OFF + 256 + 1024;

__global__ void __cluster_dims__(2, 1, 1) __launch_bounds__(384, 1)
k2_kernel(const __grid_constant__ CUtensorMap tm_cr, const __grid_constant__ CUtensorMap tm_ci, const __grid_constant__ CUtensorMap tm_h,
          const __grid_constant__ CUtensorMap tm_ab, const __grid_constant__ CUtensorMap tm_wd,
          const __nv_bfloat16* __restrict__ x, __nv_bfloat16* __restrict__ out) {
  extern __shared__ uint8_t smem_raw[];
  const uint32_t sb = (s2u(smem_raw) + 1023) & ~1023u;
  const int tid = threadIdx.x, warp = tid >> 5, lane = tid & 31;
  uint32_t rank;
  asm volatile("mov.u32 %0, %%cluster_ctarank;" : "=r"(rank));
  const int cid = blockIdx.x >> 1;
  const int q = cid & 3, n = (cid >> 2) & 1, p = cid >> 3;
  const int mt = 2 * p + (int)rank;
  const int tile = mt * 2 + n;
  const uint32_t bar_full = sb + K2_BAR_OFF;
  const uint32_t bar_empty = bar_full + 8 * K2_NS;
  const int g0 = q * 23;

  if (tid == 0) {
    for (int i = 0; i < K2_NS; i++) { mbar_init(bar_full + 8 * i, 1); mbar_init(bar_empty + 8 * i, 16); }
    asm volatile("fence.mbarrier_init.release.cluster;" ::: "memory");
  }
  __syncthreads();
  cluster_sync_all();

  if (warp >= 8) {
    reg_dec<40>();
    if (tid == 256) {
      int slot = 0; uint32_t ph = 0;
      for (int s = 0; s < 23; s++) {
        const int g = g0 + s;
        if (s >= K2_NS) mbar_wait(bar_empty + 8 * slot, ph ^ 1);
        const uint32_t dst = sb + slot * K2_STAGE;
        const uint32_t fb = bar_full + 8 * slot;
        mbar_expect(fb, K2_STAGE);
        const CUtensorMap* ta; const CUtensorMap* tb; int ka, kbrow;
        if (g < 32) { ta = &tm_cr; ka = g * 64; tb = &tm_ab; kbrow = g * 64; }
        else if (g < 64) { ta = &tm_ci; ka = (g - 32) * 64; tb = &tm_ab; kbrow = g * 64; }
        else { ta = &tm_h; ka = (g - 64) * 64; tb = &tm_wd; kbrow = (g - 64) * 64; }
        tma2d(dst, ta, ka, mt * 128, fb);
        tma3d_mc(dst + 16384 + (2 * rank) * 8192, tb, (2 * rank) * 64, n, kbrow, fb, 3);
        tma3d_mc(dst + 16384 + (2 * rank + 1) * 8192, tb, (2 * rank + 1) * 64, n, kbrow, fb, 3);
        if (++slot == K2_NS) { slot = 0; ph ^= 1; }
      }
    }
  } else {
    reg_inc<232>();
    const int wg = warp >> 2;
    float acc[112];
    float ykeep[28];
#pragma unroll
    for (int i = 0; i < 28; i++) ykeep[i] = 0.f;
    float2* part = g_part + (size_t)tile * (5 * 4 * 14 * 256) + tid;
    int slot = 0; uint32_t ph = 0;
    int first = 1;
#pragma unroll 1
    for (int s = 0; s < 23; s++) {
      const int g = g0 + s;
      mbar_wait(bar_full + 8 * slot, ph);
      wg_fence();
      const uint64_t da = make_desc(sb + slot * K2_STAGE + wg * 8192, 16, 1024);
      const uint64_t db = make_desc(sb + slot * K2_STAGE + 16384, 8192, 1024);
#pragma unroll
      for (int k = 0; k < 4; k++) wgmma_n224_tb(acc, da + k * 2, db + k * 128, !(first && k == 0));
      wg_commit();
      first = 0;
      if (s > 0) {
        wg_wait<1>();
        const int ps = (slot + K2_NS - 1) % K2_NS;
        if (lane == 0) { mbar_arrive_cluster(bar_empty + 8 * ps, 0); mbar_arrive_cluster(bar_empty + 8 * ps, 1); }
      }
      if (g == 63 && q == 2) {
        wg_wait<0>();
#pragma unroll
        for (int qq = 0; qq < 4; qq++) {
          if (qq == 2) {
#pragma unroll
            for (int i = 0; i < 28; i++) ykeep[i] = acc[56 + i];
          } else {
#pragma unroll
            for (int i = 0; i < 14; i++) part[((2 * 4 + qq) * 14 + i) * 256] = make_float2(acc[28 * qq + 2 * i], acc[28 * qq + 2 * i + 1]);
          }
        }
        first = 1;
      }
      if (++slot == K2_NS) { slot = 0; ph ^= 1; }
    }
    wg_wait<0>();
    const int myslot = (q < 2) ? q : (q + 1);
#pragma unroll
    for (int qq = 0; qq < 4; qq++) {
      if (qq != q) {
#pragma unroll
        for (int i = 0; i < 14; i++) part[((myslot * 4 + qq) * 14 + i) * 256] = make_float2(acc[28 * qq + 2 * i], acc[28 * qq + 2 * i + 1]);
      }
    }
    float own[28];
#pragma unroll
    for (int qq = 0; qq < 4; qq++) {
      if (qq == q) {
#pragma unroll
        for (int i = 0; i < 28; i++) own[i] = acc[28 * qq + i];
      }
    }
    __threadfence();
    named_bar(1, 256);
    if (tid == 0) {
      atomicAdd(&g_flags[tile], 1u);
      int it = 0;
      while (true) {
        unsigned int v;
        asm volatile("ld.acquire.gpu.global.u32 %0, [%1];" : "=r"(v) : "l"(&g_flags[tile]) : "memory");
        if (v >= 4u) break;
        if (++it > (1 << 22)) __trap();
      }
    }
    named_bar(1, 256);
    __threadfence();
    float yv[28], fv[28];
#pragma unroll
    for (int i = 0; i < 28; i++) { yv[i] = (q < 2) ? own[i] : ykeep[i]; fv[i] = (q >= 2) ? own[i] : 0.f; }
#pragma unroll
    for (int sl = 0; sl < 5; sl++) {
      const bool need = (sl != myslot) && !(q == 2 && sl == 2);
      if (need) {
#pragma unroll
        for (int i = 0; i < 14; i++) {
          float2 v = __ldcg(&part[((sl * 4 + q) * 14 + i) * 256]);
          if (sl < 3) { yv[2 * i] += v.x; yv[2 * i + 1] += v.y; } else { fv[2 * i] += v.x; fv[2 * i + 1] += v.y; }
        }
      }
    }
    const int row_base = mt * 128 + wg * 64 + (warp & 3) * 16 + (lane >> 2);
    const int col_base = n * 224 + q * 56 + (lane & 3) * 2;
#pragma unroll
    for (int i = 0; i < 14; i++) {
      const int row = row_base + (i & 1) * 8;
      const int col = col_base + (i >> 1) * 8;
      const uint32_t xw = *reinterpret_cast<const uint32_t*>(x + (size_t)row * 448 + col);
      float o[2];
#pragma unroll
      for (int e = 0; e < 2; e++) {
        const float sy = rbf(yv[2 * i + e]);
        const float gg = rbf(silu_f(rbf(fv[2 * i + e])));
        const float t = rbf(sy * gg);
        o[e] = (e ? bf_hi(xw) : bf_lo(xw)) + t;
      }
      *reinterpret_cast<uint32_t*>(out + (size_t)row * 448 + col) = pack_bf16(o[0], o[1]);
    }
  }
  cluster_sync_all();
}

typedef CUresult (*EncFn)(CUtensorMap*, CUtensorMapDataType, cuuint32_t, void*, const cuuint64_t*, const cuuint64_t*, const cuuint32_t*,
                          const cuuint32_t*, CUtensorMapInterleave, CUtensorMapSwizzle, CUtensorMapL2promotion, CUtensorMapFloatOOBfill);

void make2d(EncFn enc, CUtensorMap* tm, const void* ptr, uint64_t cols, uint64_t rows, uint32_t bc, uint32_t br) {
  cuuint64_t gd[2] = {cols, rows};
  cuuint64_t gs[1] = {cols * 2};
  cuuint32_t bd[2] = {bc, br};
  cuuint32_t es[2] = {1, 1};
  enc(tm, CU_TENSOR_MAP_DATA_TYPE_BFLOAT16, 2, const_cast<void*>(ptr), gd, gs, bd, es, CU_TENSOR_MAP_INTERLEAVE_NONE,
      CU_TENSOR_MAP_SWIZZLE_128B, CU_TENSOR_MAP_L2_PROMOTION_L2_128B, CU_TENSOR_MAP_FLOAT_OOB_FILL_NONE);
}
void make3d_half(EncFn enc, CUtensorMap* tm, const void* ptr, uint64_t rows) {
  cuuint64_t gd[3] = {224, 2, rows};
  cuuint64_t gs[2] = {448, 896};
  cuuint32_t bd[3] = {64, 1, 64};
  cuuint32_t es[3] = {1, 1, 1};
  enc(tm, CU_TENSOR_MAP_DATA_TYPE_BFLOAT16, 3, const_cast<void*>(ptr), gd, gs, bd, es, CU_TENSOR_MAP_INTERLEAVE_NONE,
      CU_TENSOR_MAP_SWIZZLE_128B, CU_TENSOR_MAP_L2_PROMOTION_L2_128B, CU_TENSOR_MAP_FLOAT_OOB_FILL_NONE);
}

struct Maps { CUtensorMap x, wr, wi, wg, wu, cr, ci, h, ab, wd; };

}

extern "C" void kernel_launch(void* const* d_in, const int* in_sizes, int n_in, void* d_out, int out_size) {
  (void)in_sizes; (void)n_in; (void)out_size;
  static Maps maps;
  static const void* cached[9] = {nullptr};
  static bool attr_done = false;
  bool same = true;
  for (int i = 0; i < 9; i++) same = same && (cached[i] == d_in[i]);
  if (!same) {
    void* fn = nullptr;
    cudaDriverEntryPointQueryResult qr;
    cudaGetDriverEntryPoint("cuTensorMapEncodeTiled", &fn, cudaEnableDefault, &qr);
    EncFn enc = (EncFn)fn;
    void *p_ab = nullptr, *p_h = nullptr;
    cudaGetSymbolAddress(&p_ab, g_ab);
    cudaGetSymbolAddress(&p_h, g_h);
    make2d(enc, &maps.x, d_in[0], 448, 2048, 64, 128);
    make2d(enc, &maps.cr, d_in[1], 2048, 2048, 64, 128);
    make2d(enc, &maps.ci, d_in[2], 2048, 2048, 64, 128);
    make2d(enc, &maps.wr, d_in[3], 448, 448, 64, 56);
    make2d(enc, &maps.wi, d_in[4], 448, 448, 64, 56);
    make2d(enc, &maps.wg, d_in[6], 1792, 448, 64, 64);
    make2d(enc, &maps.wu, d_in[7], 1792, 448, 64, 64);
    make3d_half(enc, &maps.wd, d_in[8], 1792);
    make2d(enc, &maps.h, p_h, 1792, 2048, 64, 128);
    make3d_half(enc, &maps.ab, p_ab, 4096);
    for (int i = 0; i < 9; i++) cached[i] = d_in[i];
  }
  if (!attr_done) {
    cudaFuncSetAttribute(k1_kernel, cudaFuncAttributeMaxDynamicSharedMemorySize, K1_SMEM);
    cudaFuncSetAttribute(k2_kernel, cudaFuncAttributeMaxDynamicSharedMemorySize, K2_SMEM);
    attr_done = true;
  }
  k1_kernel<<<128, 384, K1_SMEM>>>(maps.x, maps.wr, maps.wi, maps.wg, maps.wu);
  k2_kernel<<<128, 384, K2_SMEM>>>(maps.cr, maps.ci, maps.h, maps.ab, maps.wd, (const __nv_bfloat16*)d_in[0], (__nv_bfloat16*)d_out);
}
```

```cpp
#include <cuda_runtime.h>
#include <cuda_bf16.h>
#include <cuda.h>
#include <stdint.h>

namespace {

__device__ __nv_bfloat16 g_ab[4096 * 448];
__device__ __nv_bfloat16 g_h[2048 * 1792];
__device__ float4 g_part[32 * 3 * 28 * 256];
__device__ uint2 g_s[32 * 28 * 256];
__device__ unsigned int g_flags[64];

#define DBG(k, i) do {} while (0)

__device__ __forceinline__ uint32_t s2u(const void* p) { return (uint32_t)__cvta_generic_to_shared(p); }
__device__ __forceinline__ void mbar_init(uint32_t b, int c) { asm volatile("mbarrier.init.shared::cta.b64 [%0], %1;" ::"r"(b), "r"(c)); }
__device__ __forceinline__ void mbar_expect(uint32_t b, uint32_t bytes) {
  asm volatile("mbarrier.arrive.expect_tx.shared::cta.b64 _, [%0], %1;" ::"r"(b), "r"(bytes) : "memory");
}
__device__ __forceinline__ void mbar_wait(uint32_t b, uint32_t ph) {
  uint32_t done = 0;
  int it = 0;
  while (true) {
    asm volatile("{.reg .pred p; mbarrier.try_wait.parity.shared::cta.b64 p, [%1], %2; selp.u32 %0,1,0,p;}" : "=r"(done) : "r"(b), "r"(ph) : "memory");
    if (done) break;
    if (++it > (1 << 22)) __trap();
  }
}
__device__ __forceinline__ void mbar_arrive_cluster(uint32_t b, uint32_t cta) {
  uint32_t r;
  asm volatile("mapa.shared::cluster.u32 %0, %1, %2;" : "=r"(r) : "r"(b), "r"(cta));
  asm volatile("mbarrier.arrive.shared::cluster.b64 _, [%0];" ::"r"(r) : "memory");
}
__device__ __forceinline__ void tma2d(uint32_t dst, const CUtensorMap* m, int c0, int c1, uint32_t bar) {
  asm volatile("cp.async.bulk.tensor.2d.shared::cluster.global.mbarrier::complete_tx::bytes [%0], [%1, {%3,%4}], [%2];" ::"r"(dst), "l"(m), "r"(bar), "r"(c0), "r"(c1) : "memory");
}
__device__ __forceinline__ void tma2d_mc(uint32_t dst, const CUtensorMap* m, int c0, int c1, uint32_t bar, uint16_t mask) {
  asm volatile("cp.async.bulk.tensor.2d.shared::cluster.global.mbarrier::complete_tx::bytes.multicast::cluster [%0], [%1, {%3,%4}], [%2], %5;" ::"r"(dst), "l"(m), "r"(bar), "r"(c0), "r"(c1), "h"(mask) : "memory");
}
__device__ __forceinline__ void tma3d_mc(uint32_t dst, const CUtensorMap* m, int c0, int c1, int c2, uint32_t bar, uint16_t mask) {
  asm volatile("cp.async.bulk.tensor.3d.shared::cluster.global.mbarrier::complete_tx::bytes.multicast::cluster [%0], [%1, {%3,%4,%5}], [%2], %6;" ::"r"(dst), "l"(m), "r"(bar), "r"(c0), "r"(c1), "r"(c2), "h"(mask) : "memory");
}
__device__ __forceinline__ void prefetch_tmap(const CUtensorMap* m) { asm volatile("prefetch.tensormap [%0];" ::"l"(m) : "memory"); }
__device__ __forceinline__ void l2_prefetch(const void* p, uint32_t bytes) {
  asm volatile("cp.async.bulk.prefetch.L2.global [%0], %1;" ::"l"(p), "r"(bytes) : "memory");
}
__device__ __forceinline__ void cluster_arrive_relaxed() { asm volatile("barrier.cluster.arrive.relaxed.aligned;" ::: "memory"); }
__device__ __forceinline__ void cluster_wait() { asm volatile("barrier.cluster.wait.aligned;" ::: "memory"); }
__device__ __forceinline__ void wg_fence() { asm volatile("wgmma.fence.sync.aligned;" ::: "memory"); }
__device__ __forceinline__ void wg_commit() { asm volatile("wgmma.commit_group.sync.aligned;" ::: "memory"); }
template <int N> __device__ __forceinline__ void wg_wait() { asm volatile("wgmma.wait_group.sync.aligned %0;" ::"n"(N) : "memory"); }
__device__ __forceinline__ void named_bar(int id, int n) { asm volatile("bar.sync %0, %1;" ::"r"(id), "r"(n) : "memory"); }
template <int N> __device__ __forceinline__ void reg_inc() { asm volatile("setmaxnreg.inc.sync.aligned.u32 %0;" ::"n"(N)); }
template <int N> __device__ __forceinline__ void reg_dec() { asm volatile("setmaxnreg.dec.sync.aligned.u32 %0;" ::"n"(N)); }
__device__ __forceinline__ void pdl_wait() { asm volatile("griddepcontrol.wait;" ::: "memory"); }
__device__ __forceinline__ void pdl_launch() { asm volatile("griddepcontrol.launch_dependents;" ::: "memory"); }

__device__ __forceinline__ uint64_t make_desc(uint32_t addr, uint32_t lbo, uint32_t sbo) {
  return (uint64_t)((addr & 0x3FFFF) >> 4) | ((uint64_t)(lbo >> 4) << 16) | ((uint64_t)(sbo >> 4) << 32) | (1ull << 62);
}
__device__ __forceinline__ void stmatrix_x4(uint32_t addr, uint32_t r0, uint32_t r1, uint32_t r2, uint32_t r3) {
  asm volatile("stmatrix.sync.aligned.m8n8.x4.shared.b16 [%0], {%1,%2,%3,%4};" ::"r"(addr), "r"(r0), "r"(r1), "r"(r2), "r"(r3) : "memory");
}
__device__ __forceinline__ uint4 lds128(uint32_t a) {
  uint4 v;
  asm volatile("ld.shared.v4.u32 {%0,%1,%2,%3}, [%4];" : "=r"(v.x), "=r"(v.y), "=r"(v.z), "=r"(v.w) : "r"(a) : "memory");
  return v;
}
__device__ __forceinline__ void sts128(uint32_t a, uint4 v) {
  asm volatile("st.shared.v4.u32 [%0], {%1,%2,%3,%4};" ::"r"(a), "r"(v.x), "r"(v.y), "r"(v.z), "r"(v.w) : "memory");
}
__device__ __forceinline__ uint32_t pack_bf16(float lo, float hi) {
  uint32_t r;
  asm("cvt.rn.bf16x2.f32 %0, %1, %2;" : "=r"(r) : "f"(hi), "f"(lo));
  return r;
}
__device__ __forceinline__ uint32_t hmul2_bf16(uint32_t a, uint32_t b) {
  uint32_t r;
  asm("mul.rn.bf16x2 %0, %1, %2;" : "=r"(r) : "r"(a), "r"(b));
  return r;
}
__device__ __forceinline__ uint32_t hsub2_bf16(uint32_t a, uint32_t b) {
  uint32_t r;
  asm("sub.rn.bf16x2 %0, %1, %2;" : "=r"(r) : "r"(a), "r"(b));
  return r;
}
__device__ __forceinline__ uint32_t hadd2_bf16(uint32_t a, uint32_t b) {
  uint32_t r;
  asm("add.rn.bf16x2 %0, %1, %2;" : "=r"(r) : "r"(a), "r"(b));
  return r;
}
__device__ __forceinline__ float bf_lo(uint32_t w) { return __uint_as_float(w << 16); }
__device__ __forceinline__ float bf_hi(uint32_t w) { return __uint_as_float(w & 0xffff0000u); }
__device__ __forceinline__ float rbf(float x) { return __bfloat162float(__float2bfloat16_rn(x)); }
__device__ __forceinline__ float ex2f(float x) { float r; asm("ex2.approx.ftz.f32 %0, %1;" : "=f"(r) : "f"(x)); return r; }
__device__ __forceinline__ float rcpf(float x) { float r; asm("rcp.approx.ftz.f32 %0, %1;" : "=f"(r) : "f"(x)); return r; }
__device__ __forceinline__ float gelu_tanh(float x) {
  const float c1 = -2.0f * 0.7978845608028654f * 1.4426950408889634f;
  const float c2 = c1 * 0.044715f;
  const float e = ex2f(x * fmaf(c2, x * x, c1));
  return x * rcpf(1.0f + e);
}
__device__ __forceinline__ float silu_f(float x) {
  const float e = ex2f(-1.4426950408889634f * x);
  return x * rcpf(1.0f + e);
}

__device__ __forceinline__ void wgmma_n128_tb(float (&d)[64], uint64_t da, uint64_t db, int scale_d) {
  asm volatile(
    "{\n.reg .pred p;\nsetp.ne.b32 p, %66, 0;\n"
    "wgmma.mma_async.sync.aligned.m64n128k16.f32.bf16.bf16 {%0, %1, %2, %3, %4, %5, %6, %7, %8, %9, %10, %11, %12, %13, %14, %15, %16, %17, %18, %19, %20, %21, %22, %23, %24, %25, %26, %27, %28, %29, %30, %31, %32, %33, %34, %35, %36, %37, %38, %39, %40, %41, %42, %43, %44, %45, %46, %47, %48, %49, %50, %51, %52, %53, %54, %55, %56, %57, %58, %59, %60, %61, %62, %63}, %64, %65, p, 1, 1, 0, 1;\n}\n"
    : "+f"(d[0]), "+f"(d[1]), "+f"(d[2]), "+f"(d[3]), "+f"(d[4]), "+f"(d[5]), "+f"(d[6]), "+f"(d[7]), "+f"(d[8]), "+f"(d[9]), "+f"(d[10]), "+f"(d[11]), "+f"(d[12]), "+f"(d[13]), "+f"(d[14]), "+f"(d[15]), "+f"(d[16]), "+f"(d[17]), "+f"(d[18]), "+f"(d[19]), "+f"(d[20]), "+f"(d[21]), "+f"(d[22]), "+f"(d[23]), "+f"(d[24]), "+f"(d[25]), "+f"(d[26]), "+f"(d[27]), "+f"(d[28]), "+f"(d[29]), "+f"(d[30]), "+f"(d[31]), "+f"(d[32]), "+f"(d[33]), "+f"(d[34]), "+f"(d[35]), "+f"(d[36]), "+f"(d[37]), "+f"(d[38]), "+f"(d[39]), "+f"(d[40]), "+f"(d[41]), "+f"(d[42]), "+f"(d[43]), "+f"(d[44]), "+f"(d[45]), "+f"(d[46]), "+f"(d[47]), "+f"(d[48]), "+f"(d[49]), "+f"(d[50]), "+f"(d[51]), "+f"(d[52]), "+f"(d[53]), "+f"(d[54]), "+f"(d[55]), "+f"(d[56]), "+f"(d[57]), "+f"(d[58]), "+f"(d[59]), "+f"(d[60]), "+f"(d[61]), "+f"(d[62]), "+f"(d[63])
    : "l"(da), "l"(db), "r"(scale_d));
}
__device__ __forceinline__ void wgmma_n112(float (&d)[56], uint64_t da, uint64_t db, int scale_d) {
  asm volatile(
    "{\n.reg .pred p;\nsetp.ne.b32 p, %58, 0;\n"
    "wgmma.mma_async.sync.aligned.m64n112k16.f32.bf16.bf16 {%0, %1, %2, %3, %4, %5, %6, %7, %8, %9, %10, %11, %12, %13, %14, %15, %16, %17, %18, %19, %20, %21, %22, %23, %24, %25, %26, %27, %28, %29, %30, %31, %32, %33, %34, %35, %36, %37, %38, %39, %40, %41, %42, %43, %44, %45, %46, %47, %48, %49, %50, %51, %52, %53, %54, %55}, %56, %57, p, 1, 1, 0, 0;\n}\n"
    : "+f"(d[0]), "+f"(d[1]), "+f"(d[2]), "+f"(d[3]), "+f"(d[4]), "+f"(d[5]), "+f"(d[6]), "+f"(d[7]), "+f"(d[8]), "+f"(d[9]), "+f"(d[10]), "+f"(d[11]), "+f"(d[12]), "+f"(d[13]), "+f"(d[14]), "+f"(d[15]), "+f"(d[16]), "+f"(d[17]), "+f"(d[18]), "+f"(d[19]), "+f"(d[20]), "+f"(d[21]), "+f"(d[22]), "+f"(d[23]), "+f"(d[24]), "+f"(d[25]), "+f"(d[26]), "+f"(d[27]), "+f"(d[28]), "+f"(d[29]), "+f"(d[30]), "+f"(d[31]), "+f"(d[32]), "+f"(d[33]), "+f"(d[34]), "+f"(d[35]), "+f"(d[36]), "+f"(d[37]), "+f"(d[38]), "+f"(d[39]), "+f"(d[40]), "+f"(d[41]), "+f"(d[42]), "+f"(d[43]), "+f"(d[44]), "+f"(d[45]), "+f"(d[46]), "+f"(d[47]), "+f"(d[48]), "+f"(d[49]), "+f"(d[50]), "+f"(d[51]), "+f"(d[52]), "+f"(d[53]), "+f"(d[54]), "+f"(d[55])
    : "l"(da), "l"(db), "r"(scale_d));
}
__device__ __forceinline__ void wgmma_n224_tb(float (&d)[112], uint64_t da, uint64_t db, int scale_d) {
  asm volatile(
    "{\n.reg .pred p;\nsetp.ne.b32 p, %114, 0;\n"
    "wgmma.mma_async.sync.aligned.m64n224k16.f32.bf16.bf16 {%0, %1, %2, %3, %4, %5, %6, %7, %8, %9, %10, %11, %12, %13, %14, %15, %16, %17, %18, %19, %20, %21, %22, %23, %24, %25, %26, %27, %28, %29, %30, %31, %32, %33, %34, %35, %36, %37, %38, %39, %40, %41, %42, %43, %44, %45, %46, %47, %48, %49, %50, %51, %52, %53, %54, %55, %56, %57, %58, %59, %60, %61, %62, %63, %64, %65, %66, %67, %68, %69, %70, %71, %72, %73, %74, %75, %76, %77, %78, %79, %80, %81, %82, %83, %84, %85, %86, %87, %88, %89, %90, %91, %92, %93, %94, %95, %96, %97, %98, %99, %100, %101, %102, %103, %104, %105, %106, %107, %108, %109, %110, %111}, %112, %113, p, 1, 1, 0, 1;\n}\n"
    : "+f"(d[0]), "+f"(d[1]), "+f"(d[2]), "+f"(d[3]), "+f"(d[4]), "+f"(d[5]), "+f"(d[6]), "+f"(d[7]), "+f"(d[8]), "+f"(d[9]), "+f"(d[10]), "+f"(d[11]), "+f"(d[12]), "+f"(d[13]), "+f"(d[14]), "+f"(d[15]), "+f"(d[16]), "+f"(d[17]), "+f"(d[18]), "+f"(d[19]), "+f"(d[20]), "+f"(d[21]), "+f"(d[22]), "+f"(d[23]), "+f"(d[24]), "+f"(d[25]), "+f"(d[26]), "+f"(d[27]), "+f"(d[28]), "+f"(d[29]), "+f"(d[30]), "+f"(d[31]), "+f"(d[32]), "+f"(d[33]), "+f"(d[34]), "+f"(d[35]), "+f"(d[36]), "+f"(d[37]), "+f"(d[38]), "+f"(d[39]), "+f"(d[40]), "+f"(d[41]), "+f"(d[42]), "+f"(d[43]), "+f"(d[44]), "+f"(d[45]), "+f"(d[46]), "+f"(d[47]), "+f"(d[48]), "+f"(d[49]), "+f"(d[50]), "+f"(d[51]), "+f"(d[52]), "+f"(d[53]), "+f"(d[54]), "+f"(d[55]), "+f"(d[56]), "+f"(d[57]), "+f"(d[58]), "+f"(d[59]), "+f"(d[60]), "+f"(d[61]), "+f"(d[62]), "+f"(d[63]), "+f"(d[64]), "+f"(d[65]), "+f"(d[66]), "+f"(d[67]), "+f"(d[68]), "+f"(d[69]), "+f"(d[70]), "+f"(d[71]), "+f"(d[72]), "+f"(d[73]), "+f"(d[74]), "+f"(d[75]), "+f"(d[76]), "+f"(d[77]), "+f"(d[78]), "+f"(d[79]), "+f"(d[80]), "+f"(d[81]), "+f"(d[82]), "+f"(d[83]), "+f"(d[84]), "+f"(d[85]), "+f"(d[86]), "+f"(d[87]), "+f"(d[88]), "+f"(d[89]), "+f"(d[90]), "+f"(d[91]), "+f"(d[92]), "+f"(d[93]), "+f"(d[94]), "+f"(d[95]), "+f"(d[96]), "+f"(d[97]), "+f"(d[98]), "+f"(d[99]), "+f"(d[100]), "+f"(d[101]), "+f"(d[102]), "+f"(d[103]), "+f"(d[104]), "+f"(d[105]), "+f"(d[106]), "+f"(d[107]), "+f"(d[108]), "+f"(d[109]), "+f"(d[110]), "+f"(d[111])
    : "l"(da), "l"(db), "r"(scale_d));
}

constexpr int K1_NS = 6;
constexpr int K1_A_BYTES = 7 * 16384;
constexpr int K1_B_OFF = K1_A_BYTES;
constexpr int K1_STG_OFF = K1_B_OFF + K1_NS * 16384;
constexpr int K1_BAR_OFF = K1_STG_OFF + 8 * 2048;
constexpr int K1_SMEM = K1_BAR_OFF + 256 + 1024;

__device__ __forceinline__ void k1_release(uint32_t bar_empty, int s, int lane) {
  if (lane == 0) { const int ps = s % K1_NS; mbar_arrive_cluster(bar_empty + 8 * ps, 0); mbar_arrive_cluster(bar_empty + 8 * ps, 1); }
}

__device__ __forceinline__ void k1_unit_ab(uint32_t sb, uint32_t bar_full, uint32_t bar_empty, int warp, int lane, int mt, int j) {
  const uint32_t stg = sb + K1_STG_OFF + warp * 2048;
  const int wq = warp & 3;
  const int st_row = (lane & 7) + 8 * ((lane >> 3) & 1);
  const int st_chunk = lane >> 4;
  float acc[2][56];
#pragma unroll 1
  for (int kb = 0; kb < 7; kb++) {
    const int s = kb;
    const int slot = s % K1_NS; const uint32_t ph = (s / K1_NS) & 1;
    mbar_wait(bar_full + 8 * slot, ph);
    if (kb == 0 && (threadIdx.x & 127) == 0) DBG(0, 4);
    wg_fence();
    const uint64_t da = make_desc(sb + kb * 16384, 16, 1024);
    const uint64_t db = make_desc(sb + K1_B_OFF + slot * 16384, 16, 1024);
#pragma unroll
    for (int k = 0; k < 4; k++) {
      wgmma_n112(acc[0], da + k * 2, db + k * 2, (kb | k) != 0);
      wgmma_n112(acc[1], da + 512 + k * 2, db + k * 2, (kb | k) != 0);
    }
    wg_commit();
    if (kb > 0) { wg_wait<1>(); k1_release(bar_empty, s - 1, lane); }
  }
  wg_wait<0>();
  k1_release(bar_empty, 6, lane);
  if ((threadIdx.x & 127) == 0) DBG(0, 5);
  const uint32_t sgn = (j < 4) ? 0u : 0x80008000u;
  __nv_bfloat16* outp = g_ab + (size_t)((j < 4 ? 0 : 2048) + mt * 128) * 448 + (j & 3) * 112;
#pragma unroll
  for (int h = 0; h < 2; h++) {
    const int row0 = h * 64 + wq * 16;
#pragma unroll
    for (int g = 0; g < 8; g += 2) {
      const float* a = &acc[h][4 * g];
      stmatrix_x4(stg + st_row * 128 + (((g + st_chunk) ^ (st_row & 7)) * 16),
                  pack_bf16(a[0], a[1]) ^ sgn, pack_bf16(a[2], a[3]) ^ sgn, pack_bf16(a[4], a[5]) ^ sgn, pack_bf16(a[6], a[7]) ^ sgn);
    }
    __syncwarp();
#pragma unroll
    for (int t = 0; t < 4; t++) {
      const int idx = t * 32 + lane, row = idx >> 3, ch = idx & 7;
      uint4 v = lds128(stg + row * 128 + ((ch ^ (row & 7)) * 16));
      *reinterpret_cast<uint4*>(outp + (size_t)(row0 + row) * 448 + ch * 8) = v;
    }
    __syncwarp();
#pragma unroll
    for (int g = 8; g < 14; g += 2) {
      const float* a = &acc[h][4 * g];
      stmatrix_x4(stg + st_row * 128 + (((g - 8 + st_chunk) ^ (st_row & 7)) * 16),
                  pack_bf16(a[0], a[1]) ^ sgn, pack_bf16(a[2], a[3]) ^ sgn, pack_bf16(a[4], a[5]) ^ sgn, pack_bf16(a[6], a[7]) ^ sgn);
    }
    __syncwarp();
#pragma unroll
    for (int t = 0; t < 4; t++) {
      const int idx = t * 32 + lane, row = idx >> 3, ch = idx & 7;
      if (ch < 6) {
        uint4 v = lds128(stg + row * 128 + ((ch ^ (row & 7)) * 16));
        *reinterpret_cast<uint4*>(outp + (size_t)(row0 + row) * 448 + 64 + ch * 8) = v;
      }
    }
    __syncwarp();
  }
}

template <bool HALF>
__device__ __forceinline__ void k1_unit_gu(uint32_t sb, uint32_t bar_full, uint32_t bar_empty, int warp, int lane, int mt, int unit, int fb, int hsel) {
  const uint32_t stg = sb + K1_STG_OFF + warp * 2048;
  const int wq = warp & 3;
  const int st_row = (lane & 7) + 8 * ((lane >> 3) & 1);
  const int st_chunk = lane >> 4;
  constexpr int NH = HALF ? 1 : 2;
  float acc[NH][64];
#pragma unroll 1
  for (int kb = 0; kb < 7; kb++) {
    const int s = unit * 7 + kb;
    const int slot = s % K1_NS; const uint32_t ph = (s / K1_NS) & 1;
    mbar_wait(bar_full + 8 * slot, ph);
    if (kb == 0 && (threadIdx.x & 127) == 0) DBG(0, 4 + 3 * unit);
    wg_fence();
    const uint64_t da = make_desc(sb + kb * 16384 + (HALF ? hsel * 8192 : 0), 16, 1024);
    const uint64_t db = make_desc(sb + K1_B_OFF + slot * 16384, 8192, 1024);
#pragma unroll
    for (int k = 0; k < 4; k++) {
#pragma unroll
      for (int h = 0; h < NH; h++) wgmma_n128_tb(acc[h], da + h * 512 + k * 2, db + k * 128, (kb | k) != 0);
    }
    wg_commit();
    if (kb > 0) { wg_wait<1>(); k1_release(bar_empty, s - 1, lane); }
  }
  wg_wait<0>();
  k1_release(bar_empty, unit * 7 + 6, lane);
  if ((threadIdx.x & 127) == 0) DBG(0, 5 + 3 * unit);
  __nv_bfloat16* outp = g_h + (size_t)(mt * 128) * 1792 + fb * 64;
#pragma unroll
  for (int h = 0; h < NH; h++) {
    const int row0 = (HALF ? hsel : h) * 64 + wq * 16;
    uint32_t pk[16];
#pragma unroll
    for (int i = 0; i < 16; i++) {
      const uint32_t g2 = pack_bf16(acc[h][2 * i], acc[h][2 * i + 1]);
      const uint32_t u2 = pack_bf16(acc[h][32 + 2 * i], acc[h][32 + 2 * i + 1]);
      const uint32_t a2 = pack_bf16(gelu_tanh(bf_lo(g2)), gelu_tanh(bf_hi(g2)));
      pk[i] = hmul2_bf16(a2, u2);
    }
#pragma unroll
    for (int g = 0; g < 8; g += 2)
      stmatrix_x4(stg + st_row * 128 + (((g + st_chunk) ^ (st_row & 7)) * 16), pk[2 * g], pk[2 * g + 1], pk[2 * g + 2], pk[2 * g + 3]);
    __syncwarp();
#pragma unroll
    for (int t = 0; t < 4; t++) {
      const int idx = t * 32 + lane, row = idx >> 3, ch = idx & 7;
      uint4 v = lds128(stg + row * 128 + ((ch ^ (row & 7)) * 16));
      *reinterpret_cast<uint4*>(outp + (size_t)(row0 + row) * 1792 + ch * 8) = v;
    }
    __syncwarp();
  }
}

struct PfPtrs { const uint8_t* wr; const uint8_t* wi; const uint8_t* wg; const uint8_t* wu; const uint8_t* wd; const uint8_t* cr; const uint8_t* ci; };

__global__ void __cluster_dims__(2, 1, 1) __launch_bounds__(384, 1)
k1_kernel(const __grid_constant__ CUtensorMap tm_wr, const __grid_constant__ CUtensorMap tm_wi,
          const __grid_constant__ CUtensorMap tm_wg, const __grid_constant__ CUtensorMap tm_wu,
          const __nv_bfloat16* __restrict__ x, const PfPtrs pf) {
  extern __shared__ uint8_t smem_raw[];
  const uint32_t sb = (s2u(smem_raw) + 1023) & ~1023u;
  const int tid = threadIdx.x, warp = tid >> 5, lane = tid & 31;
  uint32_t rank;
  asm volatile("mov.u32 %0, %%cluster_ctarank;" : "=r"(rank));
  const int cid = blockIdx.x >> 1;
  const int p = cid >> 3, j = cid & 7;
  const int mt = 2 * p + (int)rank;
  const uint32_t bar_full = sb + K1_BAR_OFF;
  const uint32_t bar_empty = bar_full + 8 * K1_NS;
  const int fb_base = 7 * (j >> 1);
  const int fb0 = fb_base + ((j & 1) ? 4 : 0);
  const int fbh = fb_base + 3;
  const CUtensorMap* tw = (j < 4) ? &tm_wr : &tm_wi;
  const CUtensorMap* tgu = rank ? &tm_wu : &tm_wg;

  if (tid == 0) DBG(0, 0);
  if (tid == 256) {
    for (int i = 0; i < K1_NS; i++) { mbar_init(bar_full + 8 * i, 1); mbar_init(bar_empty + 8 * i, 8); }
    asm volatile("fence.mbarrier_init.release.cluster;" ::: "memory");
    prefetch_tmap(tw);
    prefetch_tmap(tgu);
    const int b = blockIdx.x;
    l2_prefetch(pf.wr + b * 3136, 3136);
    l2_prefetch(pf.wi + b * 3136, 3136);
    l2_prefetch(pf.wg + b * 12544, 12544);
    l2_prefetch(pf.wu + b * 12544, 12544);
    if (b < 64) g_flags[b] = 0;
  }
  __syncwarp();
  cluster_arrive_relaxed();
  pdl_launch();

  if (warp >= 8) {
    reg_dec<40>();
    cluster_wait();
    if (tid == 256) {
      int slot = 0; uint32_t ph = 0;
      for (int s = 0; s < 35; s++) {
        const int unit = s / 7, kb = s - unit * 7;
        if (s >= K1_NS) mbar_wait(bar_empty + 8 * slot, ph ^ 1);
        DBG(0, 20 + s);
        const uint32_t dst = sb + K1_B_OFF + slot * 16384;
        if (unit == 0) {
          mbar_expect(bar_full + 8 * slot, 14336);
          tma2d_mc(dst + rank * 7168, tw, kb * 64, (j & 3) * 112 + rank * 56, bar_full + 8 * slot, 3);
        } else {
          const int fb = (unit == 4) ? fbh : (fb0 + unit - 1);
          mbar_expect(bar_full + 8 * slot, 16384);
          tma2d_mc(dst + rank * 8192, tgu, fb * 64, kb * 64, bar_full + 8 * slot, 3);
        }
        if (s >= K1_NS && s < K1_NS + 16) {
          const int i = s - K1_NS;
          l2_prefetch(pf.cr + (size_t)blockIdx.x * 65536 + i * 4096, 4096);
          l2_prefetch(pf.ci + (size_t)blockIdx.x * 65536 + i * 4096, 4096);
          if (i == 0) l2_prefetch(pf.wd + blockIdx.x * 12544, 12544);
        }
        if (++slot == K1_NS) { slot = 0; ph ^= 1; }
      }
    }
  } else {
    reg_inc<232>();
    const int wg = warp >> 2;
    {
      const int c = lane & 7;
      uint4 v[4][7];
#pragma unroll
      for (int pass = 0; pass < 4; pass++) {
        const int r = warp * 16 + pass * 4 + (lane >> 3);
        const uint4* src = reinterpret_cast<const uint4*>(x + (size_t)(mt * 128 + r) * 448) + c;
#pragma unroll
        for (int b = 0; b < 7; b++) v[pass][b] = __ldg(src + b * 8);
      }
      float mean[4], rinv[4];
#pragma unroll
      for (int pass = 0; pass < 4; pass++) {
        float s0 = 0.f, s1 = 0.f, s2 = 0.f, s3 = 0.f;
#pragma unroll
        for (int b = 0; b < 7; b++) {
          s0 += bf_lo(v[pass][b].x) + bf_hi(v[pass][b].x); s1 += bf_lo(v[pass][b].y) + bf_hi(v[pass][b].y);
          s2 += bf_lo(v[pass][b].z) + bf_hi(v[pass][b].z); s3 += bf_lo(v[pass][b].w) + bf_hi(v[pass][b].w);
        }
        mean[pass] = (s0 + s1) + (s2 + s3);
      }
      if (tid == 0) DBG(0, 2);
#pragma unroll
      for (int o = 1; o < 8; o <<= 1) {
#pragma unroll
        for (int pass = 0; pass < 4; pass++) mean[pass] += __shfl_xor_sync(0xffffffffu, mean[pass], o);
      }
#pragma unroll
      for (int pass = 0; pass < 4; pass++) {
        mean[pass] *= (1.0f / 448.0f);
        const float m = mean[pass];
        float q0 = 0.f, q1 = 0.f, q2 = 0.f, q3 = 0.f;
#pragma unroll
        for (int b = 0; b < 7; b++) {
          float d;
          d = bf_lo(v[pass][b].x) - m; q0 = fmaf(d, d, q0); d = bf_hi(v[pass][b].x) - m; q1 = fmaf(d, d, q1);
          d = bf_lo(v[pass][b].y) - m; q2 = fmaf(d, d, q2); d = bf_hi(v[pass][b].y) - m; q3 = fmaf(d, d, q3);
          d = bf_lo(v[pass][b].z) - m; q0 = fmaf(d, d, q0); d = bf_hi(v[pass][b].z) - m; q1 = fmaf(d, d, q1);
          d = bf_lo(v[pass][b].w) - m; q2 = fmaf(d, d, q2); d = bf_hi(v[pass][b].w) - m; q3 = fmaf(d, d, q3);
        }
        rinv[pass] = (q0 + q1) + (q2 + q3);
      }
#pragma unroll
      for (int o = 1; o < 8; o <<= 1) {
#pragma unroll
        for (int pass = 0; pass < 4; pass++) rinv[pass] += __shfl_xor_sync(0xffffffffu, rinv[pass], o);
      }
#pragma unroll
      for (int pass = 0; pass < 4; pass++) {
        const float var_b = rbf(rinv[pass] * (1.0f / 448.0f));
        const float den = rbf(sqrtf(rbf(var_b + 1e-5f)));
        const float ri = 1.0f / den;
        const uint32_t m2 = pack_bf16(mean[pass], mean[pass]);
        const int r = warp * 16 + pass * 4 + (lane >> 3);
        const uint32_t a0 = sb + r * 128 + ((c ^ (r & 7)) * 16);
#pragma unroll
        for (int b = 0; b < 7; b++) {
          uint32_t w4[4] = {v[pass][b].x, v[pass][b].y, v[pass][b].z, v[pass][b].w};
#pragma unroll
          for (int q = 0; q < 4; q++) {
            const uint32_t dw = hsub2_bf16(w4[q], m2);
            w4[q] = pack_bf16(bf_lo(dw) * ri, bf_hi(dw) * ri);
          }
          sts128(a0 + b * 16384, make_uint4(w4[0], w4[1], w4[2], w4[3]));
        }
      }
    }
    asm volatile("fence.proxy.async.shared::cta;" ::: "memory");
    named_bar(1, 256);
    cluster_wait();
    if (tid == 0) DBG(0, 3);

    if (wg == 0) {
      k1_unit_ab(sb, bar_full, bar_empty, warp, lane, mt, j);
      if (tid == 0) DBG(0, 6);
      k1_unit_gu<false>(sb, bar_full, bar_empty, warp, lane, mt, 2, fb0 + 1, 0);
      if (tid == 0) DBG(0, 12);
      k1_unit_gu<true>(sb, bar_full, bar_empty, warp, lane, mt, 4, fbh, j & 1);
      if (tid == 0) DBG(0, 18);
    } else {
      k1_unit_gu<false>(sb, bar_full, bar_empty, warp, lane, mt, 1, fb0, 0);
      if (tid == 128) DBG(0, 9);
      k1_unit_gu<false>(sb, bar_full, bar_empty, warp, lane, mt, 3, fb0 + 2, 0);
      if (tid == 128) DBG(0, 15);
    }
  }
  cluster_arrive_relaxed();
  cluster_wait();
}

constexpr int K2_NS = 4;
constexpr int K2_STAGE = 16384 + 32768;
constexpr int K2_BAR_OFF = K2_NS * K2_STAGE;
constexpr int K2_SMEM = K2_BAR_OFF + 256 + 1024;

__device__ __forceinline__ void flag_signal_wait(unsigned int* flag, unsigned int target, bool do_wait) {
  __threadfence();
  named_bar(1, 256);
  if (threadIdx.x == 0) {
    atomicAdd(flag, 1u);
    if (do_wait) {
      int it = 0;
      while (true) {
        unsigned int v;
        asm volatile("ld.acquire.gpu.global.u32 %0, [%1];" : "=r"(v) : "l"(flag) : "memory");
        if (v >= target) break;
        if (++it > (1 << 22)) __trap();
      }
    }
  }
  if (do_wait) named_bar(1, 256);
}

template <int Q>
__device__ __forceinline__ void k2_y_epilogue(float (&acc)[112], int tile, int tid) {
  constexpr int G0 = (Q == 0) ? 0 : (Q == 1 ? 10 : 19);
  constexpr int G1 = (Q == 0) ? 10 : (Q == 1 ? 19 : 28);
  float4* part = g_part + (size_t)tile * (3 * 28 * 256) + tid;
#pragma unroll
  for (int g = 0; g < 28; g++) {
    if (g < G0 || g >= G1) part[(Q * 28 + g) * 256] = make_float4(acc[4 * g], acc[4 * g + 1], acc[4 * g + 2], acc[4 * g + 3]);
  }
  flag_signal_wait(&g_flags[tile], 3u, true);
  if (tid == 0) DBG(1, 30);
  constexpr int QA = (Q + 1) % 3, QB = (Q + 2) % 3;
  float4 va[G1 - G0], vb[G1 - G0];
#pragma unroll
  for (int g = G0; g < G1; g++) { va[g - G0] = __ldcg(&part[(QA * 28 + g) * 256]); vb[g - G0] = __ldcg(&part[(QB * 28 + g) * 256]); }
  uint2* sp = g_s + (size_t)tile * (28 * 256) + tid;
#pragma unroll
  for (int g = G0; g < G1; g++) {
    const float4 a = va[g - G0], b = vb[g - G0];
    sp[g * 256] = make_uint2(pack_bf16(acc[4 * g] + a.x + b.x, acc[4 * g + 1] + a.y + b.y),
                             pack_bf16(acc[4 * g + 2] + a.z + b.z, acc[4 * g + 3] + a.w + b.w));
  }
  flag_signal_wait(&g_flags[32 + tile], 0u, false);
}

__global__ void __cluster_dims__(2, 1, 1) __launch_bounds__(384, 1)
k2_kernel(const __grid_constant__ CUtensorMap tm_cr, const __grid_constant__ CUtensorMap tm_ci, const __grid_constant__ CUtensorMap tm_h,
          const __grid_constant__ CUtensorMap tm_ab, const __grid_constant__ CUtensorMap tm_wd,
          const __nv_bfloat16* __restrict__ x, __nv_bfloat16* __restrict__ out) {
  extern __shared__ uint8_t smem_raw[];
  const uint32_t sb = (s2u(smem_raw) + 1023) & ~1023u;
  const int tid = threadIdx.x, warp = tid >> 5, lane = tid & 31;
  uint32_t rank;
  asm volatile("mov.u32 %0, %%cluster_ctarank;" : "=r"(rank));
  const int cid = blockIdx.x >> 1;
  const int q = cid & 3, n = (cid >> 2) & 1, p = cid >> 3;
  const int mt = 2 * p + (int)rank;
  const int tile = mt * 2 + n;
  const uint32_t bar_full = sb + K2_BAR_OFF;
  const uint32_t bar_empty = bar_full + 8 * K2_NS;
  const int g0 = (q == 0) ? 0 : (q == 1 ? 22 : (q == 2 ? 43 : 64));
  const int nkb = (q == 0) ? 22 : (q == 3 ? 28 : 21);

  if (tid == 0) DBG(1, 0);
  if (tid == 256) {
    for (int i = 0; i < K2_NS; i++) { mbar_init(bar_full + 8 * i, 1); mbar_init(bar_empty + 8 * i, 16); }
    asm volatile("fence.mbarrier_init.release.cluster;" ::: "memory");
    if (q == 3) { prefetch_tmap(&tm_h); prefetch_tmap(&tm_wd); }
    else { prefetch_tmap(&tm_cr); prefetch_tmap(&tm_ci); prefetch_tmap(&tm_ab); }
  }
  __syncwarp();
  cluster_arrive_relaxed();
  cluster_wait();

  if (warp >= 8) {
    reg_dec<40>();
    if (tid == 256) {
      auto load_a = [&](int g, uint32_t dst, uint32_t fb) {
        if (g < 32) tma2d(dst, &tm_cr, g * 64, mt * 128, fb);
        else if (g < 64) tma2d(dst, &tm_ci, (g - 32) * 64, mt * 128, fb);
        else tma2d(dst, &tm_h, (g - 64) * 64, mt * 128, fb);
      };
      auto load_b = [&](int g, uint32_t dst, uint32_t fb) {
        const CUtensorMap* tb = (g < 64) ? &tm_ab : &tm_wd;
        const int kbrow = (g < 64) ? g * 64 : (g - 64) * 64;
        tma3d_mc(dst + 16384 + (2 * rank) * 8192, tb, (2 * rank) * 64, n, kbrow, fb, 3);
        tma3d_mc(dst + 16384 + (2 * rank + 1) * 8192, tb, (2 * rank + 1) * 64, n, kbrow, fb, 3);
      };
      for (int s = 0; s < K2_NS; s++) {
        mbar_expect(bar_full + 8 * s, K2_STAGE);
        if (q < 3) load_a(g0 + s, sb + s * K2_STAGE, bar_full + 8 * s); else load_b(g0 + s, sb + s * K2_STAGE, bar_full + 8 * s);
      }
      pdl_wait();
      DBG(1, 31);
      for (int s = 0; s < K2_NS; s++) {
        if (q < 3) load_b(g0 + s, sb + s * K2_STAGE, bar_full + 8 * s); else load_a(g0 + s, sb + s * K2_STAGE, bar_full + 8 * s);
      }
      int slot = 0; uint32_t ph = 0;
      for (int s = K2_NS; s < nkb; s++) {
        mbar_wait(bar_empty + 8 * slot, ph);
        DBG(1, 32 + s);
        const uint32_t dst = sb + slot * K2_STAGE;
        const uint32_t fb = bar_full + 8 * slot;
        mbar_expect(fb, K2_STAGE);
        load_a(g0 + s, dst, fb);
        load_b(g0 + s, dst, fb);
        if (++slot == K2_NS) { slot = 0; ph ^= 1; }
      }
    }
  } else {
    reg_inc<232>();
    const int wg = warp >> 2;
    float acc[112];
    int slot = 0; uint32_t ph = 0;
#pragma unroll 1
    for (int s = 0; s < nkb; s++) {
      mbar_wait(bar_full + 8 * slot, ph);
      if (tid == 0) DBG(1, 1 + s);
      wg_fence();
      const uint64_t da = make_desc(sb + slot * K2_STAGE + wg * 8192, 16, 1024);
      const uint64_t db = make_desc(sb + slot * K2_STAGE + 16384, 8192, 1024);
#pragma unroll
      for (int k = 0; k < 4; k++) wgmma_n224_tb(acc, da + k * 2, db + k * 128, (s | k) != 0);
      wg_commit();
      if (s > 0) {
        wg_wait<1>();
        const int ps = (slot + K2_NS - 1) % K2_NS;
        if (lane == 0) { mbar_arrive_cluster(bar_empty + 8 * ps, 0); mbar_arrive_cluster(bar_empty + 8 * ps, 1); }
      }
      if (++slot == K2_NS) { slot = 0; ph ^= 1; }
    }
    wg_wait<0>();
    pdl_wait();
    if (tid == 0) DBG(1, 29);
    if (q == 0) k2_y_epilogue<0>(acc, tile, tid);
    else if (q == 1) k2_y_epilogue<1>(acc, tile, tid);
    else if (q == 2) k2_y_epilogue<2>(acc, tile, tid);
    else {
      const int row_base = mt * 128 + wg * 64 + (warp & 3) * 16 + (lane >> 2);
      const int col_base = n * 224 + (lane & 3) * 2;
      uint32_t gw[56];
#pragma unroll
      for (int i = 0; i < 56; i++) {
        const uint32_t f2 = pack_bf16(acc[2 * i], acc[2 * i + 1]);
        gw[i] = pack_bf16(silu_f(bf_lo(f2)), silu_f(bf_hi(f2)));
      }
      const uint32_t* xp0 = reinterpret_cast<const uint32_t*>(x + (size_t)row_base * 448 + col_base);
      const uint32_t* xp1 = xp0 + 8 * 224;
      if (tid == 0) {
        int it = 0;
        while (true) {
          unsigned int v;
          asm volatile("ld.acquire.gpu.global.u32 %0, [%1];" : "=r"(v) : "l"(&g_flags[32 + tile]) : "memory");
          if (v >= 3u) break;
          if (++it > (1 << 22)) __trap();
        }
      }
      named_bar(1, 256);
      if (tid == 0) DBG(1, 30);
      const uint2* sp = g_s + (size_t)tile * (28 * 256) + tid;
      uint32_t* op0 = reinterpret_cast<uint32_t*>(out + (size_t)row_base * 448 + col_base);
      uint32_t* op1 = op0 + 8 * 224;
      uint2 sv[28];
      uint32_t xw[56];
#pragma unroll
      for (int g = 0; g < 28; g++) {
        sv[g] = __ldcg(&sp[g * 256]);
        xw[2 * g] = __ldcg(xp0 + g * 4);
        xw[2 * g + 1] = __ldcg(xp1 + g * 4);
      }
#pragma unroll
      for (int g = 0; g < 28; g++) {
        const uint32_t o0 = hadd2_bf16(xw[2 * g], hmul2_bf16(sv[g].x, gw[2 * g]));
        const uint32_t o1 = hadd2_bf16(xw[2 * g + 1], hmul2_bf16(sv[g].y, gw[2 * g + 1]));
        op0[g * 4] = o0;
        op1[g * 4] = o1;
      }
    }
    if (tid == 0) DBG(1, 63);
  }
  cluster_arrive_relaxed();
  cluster_wait();
}

typedef CUresult (*EncFn)(CUtensorMap*, CUtensorMapDataType, cuuint32_t, void*, const cuuint64_t*, const cuuint64_t*, const cuuint32_t*,
                          const cuuint32_t*, CUtensorMapInterleave, CUtensorMapSwizzle, CUtensorMapL2promotion, CUtensorMapFloatOOBfill);

void make2d(EncFn enc, CUtensorMap* tm, const void* ptr, uint64_t cols, uint64_t rows, uint32_t bc, uint32_t br) {
  cuuint64_t gd[2] = {cols, rows};
  cuuint64_t gs[1] = {cols * 2};
  cuuint32_t bd[2] = {bc, br};
  cuuint32_t es[2] = {1, 1};
  enc(tm, CU_TENSOR_MAP_DATA_TYPE_BFLOAT16, 2, const_cast<void*>(ptr), gd, gs, bd, es, CU_TENSOR_MAP_INTERLEAVE_NONE,
      CU_TENSOR_MAP_SWIZZLE_128B, CU_TENSOR_MAP_L2_PROMOTION_L2_128B, CU_TENSOR_MAP_FLOAT_OOB_FILL_NONE);
}
void make3d_half(EncFn enc, CUtensorMap* tm, const void* ptr, uint64_t rows) {
  cuuint64_t gd[3] = {224, 2, rows};
  cuuint64_t gs[2] = {448, 896};
  cuuint32_t bd[3] = {64, 1, 64};
  cuuint32_t es[3] = {1, 1, 1};
  enc(tm, CU_TENSOR_MAP_DATA_TYPE_BFLOAT16, 3, const_cast<void*>(ptr), gd, gs, bd, es, CU_TENSOR_MAP_INTERLEAVE_NONE,
      CU_TENSOR_MAP_SWIZZLE_128B, CU_TENSOR_MAP_L2_PROMOTION_L2_128B, CU_TENSOR_MAP_FLOAT_OOB_FILL_NONE);
}

struct Maps { CUtensorMap wr, wi, wg, wu, cr, ci, h, ab, wd; };

}

extern "C" void kernel_launch(void* const* d_in, const int* in_sizes, int n_in, void* d_out, int out_size) {
  (void)in_sizes; (void)n_in; (void)out_size;
  static Maps maps;
  static const void* cached[9] = {nullptr};
  static bool attr_done = false;
  bool same = true;
  for (int i = 0; i < 9; i++) same = same && (cached[i] == d_in[i]);
  if (!same) {
    void* fn = nullptr;
    cudaDriverEntryPointQueryResult qr;
    cudaGetDriverEntryPoint("cuTensorMapEncodeTiled", &fn, cudaEnableDefault, &qr);
    EncFn enc = (EncFn)fn;
    void *p_ab = nullptr, *p_h = nullptr;
    cudaGetSymbolAddress(&p_ab, g_ab);
    cudaGetSymbolAddress(&p_h, g_h);
    make2d(enc, &maps.cr, d_in[1], 2048, 2048, 64, 128);
    make2d(enc, &maps.ci, d_in[2], 2048, 2048, 64, 128);
    make2d(enc, &maps.wr, d_in[3], 448, 448, 64, 56);
    make2d(enc, &maps.wi, d_in[4], 448, 448, 64, 56);
    make2d(enc, &maps.wg, d_in[6], 1792, 448, 64, 64);
    make2d(enc, &maps.wu, d_in[7], 1792, 448, 64, 64);
    make3d_half(enc, &maps.wd, d_in[8], 1792);
    make2d(enc, &maps.h, p_h, 1792, 2048, 64, 128);
    make3d_half(enc, &maps.ab, p_ab, 4096);
    for (int i = 0; i < 9; i++) cached[i] = d_in[i];
  }
  if (!attr_done) {
    cudaFuncSetAttribute(k1_kernel, cudaFuncAttributeMaxDynamicSharedMemorySize, K1_SMEM);
    cudaFuncSetAttribute(k2_kernel, cudaFuncAttributeMaxDynamicSharedMemorySize, K2_SMEM);
    attr_done = true;
  }
  PfPtrs pf;
  pf.wr = (const uint8_t*)d_in[3]; pf.wi = (const uint8_t*)d_in[4]; pf.wg = (const uint8_t*)d_in[6]; pf.wu = (const uint8_t*)d_in[7];
  pf.wd = (const uint8_t*)d_in[8]; pf.cr = (const uint8_t*)d_in[1]; pf.ci = (const uint8_t*)d_in[2];
  k1_kernel<<<128, 384, K1_SMEM>>>(maps.wr, maps.wi, maps.wg, maps.wu, (const __nv_bfloat16*)d_in[0], pf);

  cudaLaunchConfig_t cfg = {};
  cfg.gridDim = dim3(128); cfg.blockDim = dim3(384); cfg.dynamicSmemBytes = K2_SMEM; cfg.stream = cudaStreamPerThread;
  cudaLaunchAttribute at[1];
  at[0].id = cudaLaunchAttributeProgrammaticStreamSerialization;
  at[0].val.programmaticStreamSerializationAllowed = 1;
  cfg.attrs = at; cfg.numAttrs = 1;
  cudaLaunchKernelEx(&cfg, k2_kernel, maps.cr, maps.ci, maps.h, maps.ab, maps.wd, (const __nv_bfloat16*)d_in[0], (__nv_bfloat16*)d_out);
}
```

```cpp
#include <cuda_runtime.h>
#include <cuda_bf16.h>
#include <cuda.h>
#include <stdint.h>

namespace {

__device__ __align__(1024) __nv_bfloat16 g_ab[4096 * 448];
__device__ __align__(1024) __nv_bfloat16 g_h[2048 * 1792];
__device__ float4 g_part[32 * 3 * 28 * 256];
__device__ __align__(1024) __nv_bfloat16 g_s[2048 * 448];
__device__ unsigned int g_flags[64];

#define DBG(k, i) do {} while (0)

__device__ __forceinline__ uint32_t s2u(const void* p) { return (uint32_t)__cvta_generic_to_shared(p); }
__device__ __forceinline__ void mbar_init(uint32_t b, int c) { asm volatile("mbarrier.init.shared::cta.b64 [%0], %1;" ::"r"(b), "r"(c)); }
__device__ __forceinline__ void mbar_expect(uint32_t b, uint32_t bytes) {
  asm volatile("mbarrier.arrive.expect_tx.shared::cta.b64 _, [%0], %1;" ::"r"(b), "r"(bytes) : "memory");
}
__device__ __forceinline__ void mbar_wait(uint32_t b, uint32_t ph) {
  uint32_t done = 0;
  int it = 0;
  while (true) {
    asm volatile("{.reg .pred p; mbarrier.try_wait.parity.shared::cta.b64 p, [%1], %2; selp.u32 %0,1,0,p;}" : "=r"(done) : "r"(b), "r"(ph) : "memory");
    if (done) break;
    if (++it > (1 << 22)) __trap();
  }
}
__device__ __forceinline__ void mbar_arrive_cluster(uint32_t b, uint32_t cta) {
  uint32_t r;
  asm volatile("mapa.shared::cluster.u32 %0, %1, %2;" : "=r"(r) : "r"(b), "r"(cta));
  asm volatile("mbarrier.arrive.shared::cluster.b64 _, [%0];" ::"r"(r) : "memory");
}
__device__ __forceinline__ void tma2d(uint32_t dst, const CUtensorMap* m, int c0, int c1, uint32_t bar) {
  asm volatile("cp.async.bulk.tensor.2d.shared::cluster.global.mbarrier::complete_tx::bytes [%0], [%1, {%3,%4}], [%2];" ::"r"(dst), "l"(m), "r"(bar), "r"(c0), "r"(c1) : "memory");
}
__device__ __forceinline__ void tma2d_mc(uint32_t dst, const CUtensorMap* m, int c0, int c1, uint32_t bar, uint16_t mask) {
  asm volatile("cp.async.bulk.tensor.2d.shared::cluster.global.mbarrier::complete_tx::bytes.multicast::cluster [%0], [%1, {%3,%4}], [%2], %5;" ::"r"(dst), "l"(m), "r"(bar), "r"(c0), "r"(c1), "h"(mask) : "memory");
}
__device__ __forceinline__ void tma3d_mc(uint32_t dst, const CUtensorMap* m, int c0, int c1, int c2, uint32_t bar, uint16_t mask) {
  asm volatile("cp.async.bulk.tensor.3d.shared::cluster.global.mbarrier::complete_tx::bytes.multicast::cluster [%0], [%1, {%3,%4,%5}], [%2], %6;" ::"r"(dst), "l"(m), "r"(bar), "r"(c0), "r"(c1), "r"(c2), "h"(mask) : "memory");
}
__device__ __forceinline__ void prefetch_tmap(const CUtensorMap* m) { asm volatile("prefetch.tensormap [%0];" ::"l"(m) : "memory"); }
__device__ __forceinline__ void l2_prefetch(const void* p, uint32_t bytes) {
  asm volatile("cp.async.bulk.prefetch.L2.global [%0], %1;" ::"l"(p), "r"(bytes) : "memory");
}
__device__ __forceinline__ void cluster_arrive_relaxed() { asm volatile("barrier.cluster.arrive.relaxed.aligned;" ::: "memory"); }
__device__ __forceinline__ void cluster_wait() { asm volatile("barrier.cluster.wait.aligned;" ::: "memory"); }
__device__ __forceinline__ void wg_fence() { asm volatile("wgmma.fence.sync.aligned;" ::: "memory"); }
__device__ __forceinline__ void wg_commit() { asm volatile("wgmma.commit_group.sync.aligned;" ::: "memory"); }
template <int N> __device__ __forceinline__ void wg_wait() { asm volatile("wgmma.wait_group.sync.aligned %0;" ::"n"(N) : "memory"); }
__device__ __forceinline__ void named_bar(int id, int n) { asm volatile("bar.sync %0, %1;" ::"r"(id), "r"(n) : "memory"); }
template <int N> __device__ __forceinline__ void reg_inc() { asm volatile("setmaxnreg.inc.sync.aligned.u32 %0;" ::"n"(N)); }
template <int N> __device__ __forceinline__ void reg_dec() { asm volatile("setmaxnreg.dec.sync.aligned.u32 %0;" ::"n"(N)); }
__device__ __forceinline__ void pdl_wait() { asm volatile("griddepcontrol.wait;" ::: "memory"); }
__device__ __forceinline__ void pdl_launch() { asm volatile("griddepcontrol.launch_dependents;" ::: "memory"); }

__device__ __forceinline__ uint64_t make_desc(uint32_t addr, uint32_t lbo, uint32_t sbo) {
  return (uint64_t)((addr & 0x3FFFF) >> 4) | ((uint64_t)(lbo >> 4) << 16) | ((uint64_t)(sbo >> 4) << 32) | (1ull << 62);
}
__device__ __forceinline__ void stmatrix_x4(uint32_t addr, uint32_t r0, uint32_t r1, uint32_t r2, uint32_t r3) {
  asm volatile("stmatrix.sync.aligned.m8n8.x4.shared.b16 [%0], {%1,%2,%3,%4};" ::"r"(addr), "r"(r0), "r"(r1), "r"(r2), "r"(r3) : "memory");
}
__device__ __forceinline__ uint4 lds128(uint32_t a) {
  uint4 v;
  asm volatile("ld.shared.v4.u32 {%0,%1,%2,%3}, [%4];" : "=r"(v.x), "=r"(v.y), "=r"(v.z), "=r"(v.w) : "r"(a) : "memory");
  return v;
}
__device__ __forceinline__ void sts128(uint32_t a, uint4 v) {
  asm volatile("st.shared.v4.u32 [%0], {%1,%2,%3,%4};" ::"r"(a), "r"(v.x), "r"(v.y), "r"(v.z), "r"(v.w) : "memory");
}
__device__ __forceinline__ void stg128(void* p, uint4 v) {
  asm volatile("st.global.v4.u32 [%0], {%1,%2,%3,%4};" ::"l"(p), "r"(v.x), "r"(v.y), "r"(v.z), "r"(v.w) : "memory");
}
__device__ __forceinline__ uint32_t pack_bf16(float lo, float hi) {
  uint32_t r;
  asm("cvt.rn.bf16x2.f32 %0, %1, %2;" : "=r"(r) : "f"(hi), "f"(lo));
  return r;
}
__device__ __forceinline__ uint32_t hmul2_bf16(uint32_t a, uint32_t b) {
  uint32_t r;
  asm("mul.rn.bf16x2 %0, %1, %2;" : "=r"(r) : "r"(a), "r"(b));
  return r;
}
__device__ __forceinline__ uint32_t hsub2_bf16(uint32_t a, uint32_t b) {
  uint32_t r;
  asm("sub.rn.bf16x2 %0, %1, %2;" : "=r"(r) : "r"(a), "r"(b));
  return r;
}
__device__ __forceinline__ uint32_t hadd2_bf16(uint32_t a, uint32_t b) {
  uint32_t r;
  asm("add.rn.bf16x2 %0, %1, %2;" : "=r"(r) : "r"(a), "r"(b));
  return r;
}
__device__ __forceinline__ uint32_t hfma2_bf16(uint32_t a, uint32_t b, uint32_t c) {
  uint32_t r;
  asm("fma.rn.bf16x2 %0, %1, %2, %3;" : "=r"(r) : "r"(a), "r"(b), "r"(c));
  return r;
}
__device__ __forceinline__ bool mbar_test(uint32_t b, uint32_t ph) {
  uint32_t done;
  asm volatile("{.reg .pred p; mbarrier.test_wait.parity.shared::cta.b64 p, [%1], %2; selp.u32 %0,1,0,p;}" : "=r"(done) : "r"(b), "r"(ph) : "memory");
  return done != 0;
}
__device__ __forceinline__ uint4 ldg128_cg(const void* p) {
  uint4 v;
  asm volatile("ld.global.cg.v4.u32 {%0,%1,%2,%3}, [%4];" : "=r"(v.x), "=r"(v.y), "=r"(v.z), "=r"(v.w) : "l"(p) : "memory");
  return v;
}
__device__ __forceinline__ float bf_lo(uint32_t w) { return __uint_as_float(w << 16); }
__device__ __forceinline__ float bf_hi(uint32_t w) { return __uint_as_float(w & 0xffff0000u); }
__device__ __forceinline__ float rbf(float x) { return __bfloat162float(__float2bfloat16_rn(x)); }
__device__ __forceinline__ float ex2f(float x) { float r; asm("ex2.approx.ftz.f32 %0, %1;" : "=f"(r) : "f"(x)); return r; }
__device__ __forceinline__ float rcpf(float x) { float r; asm("rcp.approx.ftz.f32 %0, %1;" : "=f"(r) : "f"(x)); return r; }
__device__ __forceinline__ float gelu_tanh(float x) {
  const float c1 = -2.0f * 0.7978845608028654f * 1.4426950408889634f;
  const float c2 = c1 * 0.044715f;
  const float e = ex2f(x * fmaf(c2, x * x, c1));
  return x * rcpf(1.0f + e);
}
__device__ __forceinline__ float silu_f(float x) {
  const float e = ex2f(-1.4426950408889634f * x);
  return x * rcpf(1.0f + e);
}

__device__ __forceinline__ void wgmma_n128_tb(float (&d)[64], uint64_t da, uint64_t db, int scale_d) {
  asm volatile(
    "{\n.reg .pred p;\nsetp.ne.b32 p, %66, 0;\n"
    "wgmma.mma_async.sync.aligned.m64n128k16.f32.bf16.bf16 {%0, %1, %2, %3, %4, %5, %6, %7, %8, %9, %10, %11, %12, %13, %14, %15, %16, %17, %18, %19, %20, %21, %22, %23, %24, %25, %26, %27, %28, %29, %30, %31, %32, %33, %34, %35, %36, %37, %38, %39, %40, %41, %42, %43, %44, %45, %46, %47, %48, %49, %50, %51, %52, %53, %54, %55, %56, %57, %58, %59, %60, %61, %62, %63}, %64, %65, p, 1, 1, 0, 1;\n}\n"
    : "+f"(d[0]), "+f"(d[1]), "+f"(d[2]), "+f"(d[3]), "+f"(d[4]), "+f"(d[5]), "+f"(d[6]), "+f"(d[7]), "+f"(d[8]), "+f"(d[9]), "+f"(d[10]), "+f"(d[11]), "+f"(d[12]), "+f"(d[13]), "+f"(d[14]), "+f"(d[15]), "+f"(d[16]), "+f"(d[17]), "+f"(d[18]), "+f"(d[19]), "+f"(d[20]), "+f"(d[21]), "+f"(d[22]), "+f"(d[23]), "+f"(d[24]), "+f"(d[25]), "+f"(d[26]), "+f"(d[27]), "+f"(d[28]), "+f"(d[29]), "+f"(d[30]), "+f"(d[31]), "+f"(d[32]), "+f"(d[33]), "+f"(d[34]), "+f"(d[35]), "+f"(d[36]), "+f"(d[37]), "+f"(d[38]), "+f"(d[39]), "+f"(d[40]), "+f"(d[41]), "+f"(d[42]), "+f"(d[43]), "+f"(d[44]), "+f"(d[45]), "+f"(d[46]), "+f"(d[47]), "+f"(d[48]), "+f"(d[49]), "+f"(d[50]), "+f"(d[51]), "+f"(d[52]), "+f"(d[53]), "+f"(d[54]), "+f"(d[55]), "+f"(d[56]), "+f"(d[57]), "+f"(d[58]), "+f"(d[59]), "+f"(d[60]), "+f"(d[61]), "+f"(d[62]), "+f"(d[63])
    : "l"(da), "l"(db), "r"(scale_d));
}
__device__ __forceinline__ void wgmma_n112(float (&d)[56], uint64_t da, uint64_t db, int scale_d) {
  asm volatile(
    "{\n.reg .pred p;\nsetp.ne.b32 p, %58, 0;\n"
    "wgmma.mma_async.sync.aligned.m64n112k16.f32.bf16.bf16 {%0, %1, %2, %3, %4, %5, %6, %7, %8, %9, %10, %11, %12, %13, %14, %15, %16, %17, %18, %19, %20, %21, %22, %23, %24, %25, %26, %27, %28, %29, %30, %31, %32, %33, %34, %35, %36, %37, %38, %39, %40, %41, %42, %43, %44, %45, %46, %47, %48, %49, %50, %51, %52, %53, %54, %55}, %56, %57, p, 1, 1, 0, 0;\n}\n"
    : "+f"(d[0]), "+f"(d[1]), "+f"(d[2]), "+f"(d[3]), "+f"(d[4]), "+f"(d[5]), "+f"(d[6]), "+f"(d[7]), "+f"(d[8]), "+f"(d[9]), "+f"(d[10]), "+f"(d[11]), "+f"(d[12]), "+f"(d[13]), "+f"(d[14]), "+f"(d[15]), "+f"(d[16]), "+f"(d[17]), "+f"(d[18]), "+f"(d[19]), "+f"(d[20]), "+f"(d[21]), "+f"(d[22]), "+f"(d[23]), "+f"(d[24]), "+f"(d[25]), "+f"(d[26]), "+f"(d[27]), "+f"(d[28]), "+f"(d[29]), "+f"(d[30]), "+f"(d[31]), "+f"(d[32]), "+f"(d[33]), "+f"(d[34]), "+f"(d[35]), "+f"(d[36]), "+f"(d[37]), "+f"(d[38]), "+f"(d[39]), "+f"(d[40]), "+f"(d[41]), "+f"(d[42]), "+f"(d[43]), "+f"(d[44]), "+f"(d[45]), "+f"(d[46]), "+f"(d[47]), "+f"(d[48]), "+f"(d[49]), "+f"(d[50]), "+f"(d[51]), "+f"(d[52]), "+f"(d[53]), "+f"(d[54]), "+f"(d[55])
    : "l"(da), "l"(db), "r"(scale_d));
}
__device__ __forceinline__ void wgmma_n224_tb(float (&d)[112], uint64_t da, uint64_t db, int scale_d) {
  asm volatile(
    "{\n.reg .pred p;\nsetp.ne.b32 p, %114, 0;\n"
    "wgmma.mma_async.sync.aligned.m64n224k16.f32.bf16.bf16 {%0, %1, %2, %3, %4, %5, %6, %7, %8, %9, %10, %11, %12, %13, %14, %15, %16, %17, %18, %19, %20, %21, %22, %23, %24, %25, %26, %27, %28, %29, %30, %31, %32, %33, %34, %35, %36, %37, %38, %39, %40, %41, %42, %43, %44, %45, %46, %47, %48, %49, %50, %51, %52, %53, %54, %55, %56, %57, %58, %59, %60, %61, %62, %63, %64, %65, %66, %67, %68, %69, %70, %71, %72, %73, %74, %75, %76, %77, %78, %79, %80, %81, %82, %83, %84, %85, %86, %87, %88, %89, %90, %91, %92, %93, %94, %95, %96, %97, %98, %99, %100, %101, %102, %103, %104, %105, %106, %107, %108, %109, %110, %111}, %112, %113, p, 1, 1, 0, 1;\n}\n"
    : "+f"(d[0]), "+f"(d[1]), "+f"(d[2]), "+f"(d[3]), "+f"(d[4]), "+f"(d[5]), "+f"(d[6]), "+f"(d[7]), "+f"(d[8]), "+f"(d[9]), "+f"(d[10]), "+f"(d[11]), "+f"(d[12]), "+f"(d[13]), "+f"(d[14]), "+f"(d[15]), "+f"(d[16]), "+f"(d[17]), "+f"(d[18]), "+f"(d[19]), "+f"(d[20]), "+f"(d[21]), "+f"(d[22]), "+f"(d[23]), "+f"(d[24]), "+f"(d[25]), "+f"(d[26]), "+f"(d[27]), "+f"(d[28]), "+f"(d[29]), "+f"(d[30]), "+f"(d[31]), "+f"(d[32]), "+f"(d[33]), "+f"(d[34]), "+f"(d[35]), "+f"(d[36]), "+f"(d[37]), "+f"(d[38]), "+f"(d[39]), "+f"(d[40]), "+f"(d[41]), "+f"(d[42]), "+f"(d[43]), "+f"(d[44]), "+f"(d[45]), "+f"(d[46]), "+f"(d[47]), "+f"(d[48]), "+f"(d[49]), "+f"(d[50]), "+f"(d[51]), "+f"(d[52]), "+f"(d[53]), "+f"(d[54]), "+f"(d[55]), "+f"(d[56]), "+f"(d[57]), "+f"(d[58]), "+f"(d[59]), "+f"(d[60]), "+f"(d[61]), "+f"(d[62]), "+f"(d[63]), "+f"(d[64]), "+f"(d[65]), "+f"(d[66]), "+f"(d[67]), "+f"(d[68]), "+f"(d[69]), "+f"(d[70]), "+f"(d[71]), "+f"(d[72]), "+f"(d[73]), "+f"(d[74]), "+f"(d[75]), "+f"(d[76]), "+f"(d[77]), "+f"(d[78]), "+f"(d[79]), "+f"(d[80]), "+f"(d[81]), "+f"(d[82]), "+f"(d[83]), "+f"(d[84]), "+f"(d[85]), "+f"(d[86]), "+f"(d[87]), "+f"(d[88]), "+f"(d[89]), "+f"(d[90]), "+f"(d[91]), "+f"(d[92]), "+f"(d[93]), "+f"(d[94]), "+f"(d[95]), "+f"(d[96]), "+f"(d[97]), "+f"(d[98]), "+f"(d[99]), "+f"(d[100]), "+f"(d[101]), "+f"(d[102]), "+f"(d[103]), "+f"(d[104]), "+f"(d[105]), "+f"(d[106]), "+f"(d[107]), "+f"(d[108]), "+f"(d[109]), "+f"(d[110]), "+f"(d[111])
    : "l"(da), "l"(db), "r"(scale_d));
}

constexpr int K1_NS = 6;
constexpr int K1_A_BYTES = 7 * 16384;
constexpr int K1_B_OFF = K1_A_BYTES;
constexpr int K1_STG_OFF = K1_B_OFF + K1_NS * 16384;
constexpr int K1_BAR_OFF = K1_STG_OFF + 8 * 2048;
constexpr int K1_SMEM = K1_BAR_OFF + 256 + 1024;

__device__ __forceinline__ void k1_release(uint32_t bar_empty, int s, int lane) {
  if (lane == 0) { const int ps = s % K1_NS; mbar_arrive_cluster(bar_empty + 8 * ps, 0); mbar_arrive_cluster(bar_empty + 8 * ps, 1); }
}

__device__ __forceinline__ void k1_unit_ab(uint32_t sb, uint32_t bar_full, uint32_t bar_empty, int warp, int lane, int mt, int j) {
  const uint32_t stg = sb + K1_STG_OFF + warp * 2048;
  const int wq = warp & 3;
  const int st_row = (lane & 7) + 8 * ((lane >> 3) & 1);
  const int st_chunk = lane >> 4;
  float acc[2][56];
#pragma unroll 1
  for (int kb = 0; kb < 7; kb++) {
    const int s = kb;
    const int slot = s % K1_NS; const uint32_t ph = (s / K1_NS) & 1;
    bool released = (kb == 0);
    if (!mbar_test(bar_full + 8 * slot, ph)) {
      if (!released) { wg_wait<0>(); k1_release(bar_empty, s - 1, lane); released = true; }
      mbar_wait(bar_full + 8 * slot, ph);
    }
    if (kb == 0 && (threadIdx.x & 127) == 0) DBG(0, 4);
    wg_fence();
    const uint64_t da = make_desc(sb + kb * 16384, 16, 1024);
    const uint64_t db = make_desc(sb + K1_B_OFF + slot * 16384, 16, 1024);
#pragma unroll
    for (int k = 0; k < 4; k++) {
      wgmma_n112(acc[0], da + k * 2, db + k * 2, (kb | k) != 0);
      wgmma_n112(acc[1], da + 512 + k * 2, db + k * 2, (kb | k) != 0);
    }
    wg_commit();
    if (!released) { wg_wait<1>(); k1_release(bar_empty, s - 1, lane); }
  }
  wg_wait<0>();
  k1_release(bar_empty, 6, lane);
  if ((threadIdx.x & 127) == 0) DBG(0, 5);
  const uint32_t sgn = (j < 4) ? 0u : 0x80008000u;
  __nv_bfloat16* outp = g_ab + (size_t)((j < 4 ? 0 : 2048) + mt * 128) * 448 + (j & 3) * 112;
#pragma unroll
  for (int h = 0; h < 2; h++) {
    const int row0 = h * 64 + wq * 16;
#pragma unroll
    for (int g = 0; g < 8; g += 2) {
      const float* a = &acc[h][4 * g];
      stmatrix_x4(stg + st_row * 128 + (((g + st_chunk) ^ (st_row & 7)) * 16),
                  pack_bf16(a[0], a[1]) ^ sgn, pack_bf16(a[2], a[3]) ^ sgn, pack_bf16(a[4], a[5]) ^ sgn, pack_bf16(a[6], a[7]) ^ sgn);
    }
    __syncwarp();
    {
      uint4 v[4];
#pragma unroll
      for (int t = 0; t < 4; t++) { const int row = t * 4 + (lane >> 3); v[t] = lds128(stg + row * 128 + (((lane & 7) ^ (row & 7)) * 16)); }
      __nv_bfloat16* o = outp + (size_t)(row0 + (lane >> 3)) * 448 + (lane & 7) * 8;
#pragma unroll
      for (int t = 0; t < 4; t++) stg128(o + t * 4 * 448, v[t]);
    }
    __syncwarp();
#pragma unroll
    for (int g = 8; g < 14; g += 2) {
      const float* a = &acc[h][4 * g];
      stmatrix_x4(stg + st_row * 128 + (((g - 8 + st_chunk) ^ (st_row & 7)) * 16),
                  pack_bf16(a[0], a[1]) ^ sgn, pack_bf16(a[2], a[3]) ^ sgn, pack_bf16(a[4], a[5]) ^ sgn, pack_bf16(a[6], a[7]) ^ sgn);
    }
    __syncwarp();
    if ((lane & 7) < 6) {
      uint4 v[4];
#pragma unroll
      for (int t = 0; t < 4; t++) { const int row = t * 4 + (lane >> 3); v[t] = lds128(stg + row * 128 + (((lane & 7) ^ (row & 7)) * 16)); }
      __nv_bfloat16* o = outp + (size_t)(row0 + (lane >> 3)) * 448 + 64 + (lane & 7) * 8;
#pragma unroll
      for (int t = 0; t < 4; t++) stg128(o + t * 4 * 448, v[t]);
    }
    __syncwarp();
  }
}

template <bool HALF>
__device__ __forceinline__ void k1_unit_gu(uint32_t sb, uint32_t bar_full, uint32_t bar_empty, int warp, int lane, int mt, int unit, int fb, int hsel) {
  const uint32_t stg = sb + K1_STG_OFF + warp * 2048;
  const int wq = warp & 3;
  const int st_row = (lane & 7) + 8 * ((lane >> 3) & 1);
  const int st_chunk = lane >> 4;
  constexpr int NH = HALF ? 1 : 2;
  float acc[NH][64];
#pragma unroll 1
  for (int kb = 0; kb < 7; kb++) {
    const int s = unit * 7 + kb;
    const int slot = s % K1_NS; const uint32_t ph = (s / K1_NS) & 1;
    bool released = (kb == 0);
    if (!mbar_test(bar_full + 8 * slot, ph)) {
      if (!released) { wg_wait<0>(); k1_release(bar_empty, s - 1, lane); released = true; }
      mbar_wait(bar_full + 8 * slot, ph);
    }
    if (kb == 0 && (threadIdx.x & 127) == 0) DBG(0, 4 + 3 * unit);
    wg_fence();
    const uint64_t da = make_desc(sb + kb * 16384 + (HALF ? hsel * 8192 : 0), 16, 1024);
    const uint64_t db = make_desc(sb + K1_B_OFF + slot * 16384, 8192, 1024);
#pragma unroll
    for (int k = 0; k < 4; k++) {
#pragma unroll
      for (int h = 0; h < NH; h++) wgmma_n128_tb(acc[h], da + h * 512 + k * 2, db + k * 128, (kb | k) != 0);
    }
    wg_commit();
    if (!released) { wg_wait<1>(); k1_release(bar_empty, s - 1, lane); }
  }
  wg_wait<0>();
  k1_release(bar_empty, unit * 7 + 6, lane);
  if ((threadIdx.x & 127) == 0) DBG(0, 5 + 3 * unit);
  __nv_bfloat16* outp = g_h + (size_t)(mt * 128) * 1792 + fb * 64;
#pragma unroll
  for (int h = 0; h < NH; h++) {
    const int row0 = (HALF ? hsel : h) * 64 + wq * 16;
    uint32_t pk[16];
#pragma unroll
    for (int i = 0; i < 16; i++) {
      const uint32_t g2 = pack_bf16(acc[h][2 * i], acc[h][2 * i + 1]);
      const uint32_t u2 = pack_bf16(acc[h][32 + 2 * i], acc[h][32 + 2 * i + 1]);
      const uint32_t a2 = pack_bf16(gelu_tanh(bf_lo(g2)), gelu_tanh(bf_hi(g2)));
      pk[i] = hmul2_bf16(a2, u2);
    }
#pragma unroll
    for (int g = 0; g < 8; g += 2)
      stmatrix_x4(stg + st_row * 128 + (((g + st_chunk) ^ (st_row & 7)) * 16), pk[2 * g], pk[2 * g + 1], pk[2 * g + 2], pk[2 * g + 3]);
    __syncwarp();
    {
      uint4 v[4];
#pragma unroll
      for (int t = 0; t < 4; t++) { const int row = t * 4 + (lane >> 3); v[t] = lds128(stg + row * 128 + (((lane & 7) ^ (row & 7)) * 16)); }
      __nv_bfloat16* o = outp + (size_t)(row0 + (lane >> 3)) * 1792 + (lane & 7) * 8;
#pragma unroll
      for (int t = 0; t < 4; t++) stg128(o + t * 4 * 1792, v[t]);
    }
    __syncwarp();
  }
}

struct PfPtrs { const uint8_t* wr; const uint8_t* wi; const uint8_t* wg; const uint8_t* wu; const uint8_t* wd; const uint8_t* cr; const uint8_t* ci; };

__global__ void __cluster_dims__(2, 1, 1) __launch_bounds__(384, 1)
k1_kernel(const __grid_constant__ CUtensorMap tm_wr, const __grid_constant__ CUtensorMap tm_wi,
          const __grid_constant__ CUtensorMap tm_wg, const __grid_constant__ CUtensorMap tm_wu,
          const __nv_bfloat16* __restrict__ x, const PfPtrs pf) {
  extern __shared__ uint8_t smem_raw[];
  const uint32_t sb = (s2u(smem_raw) + 1023) & ~1023u;
  const int tid = threadIdx.x, warp = tid >> 5, lane = tid & 31;
  uint32_t rank;
  asm volatile("mov.u32 %0, %%cluster_ctarank;" : "=r"(rank));
  const int cid = blockIdx.x >> 1;
  const int p = cid >> 3, j = cid & 7;
  const int mt = 2 * p + (int)rank;
  const uint32_t bar_full = sb + K1_BAR_OFF;
  const uint32_t bar_empty = bar_full + 8 * K1_NS;
  const int fb_base = 7 * (j >> 1);
  const int fb0 = fb_base + ((j & 1) ? 4 : 0);
  const int fbh = fb_base + 3;
  const CUtensorMap* tw = (j < 4) ? &tm_wr : &tm_wi;
  const CUtensorMap* tgu = rank ? &tm_wu : &tm_wg;

  if (tid == 0) DBG(0, 0);
  if (tid == 256) {
    for (int i = 0; i < K1_NS; i++) { mbar_init(bar_full + 8 * i, 1); mbar_init(bar_empty + 8 * i, 8); }
    asm volatile("fence.mbarrier_init.release.cluster;" ::: "memory");
    prefetch_tmap(tw);
    prefetch_tmap(tgu);
    if (blockIdx.x < 64) g_flags[blockIdx.x] = 0;
  }
  __syncwarp();
  cluster_arrive_relaxed();
  pdl_launch();

  if (warp >= 8) {
    reg_dec<40>();
    cluster_wait();
    if (tid == 256) {
      int slot = 0; uint32_t ph = 0;
      for (int s = 0; s < 35; s++) {
        const int unit = s / 7, kb = s - unit * 7;
        if (s >= K1_NS) mbar_wait(bar_empty + 8 * slot, ph ^ 1);
        DBG(0, 20 + s);
        const uint32_t dst = sb + K1_B_OFF + slot * 16384;
        if (unit == 0) {
          mbar_expect(bar_full + 8 * slot, 14336);
          tma2d_mc(dst + rank * 7168, tw, kb * 64, (j & 3) * 112 + rank * 56, bar_full + 8 * slot, 3);
        } else {
          const int fb = (unit == 4) ? fbh : (fb0 + unit - 1);
          mbar_expect(bar_full + 8 * slot, 16384);
          tma2d_mc(dst + rank * 8192, tgu, fb * 64, kb * 64, bar_full + 8 * slot, 3);
        }
        if (s >= K1_NS && s < K1_NS + 16) {
          const int i = s - K1_NS;
          l2_prefetch(pf.cr + (size_t)blockIdx.x * 65536 + i * 4096, 4096);
          l2_prefetch(pf.ci + (size_t)blockIdx.x * 65536 + i * 4096, 4096);
          if (i == 0) l2_prefetch(pf.wd + blockIdx.x * 12544, 12544);
        }
        if (++slot == K1_NS) { slot = 0; ph ^= 1; }
      }
    }
  } else {
    reg_inc<232>();
    const int wg = warp >> 2;
    {
      const int c = lane & 7;
      uint4 v[4][7];
#pragma unroll
      for (int pass = 0; pass < 4; pass++) {
        const int r = warp * 16 + pass * 4 + (lane >> 3);
        const uint4* src = reinterpret_cast<const uint4*>(x + (size_t)(mt * 128 + r) * 448) + c;
#pragma unroll
        for (int b = 0; b < 7; b++)
          asm volatile("ld.global.nc.v4.u32 {%0,%1,%2,%3}, [%4];" : "=r"(v[pass][b].x), "=r"(v[pass][b].y), "=r"(v[pass][b].z), "=r"(v[pass][b].w) : "l"(src + b * 8) : "memory");
      }
      if (tid == 0) {
        const int b = blockIdx.x;
        l2_prefetch(pf.wr + b * 3136, 3136);
        l2_prefetch(pf.wi + b * 3136, 3136);
        l2_prefetch(pf.wg + b * 12544, 12544);
        l2_prefetch(pf.wu + b * 12544, 12544);
      }
      float mean[4], rinv[4];
#pragma unroll
      for (int pass = 0; pass < 4; pass++) {
        float s0 = 0.f, s1 = 0.f, s2 = 0.f, s3 = 0.f;
#pragma unroll
        for (int b = 0; b < 7; b++) {
          s0 += bf_lo(v[pass][b].x) + bf_hi(v[pass][b].x); s1 += bf_lo(v[pass][b].y) + bf_hi(v[pass][b].y);
          s2 += bf_lo(v[pass][b].z) + bf_hi(v[pass][b].z); s3 += bf_lo(v[pass][b].w) + bf_hi(v[pass][b].w);
        }
        mean[pass] = (s0 + s1) + (s2 + s3);
      }
      if (tid == 0) DBG(0, 2);
#pragma unroll
      for (int o = 1; o < 8; o <<= 1) {
#pragma unroll
        for (int pass = 0; pass < 4; pass++) mean[pass] += __shfl_xor_sync(0xffffffffu, mean[pass], o);
      }
#pragma unroll
      for (int pass = 0; pass < 4; pass++) {
        mean[pass] *= (1.0f / 448.0f);
        const float m = mean[pass];
        float q0 = 0.f, q1 = 0.f, q2 = 0.f, q3 = 0.f;
#pragma unroll
        for (int b = 0; b < 7; b++) {
          float d;
          d = bf_lo(v[pass][b].x) - m; q0 = fmaf(d, d, q0); d = bf_hi(v[pass][b].x) - m; q1 = fmaf(d, d, q1);
          d = bf_lo(v[pass][b].y) - m; q2 = fmaf(d, d, q2); d = bf_hi(v[pass][b].y) - m; q3 = fmaf(d, d, q3);
          d = bf_lo(v[pass][b].z) - m; q0 = fmaf(d, d, q0); d = bf_hi(v[pass][b].z) - m; q1 = fmaf(d, d, q1);
          d = bf_lo(v[pass][b].w) - m; q2 = fmaf(d, d, q2); d = bf_hi(v[pass][b].w) - m; q3 = fmaf(d, d, q3);
        }
        rinv[pass] = (q0 + q1) + (q2 + q3);
      }
#pragma unroll
      for (int o = 1; o < 8; o <<= 1) {
#pragma unroll
        for (int pass = 0; pass < 4; pass++) rinv[pass] += __shfl_xor_sync(0xffffffffu, rinv[pass], o);
      }
#pragma unroll
      for (int pass = 0; pass < 4; pass++) {
        const float var_b = rbf(rinv[pass] * (1.0f / 448.0f));
        const float den = rbf(sqrtf(rbf(var_b + 1e-5f)));
        const float ri = 1.0f / den;
        const float rih = rbf(ri);
        const uint32_t rhi2 = pack_bf16(rih, rih), rlo2 = pack_bf16(ri - rih, ri - rih);
        const uint32_t m2 = pack_bf16(mean[pass], mean[pass]);
        const int r = warp * 16 + pass * 4 + (lane >> 3);
        const uint32_t a0 = sb + r * 128 + ((c ^ (r & 7)) * 16);
#pragma unroll
        for (int b = 0; b < 7; b++) {
          uint32_t w4[4] = {v[pass][b].x, v[pass][b].y, v[pass][b].z, v[pass][b].w};
#pragma unroll
          for (int q = 0; q < 4; q++) {
            const uint32_t dw = hsub2_bf16(w4[q], m2);
            w4[q] = hfma2_bf16(dw, rhi2, hmul2_bf16(dw, rlo2));
          }
          sts128(a0 + b * 16384, make_uint4(w4[0], w4[1], w4[2], w4[3]));
        }
      }
    }
    asm volatile("fence.proxy.async.shared::cta;" ::: "memory");
    named_bar(1, 256);
    cluster_wait();
    if (tid == 0) DBG(0, 3);

    if (wg == 0) {
      k1_unit_ab(sb, bar_full, bar_empty, warp, lane, mt, j);
      if (tid == 0) DBG(0, 6);
      k1_unit_gu<false>(sb, bar_full, bar_empty, warp, lane, mt, 2, fb0 + 1, 0);
      if (tid == 0) DBG(0, 12);
      k1_unit_gu<true>(sb, bar_full, bar_empty, warp, lane, mt, 4, fbh, j & 1);
      if (tid == 0) DBG(0, 18);
    } else {
      k1_unit_gu<false>(sb, bar_full, bar_empty, warp, lane, mt, 1, fb0, 0);
      if (tid == 128) DBG(0, 9);
      k1_unit_gu<false>(sb, bar_full, bar_empty, warp, lane, mt, 3, fb0 + 2, 0);
      if (tid == 128) DBG(0, 15);
    }
  }
  cluster_arrive_relaxed();
  cluster_wait();
}

constexpr int K2_NS = 4;
constexpr int K2_STAGE = 16384 + 32768;
constexpr int K2_BAR_OFF = K2_NS * K2_STAGE;
constexpr int K2_SMEM = K2_BAR_OFF + 256 + 1024;

__device__ __forceinline__ void flag_signal_wait(unsigned int* flag, unsigned int target, bool do_wait) {
  __threadfence();
  named_bar(1, 256);
  if (threadIdx.x == 0) {
    atomicAdd(flag, 1u);
    if (do_wait) {
      int it = 0;
      while (true) {
        unsigned int v;
        asm volatile("ld.acquire.gpu.global.u32 %0, [%1];" : "=r"(v) : "l"(flag) : "memory");
        if (v >= target) break;
        if (++it > (1 << 22)) __trap();
      }
    }
  }
  if (do_wait) named_bar(1, 256);
}

constexpr int K2_PITCH = 464;

template <int Q>
__device__ __forceinline__ void k2_y_epilogue(float (&acc)[112], int tile, int tid, uint32_t sb, int mt, int n) {
  constexpr int G0 = (Q == 0) ? 0 : (Q == 1 ? 10 : 20);
  constexpr int G1 = (Q == 0) ? 10 : (Q == 1 ? 20 : 28);
  float4* part = g_part + (size_t)tile * (3 * 28 * 256) + tid;
#pragma unroll
  for (int g = 0; g < 28; g++) {
    if (g < G0 || g >= G1) part[(Q * 28 + g) * 256] = make_float4(acc[4 * g], acc[4 * g + 1], acc[4 * g + 2], acc[4 * g + 3]);
  }
  flag_signal_wait(&g_flags[tile], 3u, true);
  if (tid == 0) DBG(1, 30);
  constexpr int QA = (Q + 1) % 3, QB = (Q + 2) % 3;
  float4 va[G1 - G0], vb[G1 - G0];
#pragma unroll
  for (int g = G0; g < G1; g++) { va[g - G0] = __ldcg(&part[(QA * 28 + g) * 256]); vb[g - G0] = __ldcg(&part[(QB * 28 + g) * 256]); }
  const int warp = tid >> 5, lane = tid & 31;
  const uint32_t stg = sb + warp * 16 * K2_PITCH;
  const int st_row = (lane & 7) + 8 * ((lane >> 3) & 1);
  const int st_chunk = lane >> 4;
#pragma unroll
  for (int g = G0; g < G1; g += 2) {
    uint32_t pk[4];
#pragma unroll
    for (int e = 0; e < 2; e++) {
      const float4 a = va[g + e - G0], b = vb[g + e - G0];
      const float* c = &acc[4 * (g + e)];
      pk[2 * e] = pack_bf16(c[0] + a.x + b.x, c[1] + a.y + b.y);
      pk[2 * e + 1] = pack_bf16(c[2] + a.z + b.z, c[3] + a.w + b.w);
    }
    stmatrix_x4(stg + st_row * K2_PITCH + (g - G0 + st_chunk) * 16, pk[0], pk[1], pk[2], pk[3]);
  }
  __syncwarp();
  constexpr int NCH2 = (G1 - G0) / 2;
  __nv_bfloat16* sp = g_s + (size_t)(mt * 128 + warp * 16 + (lane >> 1)) * 448 + n * 224 + (G0 + (lane & 1) * NCH2) * 8;
  const uint32_t lp = stg + (lane >> 1) * K2_PITCH + (lane & 1) * NCH2 * 16;
#pragma unroll
  for (int t = 0; t < NCH2; t++) stg128(sp + t * 8, lds128(lp + t * 16));
  flag_signal_wait(&g_flags[32 + tile], 0u, false);
}

__global__ void __cluster_dims__(2, 1, 1) __launch_bounds__(384, 1)
k2_kernel(const __grid_constant__ CUtensorMap tm_cr, const __grid_constant__ CUtensorMap tm_ci, const __grid_constant__ CUtensorMap tm_h,
          const __grid_constant__ CUtensorMap tm_ab, const __grid_constant__ CUtensorMap tm_wd,
          const __nv_bfloat16* __restrict__ x, __nv_bfloat16* __restrict__ out) {
  extern __shared__ uint8_t smem_raw[];
  const uint32_t sb = (s2u(smem_raw) + 1023) & ~1023u;
  const int tid = threadIdx.x, warp = tid >> 5, lane = tid & 31;
  uint32_t rank;
  asm volatile("mov.u32 %0, %%cluster_ctarank;" : "=r"(rank));
  const int cid = blockIdx.x >> 1;
  const int q = cid & 3, n = (cid >> 2) & 1, p = cid >> 3;
  const int mt = 2 * p + (int)rank;
  const int tile = mt * 2 + n;
  const uint32_t bar_full = sb + K2_BAR_OFF;
  const uint32_t bar_empty = bar_full + 8 * K2_NS;
  const int g0 = (q == 0) ? 0 : (q == 1 ? 22 : (q == 2 ? 43 : 64));
  const int nkb = (q == 0) ? 22 : (q == 3 ? 28 : 21);

  if (tid == 0) DBG(1, 0);
  if (tid == 256) {
    for (int i = 0; i < K2_NS; i++) { mbar_init(bar_full + 8 * i, 1); mbar_init(bar_empty + 8 * i, 16); }
    asm volatile("fence.mbarrier_init.release.cluster;" ::: "memory");
    if (q == 3) { prefetch_tmap(&tm_h); prefetch_tmap(&tm_wd); }
    else { prefetch_tmap(&tm_cr); prefetch_tmap(&tm_ci); prefetch_tmap(&tm_ab); }
  }
  __syncwarp();
  cluster_arrive_relaxed();
  cluster_wait();

  if (warp >= 8) {
    reg_dec<40>();
    if (tid == 256) {
      auto load_a = [&](int g, uint32_t dst, uint32_t fb) {
        if (g < 32) tma2d(dst, &tm_cr, g * 64, mt * 128, fb);
        else if (g < 64) tma2d(dst, &tm_ci, (g - 32) * 64, mt * 128, fb);
        else tma2d(dst, &tm_h, (g - 64) * 64, mt * 128, fb);
      };
      auto load_b = [&](int g, uint32_t dst, uint32_t fb) {
        const CUtensorMap* tb = (g < 64) ? &tm_ab : &tm_wd;
        const int kbrow = (g < 64) ? g * 64 : (g - 64) * 64;
        tma3d_mc(dst + 16384 + (2 * rank) * 8192, tb, (2 * rank) * 64, n, kbrow, fb, 3);
        tma3d_mc(dst + 16384 + (2 * rank + 1) * 8192, tb, (2 * rank + 1) * 64, n, kbrow, fb, 3);
      };
      for (int s = 0; s < K2_NS; s++) {
        mbar_expect(bar_full + 8 * s, K2_STAGE);
        if (q < 3) load_a(g0 + s, sb + s * K2_STAGE, bar_full + 8 * s); else load_b(g0 + s, sb + s * K2_STAGE, bar_full + 8 * s);
      }
      pdl_wait();
      DBG(1, 31);
      for (int s = 0; s < K2_NS; s++) {
        if (q < 3) load_b(g0 + s, sb + s * K2_STAGE, bar_full + 8 * s); else load_a(g0 + s, sb + s * K2_STAGE, bar_full + 8 * s);
      }
      int slot = 0; uint32_t ph = 0;
      for (int s = K2_NS; s < nkb; s++) {
        mbar_wait(bar_empty + 8 * slot, ph);
        DBG(1, 32 + s);
        const uint32_t dst = sb + slot * K2_STAGE;
        const uint32_t fb = bar_full + 8 * slot;
        mbar_expect(fb, K2_STAGE);
        load_a(g0 + s, dst, fb);
        load_b(g0 + s, dst, fb);
        if (++slot == K2_NS) { slot = 0; ph ^= 1; }
      }
    }
  } else {
    reg_inc<232>();
    const int wg = warp >> 2;
    float acc[112];
    int slot = 0; uint32_t ph = 0;
#pragma unroll 1
    for (int s = 0; s < nkb; s++) {
      mbar_wait(bar_full + 8 * slot, ph);
      if (tid == 0) DBG(1, 1 + s);
      wg_fence();
      const uint64_t da = make_desc(sb + slot * K2_STAGE + wg * 8192, 16, 1024);
      const uint64_t db = make_desc(sb + slot * K2_STAGE + 16384, 8192, 1024);
#pragma unroll
      for (int k = 0; k < 4; k++) wgmma_n224_tb(acc, da + k * 2, db + k * 128, (s | k) != 0);
      wg_commit();
      if (s > 0) {
        wg_wait<1>();
        const int ps = (slot + K2_NS - 1) % K2_NS;
        if (lane == 0) { mbar_arrive_cluster(bar_empty + 8 * ps, 0); mbar_arrive_cluster(bar_empty + 8 * ps, 1); }
      }
      if (++slot == K2_NS) { slot = 0; ph ^= 1; }
    }
    wg_wait<0>();
    pdl_wait();
    named_bar(1, 256);
    if (tid == 0) DBG(1, 29);
    if (q == 0) k2_y_epilogue<0>(acc, tile, tid, sb, mt, n);
    else if (q == 1) k2_y_epilogue<1>(acc, tile, tid, sb, mt, n);
    else if (q == 2) k2_y_epilogue<2>(acc, tile, tid, sb, mt, n);
    else {
      const uint32_t stg = sb + warp * 16 * K2_PITCH;
      const int st_row = (lane & 7) + 8 * ((lane >> 3) & 1);
      const int st_chunk = lane >> 4;
#pragma unroll
      for (int g = 0; g < 28; g += 2) {
        uint32_t pk[4];
#pragma unroll
        for (int e = 0; e < 4; e++) {
          const uint32_t f2 = pack_bf16(acc[4 * g + 2 * e], acc[4 * g + 2 * e + 1]);
          pk[e] = pack_bf16(silu_f(bf_lo(f2)), silu_f(bf_hi(f2)));
        }
        stmatrix_x4(stg + st_row * K2_PITCH + (g + st_chunk) * 16, pk[0], pk[1], pk[2], pk[3]);
      }
      const size_t gbase = (size_t)(mt * 128 + warp * 16) * 448 + n * 224 + (lane < 28 ? lane : 0) * 8;
      const __nv_bfloat16* xp = x + gbase;
      uint4 xv[16];
#pragma unroll
      for (int t = 0; t < 16; t++) xv[t] = ldg128_cg(xp + t * 448);
      if (lane == 0) {
        int it = 0;
        while (true) {
          unsigned int v;
          asm volatile("ld.acquire.gpu.global.u32 %0, [%1];" : "=r"(v) : "l"(&g_flags[32 + tile]) : "memory");
          if (v >= 3u) break;
          if (++it > (1 << 22)) __trap();
        }
      }
      __syncwarp();
      if (tid == 0) DBG(1, 30);
      const __nv_bfloat16* sp = g_s + gbase;
      uint4 sv[16];
#pragma unroll
      for (int t = 0; t < 16; t++) sv[t] = ldg128_cg(sp + t * 448);
      __nv_bfloat16* op = out + gbase;
      const uint32_t lp = stg + (lane < 28 ? lane : 0) * 16;
#pragma unroll
      for (int t = 0; t < 16; t++) {
        const uint4 gv = lds128(lp + t * K2_PITCH);
        uint4 o;
        o.x = hadd2_bf16(xv[t].x, hmul2_bf16(sv[t].x, gv.x));
        o.y = hadd2_bf16(xv[t].y, hmul2_bf16(sv[t].y, gv.y));
        o.z = hadd2_bf16(xv[t].z, hmul2_bf16(sv[t].z, gv.z));
        o.w = hadd2_bf16(xv[t].w, hmul2_bf16(sv[t].w, gv.w));
        if (lane < 28) stg128(op + t * 448, o);
      }
    }
    if (tid == 0) DBG(1, 63);
  }
  cluster_arrive_relaxed();
  cluster_wait();
}

typedef CUresult (*EncFn)(CUtensorMap*, CUtensorMapDataType, cuuint32_t, void*, const cuuint64_t*, const cuuint64_t*, const cuuint32_t*,
                          const cuuint32_t*, CUtensorMapInterleave, CUtensorMapSwizzle, CUtensorMapL2promotion, CUtensorMapFloatOOBfill);

void make2d(EncFn enc, CUtensorMap* tm, const void* ptr, uint64_t cols, uint64_t rows, uint32_t bc, uint32_t br) {
  cuuint64_t gd[2] = {cols, rows};
  cuuint64_t gs[1] = {cols * 2};
  cuuint32_t bd[2] = {bc, br};
  cuuint32_t es[2] = {1, 1};
  enc(tm, CU_TENSOR_MAP_DATA_TYPE_BFLOAT16, 2, const_cast<void*>(ptr), gd, gs, bd, es, CU_TENSOR_MAP_INTERLEAVE_NONE,
      CU_TENSOR_MAP_SWIZZLE_128B, CU_TENSOR_MAP_L2_PROMOTION_L2_128B, CU_TENSOR_MAP_FLOAT_OOB_FILL_NONE);
}
void make3d_half(EncFn enc, CUtensorMap* tm, const void* ptr, uint64_t rows) {
  cuuint64_t gd[3] = {224, 2, rows};
  cuuint64_t gs[2] = {448, 896};
  cuuint32_t bd[3] = {64, 1, 64};
  cuuint32_t es[3] = {1, 1, 1};
  enc(tm, CU_TENSOR_MAP_DATA_TYPE_BFLOAT16, 3, const_cast<void*>(ptr), gd, gs, bd, es, CU_TENSOR_MAP_INTERLEAVE_NONE,
      CU_TENSOR_MAP_SWIZZLE_128B, CU_TENSOR_MAP_L2_PROMOTION_L2_128B, CU_TENSOR_MAP_FLOAT_OOB_FILL_NONE);
}

struct Maps { CUtensorMap wr, wi, wg, wu, cr, ci, h, ab, wd; };

}

extern "C" void kernel_launch(void* const* d_in, const int* in_sizes, int n_in, void* d_out, int out_size) {
  (void)in_sizes; (void)n_in; (void)out_size;
  static Maps maps;
  static const void* cached[9] = {nullptr};
  static bool attr_done = false;
  bool same = true;
  for (int i = 0; i < 9; i++) same = same && (cached[i] == d_in[i]);
  if (!same) {
    void* fn = nullptr;
    cudaDriverEntryPointQueryResult qr;
    cudaGetDriverEntryPoint("cuTensorMapEncodeTiled", &fn, cudaEnableDefault, &qr);
    EncFn enc = (EncFn)fn;
    void *p_ab = nullptr, *p_h = nullptr;
    cudaGetSymbolAddress(&p_ab, g_ab);
    cudaGetSymbolAddress(&p_h, g_h);
    make2d(enc, &maps.cr, d_in[1], 2048, 2048, 64, 128);
    make2d(enc, &maps.ci, d_in[2], 2048, 2048, 64, 128);
    make2d(enc, &maps.wr, d_in[3], 448, 448, 64, 56);
    make2d(enc, &maps.wi, d_in[4], 448, 448, 64, 56);
    make2d(enc, &maps.wg, d_in[6], 1792, 448, 64, 64);
    make2d(enc, &maps.wu, d_in[7], 1792, 448, 64, 64);
    make3d_half(enc, &maps.wd, d_in[8], 1792);
    make2d(enc, &maps.h, p_h, 1792, 2048, 64, 128);
    make3d_half(enc, &maps.ab, p_ab, 4096);
    for (int i = 0; i < 9; i++) cached[i] = d_in[i];
  }
  if (!attr_done) {
    cudaFuncSetAttribute(k1_kernel, cudaFuncAttributeMaxDynamicSharedMemorySize, K1_SMEM);
    cudaFuncSetAttribute(k2_kernel, cudaFuncAttributeMaxDynamicSharedMemorySize, K2_SMEM);
    attr_done = true;
  }
  PfPtrs pf;
  pf.wr = (const uint8_t*)d_in[3]; pf.wi = (const uint8_t*)d_in[4]; pf.wg = (const uint8_t*)d_in[6]; pf.wu = (const uint8_t*)d_in[7];
  pf.wd = (const uint8_t*)d_in[8]; pf.cr = (const uint8_t*)d_in[1]; pf.ci = (const uint8_t*)d_in[2];
  k1_kernel<<<128, 384, K1_SMEM>>>(maps.wr, maps.wi, maps.wg, maps.wu, (const __nv_bfloat16*)d_in[0], pf);

  cudaLaunchConfig_t cfg = {};
  cfg.gridDim = dim3(128); cfg.blockDim = dim3(384); cfg.dynamicSmemBytes = K2_SMEM; cfg.stream = cudaStreamPerThread;
  cudaLaunchAttribute at[1];
  at[0].id = cudaLaunchAttributeProgrammaticStreamSerialization;
  at[0].val.programmaticStreamSerializationAllowed = 1;
  cfg.attrs = at; cfg.numAttrs = 1;
  cudaLaunchKernelEx(&cfg, k2_kernel, maps.cr, maps.ci, maps.h, maps.ab, maps.wd, (const __nv_bfloat16*)d_in[0], (__nv_bfloat16*)d_out);
}
```

```cpp
#include <cuda_runtime.h>
#include <cuda_bf16.h>
#include <cuda.h>
#include <stdint.h>

namespace {

__device__ __align__(1024) __nv_bfloat16 g_ab[4096 * 448];
__device__ __align__(1024) __nv_bfloat16 g_h[2048 * 1792];
__device__ float4 g_part[32 * 3 * 28 * 256];
__device__ __align__(1024) __nv_bfloat16 g_s[2048 * 448];
__device__ unsigned int g_flags[64];

#define DBG(k, i) do {} while (0)
#define DBGC(k, i) do {} while (0)

#define TIMEOUT(code) __trap()
#define SPIN_LIMIT (1 << 22)
__device__ __forceinline__ uint32_t s2u(const void* p) { return (uint32_t)__cvta_generic_to_shared(p); }
__device__ __forceinline__ void mbar_init(uint32_t b, int c) { asm volatile("mbarrier.init.shared::cta.b64 [%0], %1;" ::"r"(b), "r"(c)); }
__device__ __forceinline__ void mbar_expect(uint32_t b, uint32_t bytes) {
  asm volatile("mbarrier.arrive.expect_tx.shared::cta.b64 _, [%0], %1;" ::"r"(b), "r"(bytes) : "memory");
}
__device__ __forceinline__ void mbar_wait(uint32_t b, uint32_t ph, int code = 1) {
  uint32_t done = 0;
  int it = 0;
  while (true) {
    asm volatile("{.reg .pred p; mbarrier.try_wait.parity.shared::cta.b64 p, [%1], %2; selp.u32 %0,1,0,p;}" : "=r"(done) : "r"(b), "r"(ph) : "memory");
    if (done) break;
    if (++it > SPIN_LIMIT) { TIMEOUT(code); break; }
  }
}
__device__ __forceinline__ void mbar_arrive_cluster(uint32_t b, uint32_t cta) {
  uint32_t r;
  asm volatile("mapa.shared::cluster.u32 %0, %1, %2;" : "=r"(r) : "r"(b), "r"(cta));
  asm volatile("mbarrier.arrive.shared::cluster.b64 _, [%0];" ::"r"(r) : "memory");
}
__device__ __forceinline__ void tma2d(uint32_t dst, const CUtensorMap* m, int c0, int c1, uint32_t bar) {
  asm volatile("cp.async.bulk.tensor.2d.shared::cluster.global.mbarrier::complete_tx::bytes [%0], [%1, {%3,%4}], [%2];" ::"r"(dst), "l"(m), "r"(bar), "r"(c0), "r"(c1) : "memory");
}
__device__ __forceinline__ void tma2d_mc(uint32_t dst, const CUtensorMap* m, int c0, int c1, uint32_t bar, uint16_t mask) {
  asm volatile("cp.async.bulk.tensor.2d.shared::cluster.global.mbarrier::complete_tx::bytes.multicast::cluster [%0], [%1, {%3,%4}], [%2], %5;" ::"r"(dst), "l"(m), "r"(bar), "r"(c0), "r"(c1), "h"(mask) : "memory");
}
__device__ __forceinline__ void tma3d_mc(uint32_t dst, const CUtensorMap* m, int c0, int c1, int c2, uint32_t bar, uint16_t mask) {
  asm volatile("cp.async.bulk.tensor.3d.shared::cluster.global.mbarrier::complete_tx::bytes.multicast::cluster [%0], [%1, {%3,%4,%5}], [%2], %6;" ::"r"(dst), "l"(m), "r"(bar), "r"(c0), "r"(c1), "r"(c2), "h"(mask) : "memory");
}
__device__ __forceinline__ void prefetch_tmap(const CUtensorMap* m) { asm volatile("prefetch.tensormap [%0];" ::"l"(m) : "memory"); }
__device__ __forceinline__ void l2_prefetch(const void* p, uint32_t bytes) {
  asm volatile("cp.async.bulk.prefetch.L2.global [%0], %1;" ::"l"(p), "r"(bytes) : "memory");
}
__device__ __forceinline__ void cluster_arrive_relaxed() { asm volatile("barrier.cluster.arrive.relaxed.aligned;" ::: "memory"); }
__device__ __forceinline__ void cluster_wait() { asm volatile("barrier.cluster.wait.aligned;" ::: "memory"); }
__device__ __forceinline__ void wg_fence() { __syncwarp(); asm volatile("wgmma.fence.sync.aligned;" ::: "memory"); }
__device__ __forceinline__ void wg_commit() { asm volatile("wgmma.commit_group.sync.aligned;" ::: "memory"); }
template <int N> __device__ __forceinline__ void wg_wait() { __syncwarp(); asm volatile("wgmma.wait_group.sync.aligned %0;" ::"n"(N) : "memory"); }
__device__ __forceinline__ void named_bar(int id, int n) { asm volatile("bar.sync %0, %1;" ::"r"(id), "r"(n) : "memory"); }
__device__ __forceinline__ void named_arrive(int id, int n) { asm volatile("bar.arrive %0, %1;" ::"r"(id), "r"(n) : "memory"); }
template <int N> __device__ __forceinline__ void reg_inc() { asm volatile("setmaxnreg.inc.sync.aligned.u32 %0;" ::"n"(N)); }
template <int N> __device__ __forceinline__ void reg_dec() { asm volatile("setmaxnreg.dec.sync.aligned.u32 %0;" ::"n"(N)); }
__device__ __forceinline__ void pdl_wait() { asm volatile("griddepcontrol.wait;" ::: "memory"); }
__device__ __forceinline__ void pdl_launch() { asm volatile("griddepcontrol.launch_dependents;" ::: "memory"); }

__device__ __forceinline__ uint32_t make_desc(uint32_t addr, uint32_t lbo, uint32_t  ) {
  return ((addr & 0x3FFFF) >> 4) | ((lbo >> 4) << 16);
}
__device__ __forceinline__ void stmatrix_x4(uint32_t addr, uint32_t r0, uint32_t r1, uint32_t r2, uint32_t r3) {
  asm volatile("stmatrix.sync.aligned.m8n8.x4.shared.b16 [%0], {%1,%2,%3,%4};" ::"r"(addr), "r"(r0), "r"(r1), "r"(r2), "r"(r3) : "memory");
}
__device__ __forceinline__ uint4 lds128(uint32_t a) {
  uint4 v;
  asm volatile("ld.shared.v4.u32 {%0,%1,%2,%3}, [%4];" : "=r"(v.x), "=r"(v.y), "=r"(v.z), "=r"(v.w) : "r"(a) : "memory");
  return v;
}
__device__ __forceinline__ void sts128(uint32_t a, uint4 v) {
  asm volatile("st.shared.v4.u32 [%0], {%1,%2,%3,%4};" ::"r"(a), "r"(v.x), "r"(v.y), "r"(v.z), "r"(v.w) : "memory");
}
__device__ __forceinline__ void stg128(void* p, uint4 v) {
  asm volatile("st.global.v4.u32 [%0], {%1,%2,%3,%4};" ::"l"(p), "r"(v.x), "r"(v.y), "r"(v.z), "r"(v.w) : "memory");
}
__device__ __forceinline__ uint32_t pack_bf16(float lo, float hi) {
  uint32_t r;
  asm("cvt.rn.bf16x2.f32 %0, %1, %2;" : "=r"(r) : "f"(hi), "f"(lo));
  return r;
}
__device__ __forceinline__ uint32_t hmul2_bf16(uint32_t a, uint32_t b) {
  uint32_t r;
  asm("mul.rn.bf16x2 %0, %1, %2;" : "=r"(r) : "r"(a), "r"(b));
  return r;
}
__device__ __forceinline__ uint32_t hsub2_bf16(uint32_t a, uint32_t b) {
  uint32_t r;
  asm("sub.rn.bf16x2 %0, %1, %2;" : "=r"(r) : "r"(a), "r"(b));
  return r;
}
__device__ __forceinline__ uint32_t hadd2_bf16(uint32_t a, uint32_t b) {
  uint32_t r;
  asm("add.rn.bf16x2 %0, %1, %2;" : "=r"(r) : "r"(a), "r"(b));
  return r;
}
__device__ __forceinline__ uint32_t hfma2_bf16(uint32_t a, uint32_t b, uint32_t c) {
  uint32_t r;
  asm("fma.rn.bf16x2 %0, %1, %2, %3;" : "=r"(r) : "r"(a), "r"(b), "r"(c));
  return r;
}
__device__ __forceinline__ bool mbar_test(uint32_t b, uint32_t ph) {
  uint32_t done;
  asm volatile("{.reg .pred p; mbarrier.test_wait.parity.shared::cta.b64 p, [%1], %2; selp.u32 %0,1,0,p;}" : "=r"(done) : "r"(b), "r"(ph) : "memory");
  return __all_sync(0xffffffffu, done != 0);
}
__device__ __forceinline__ uint4 ldg128_cg(const void* p) {
  uint4 v;
  asm volatile("ld.global.cg.v4.u32 {%0,%1,%2,%3}, [%4];" : "=r"(v.x), "=r"(v.y), "=r"(v.z), "=r"(v.w) : "l"(p) : "memory");
  return v;
}
__device__ __forceinline__ float bf_lo(uint32_t w) { return __uint_as_float(w << 16); }
__device__ __forceinline__ float bf_hi(uint32_t w) { return __uint_as_float(w & 0xffff0000u); }
__device__ __forceinline__ float rbf(float x) { return __bfloat162float(__float2bfloat16_rn(x)); }
__device__ __forceinline__ float ex2f(float x) { float r; asm("ex2.approx.ftz.f32 %0, %1;" : "=f"(r) : "f"(x)); return r; }
__device__ __forceinline__ float rcpf(float x) { float r; asm("rcp.approx.ftz.f32 %0, %1;" : "=f"(r) : "f"(x)); return r; }
__device__ __forceinline__ float gelu_tanh(float x) {
  const float c1 = -2.0f * 0.7978845608028654f * 1.4426950408889634f;
  const float c2 = c1 * 0.044715f;
  const float e = ex2f(x * fmaf(c2, x * x, c1));
  return x * rcpf(1.0f + e);
}
__device__ __forceinline__ float silu_f(float x) {
  const float e = ex2f(-1.4426950408889634f * x);
  return x * rcpf(1.0f + e);
}

__device__ __forceinline__ void wgmma_n128_tb(float (&d)[64], uint32_t da, uint32_t db, int scale_d) {
  asm volatile(
    "{\n.reg .pred p;\n.reg .b64 da, db;\nsetp.ne.b32 p, %66, 0;\n"
    "mov.b64 da, {%64, 0x40000040};\nmov.b64 db, {%65, 0x40000040};\n"
    "wgmma.mma_async.sync.aligned.m64n128k16.f32.bf16.bf16 {%0, %1, %2, %3, %4, %5, %6, %7, %8, %9, %10, %11, %12, %13, %14, %15, %16, %17, %18, %19, %20, %21, %22, %23, %24, %25, %26, %27, %28, %29, %30, %31, %32, %33, %34, %35, %36, %37, %38, %39, %40, %41, %42, %43, %44, %45, %46, %47, %48, %49, %50, %51, %52, %53, %54, %55, %56, %57, %58, %59, %60, %61, %62, %63}, da, db, p, 1, 1, 0, 1;\n}\n"
    : "+f"(d[0]), "+f"(d[1]), "+f"(d[2]), "+f"(d[3]), "+f"(d[4]), "+f"(d[5]), "+f"(d[6]), "+f"(d[7]), "+f"(d[8]), "+f"(d[9]), "+f"(d[10]), "+f"(d[11]), "+f"(d[12]), "+f"(d[13]), "+f"(d[14]), "+f"(d[15]), "+f"(d[16]), "+f"(d[17]), "+f"(d[18]), "+f"(d[19]), "+f"(d[20]), "+f"(d[21]), "+f"(d[22]), "+f"(d[23]), "+f"(d[24]), "+f"(d[25]), "+f"(d[26]), "+f"(d[27]), "+f"(d[28]), "+f"(d[29]), "+f"(d[30]), "+f"(d[31]), "+f"(d[32]), "+f"(d[33]), "+f"(d[34]), "+f"(d[35]), "+f"(d[36]), "+f"(d[37]), "+f"(d[38]), "+f"(d[39]), "+f"(d[40]), "+f"(d[41]), "+f"(d[42]), "+f"(d[43]), "+f"(d[44]), "+f"(d[45]), "+f"(d[46]), "+f"(d[47]), "+f"(d[48]), "+f"(d[49]), "+f"(d[50]), "+f"(d[51]), "+f"(d[52]), "+f"(d[53]), "+f"(d[54]), "+f"(d[55]), "+f"(d[56]), "+f"(d[57]), "+f"(d[58]), "+f"(d[59]), "+f"(d[60]), "+f"(d[61]), "+f"(d[62]), "+f"(d[63])
    : "r"(da), "r"(db), "r"(scale_d));
}
__device__ __forceinline__ void wgmma_n112(float (&d)[56], uint32_t da, uint32_t db, int scale_d) {
  asm volatile(
    "{\n.reg .pred p;\n.reg .b64 da, db;\nsetp.ne.b32 p, %58, 0;\n"
    "mov.b64 da, {%56, 0x40000040};\nmov.b64 db, {%57, 0x40000040};\n"
    "wgmma.mma_async.sync.aligned.m64n112k16.f32.bf16.bf16 {%0, %1, %2, %3, %4, %5, %6, %7, %8, %9, %10, %11, %12, %13, %14, %15, %16, %17, %18, %19, %20, %21, %22, %23, %24, %25, %26, %27, %28, %29, %30, %31, %32, %33, %34, %35, %36, %37, %38, %39, %40, %41, %42, %43, %44, %45, %46, %47, %48, %49, %50, %51, %52, %53, %54, %55}, da, db, p, 1, 1, 0, 0;\n}\n"
    : "+f"(d[0]), "+f"(d[1]), "+f"(d[2]), "+f"(d[3]), "+f"(d[4]), "+f"(d[5]), "+f"(d[6]), "+f"(d[7]), "+f"(d[8]), "+f"(d[9]), "+f"(d[10]), "+f"(d[11]), "+f"(d[12]), "+f"(d[13]), "+f"(d[14]), "+f"(d[15]), "+f"(d[16]), "+f"(d[17]), "+f"(d[18]), "+f"(d[19]), "+f"(d[20]), "+f"(d[21]), "+f"(d[22]), "+f"(d[23]), "+f"(d[24]), "+f"(d[25]), "+f"(d[26]), "+f"(d[27]), "+f"(d[28]), "+f"(d[29]), "+f"(d[30]), "+f"(d[31]), "+f"(d[32]), "+f"(d[33]), "+f"(d[34]), "+f"(d[35]), "+f"(d[36]), "+f"(d[37]), "+f"(d[38]), "+f"(d[39]), "+f"(d[40]), "+f"(d[41]), "+f"(d[42]), "+f"(d[43]), "+f"(d[44]), "+f"(d[45]), "+f"(d[46]), "+f"(d[47]), "+f"(d[48]), "+f"(d[49]), "+f"(d[50]), "+f"(d[51]), "+f"(d[52]), "+f"(d[53]), "+f"(d[54]), "+f"(d[55])
    : "r"(da), "r"(db), "r"(scale_d));
}
__device__ __forceinline__ void wgmma_n224_tb(float (&d)[112], uint32_t da, uint32_t db, int scale_d) {
  asm volatile(
    "{\n.reg .pred p;\n.reg .b64 da, db;\nsetp.ne.b32 p, %114, 0;\n"
    "mov.b64 da, {%112, 0x40000040};\nmov.b64 db, {%113, 0x40000040};\n"
    "wgmma.mma_async.sync.aligned.m64n224k16.f32.bf16.bf16 {%0, %1, %2, %3, %4, %5, %6, %7, %8, %9, %10, %11, %12, %13, %14, %15, %16, %17, %18, %19, %20, %21, %22, %23, %24, %25, %26, %27, %28, %29, %30, %31, %32, %33, %34, %35, %36, %37, %38, %39, %40, %41, %42, %43, %44, %45, %46, %47, %48, %49, %50, %51, %52, %53, %54, %55, %56, %57, %58, %59, %60, %61, %62, %63, %64, %65, %66, %67, %68, %69, %70, %71, %72, %73, %74, %75, %76, %77, %78, %79, %80, %81, %82, %83, %84, %85, %86, %87, %88, %89, %90, %91, %92, %93, %94, %95, %96, %97, %98, %99, %100, %101, %102, %103, %104, %105, %106, %107, %108, %109, %110, %111}, da, db, p, 1, 1, 0, 1;\n}\n"
    : "+f"(d[0]), "+f"(d[1]), "+f"(d[2]), "+f"(d[3]), "+f"(d[4]), "+f"(d[5]), "+f"(d[6]), "+f"(d[7]), "+f"(d[8]), "+f"(d[9]), "+f"(d[10]), "+f"(d[11]), "+f"(d[12]), "+f"(d[13]), "+f"(d[14]), "+f"(d[15]), "+f"(d[16]), "+f"(d[17]), "+f"(d[18]), "+f"(d[19]), "+f"(d[20]), "+f"(d[21]), "+f"(d[22]), "+f"(d[23]), "+f"(d[24]), "+f"(d[25]), "+f"(d[26]), "+f"(d[27]), "+f"(d[28]), "+f"(d[29]), "+f"(d[30]), "+f"(d[31]), "+f"(d[32]), "+f"(d[33]), "+f"(d[34]), "+f"(d[35]), "+f"(d[36]), "+f"(d[37]), "+f"(d[38]), "+f"(d[39]), "+f"(d[40]), "+f"(d[41]), "+f"(d[42]), "+f"(d[43]), "+f"(d[44]), "+f"(d[45]), "+f"(d[46]), "+f"(d[47]), "+f"(d[48]), "+f"(d[49]), "+f"(d[50]), "+f"(d[51]), "+f"(d[52]), "+f"(d[53]), "+f"(d[54]), "+f"(d[55]), "+f"(d[56]), "+f"(d[57]), "+f"(d[58]), "+f"(d[59]), "+f"(d[60]), "+f"(d[61]), "+f"(d[62]), "+f"(d[63]), "+f"(d[64]), "+f"(d[65]), "+f"(d[66]), "+f"(d[67]), "+f"(d[68]), "+f"(d[69]), "+f"(d[70]), "+f"(d[71]), "+f"(d[72]), "+f"(d[73]), "+f"(d[74]), "+f"(d[75]), "+f"(d[76]), "+f"(d[77]), "+f"(d[78]), "+f"(d[79]), "+f"(d[80]), "+f"(d[81]), "+f"(d[82]), "+f"(d[83]), "+f"(d[84]), "+f"(d[85]), "+f"(d[86]), "+f"(d[87]), "+f"(d[88]), "+f"(d[89]), "+f"(d[90]), "+f"(d[91]), "+f"(d[92]), "+f"(d[93]), "+f"(d[94]), "+f"(d[95]), "+f"(d[96]), "+f"(d[97]), "+f"(d[98]), "+f"(d[99]), "+f"(d[100]), "+f"(d[101]), "+f"(d[102]), "+f"(d[103]), "+f"(d[104]), "+f"(d[105]), "+f"(d[106]), "+f"(d[107]), "+f"(d[108]), "+f"(d[109]), "+f"(d[110]), "+f"(d[111])
    : "r"(da), "r"(db), "r"(scale_d));
}

constexpr int K1_NS = 6;
constexpr int K1_A_BYTES = 7 * 16384;
constexpr int K1_B_OFF = K1_A_BYTES;
constexpr int K1_STG_OFF = K1_B_OFF + K1_NS * 16384;
constexpr int K1_BAR_OFF = K1_STG_OFF + 8 * 2048;
constexpr int K1_SMEM = K1_BAR_OFF + 256 + 1024;

struct K1Ctx {
  uint32_t sb, bar_full, rel0, rel1;
  uint32_t dA, dBk, dBn;
  bool lane0;
};
__device__ __forceinline__ void k1_release(const K1Ctx& c, int slot) {
  if (c.lane0) {
    asm volatile("mbarrier.arrive.shared::cluster.b64 _, [%0];" ::"r"(c.rel0 + 8 * slot) : "memory");
    asm volatile("mbarrier.arrive.shared::cluster.b64 _, [%0];" ::"r"(c.rel1 + 8 * slot) : "memory");
  }
}

__device__ __forceinline__ void k1_unit_ab(const K1Ctx& c, int warp, int lane, int mt, int j) {
  const uint32_t stg = c.sb + K1_STG_OFF + warp * 2048;
  const int wq = warp & 3;
  const int st_row = (lane & 7) + 8 * ((lane >> 3) & 1);
  const int st_chunk = lane >> 4;
  float acc[2][56];
#pragma unroll
  for (int kb = 0; kb < 7; kb++) {
    constexpr int NS = K1_NS;
    const int slot = kb % NS; const uint32_t ph = (kb / NS) & 1;
    const int pslot = (kb + NS - 1) % NS;
    bool released = (kb == 0);
    if (!mbar_test(c.bar_full + 8 * slot, ph)) {
      if (kb > 0) { wg_wait<0>(); k1_release(c, pslot); released = true; }
      mbar_wait(c.bar_full + 8 * slot, ph, 3);
    }
    if (kb == 6) named_arrive(2, 256);
    if (kb == 0 && (threadIdx.x & 127) == 0) DBG(0, 4);
    if ((threadIdx.x & 127) == 0) DBGC(1, 46 + kb);
    wg_fence();
    const uint32_t da = c.dA + kb * 1024;
    const uint32_t db = c.dBk + slot * 1024;
#pragma unroll
    for (int k = 0; k < 4; k++) {
      wgmma_n112(acc[0], da + k * 2, db + k * 2, (kb | k) != 0);
      wgmma_n112(acc[1], da + 512 + k * 2, db + k * 2, (kb | k) != 0);
    }
    wg_commit();
    if (!released) { wg_wait<1>(); k1_release(c, pslot); }
  }
  wg_wait<0>();
  k1_release(c, 6 % K1_NS);
  if ((threadIdx.x & 127) == 0) DBG(0, 5);
  const uint32_t sgn = (j < 4) ? 0u : 0x80008000u;
  __nv_bfloat16* outp = g_ab + (size_t)((j < 4 ? 0 : 2048) + mt * 128) * 448 + (j & 3) * 112;
#pragma unroll
  for (int h = 0; h < 2; h++) {
    const int row0 = h * 64 + wq * 16;
#pragma unroll
    for (int g = 0; g < 8; g += 2) {
      const float* a = &acc[h][4 * g];
      stmatrix_x4(stg + st_row * 128 + (((g + st_chunk) ^ (st_row & 7)) * 16),
                  pack_bf16(a[0], a[1]) ^ sgn, pack_bf16(a[2], a[3]) ^ sgn, pack_bf16(a[4], a[5]) ^ sgn, pack_bf16(a[6], a[7]) ^ sgn);
    }
    __syncwarp();
    {
      uint4 v[4];
#pragma unroll
      for (int t = 0; t < 4; t++) { const int row = t * 4 + (lane >> 3); v[t] = lds128(stg + row * 128 + (((lane & 7) ^ (row & 7)) * 16)); }
      __nv_bfloat16* o = outp + (size_t)(row0 + (lane >> 3)) * 448 + (lane & 7) * 8;
#pragma unroll
      for (int t = 0; t < 4; t++) stg128(o + t * 4 * 448, v[t]);
    }
    __syncwarp();
#pragma unroll
    for (int g = 8; g < 14; g += 2) {
      const float* a = &acc[h][4 * g];
      stmatrix_x4(stg + st_row * 128 + (((g - 8 + st_chunk) ^ (st_row & 7)) * 16),
                  pack_bf16(a[0], a[1]) ^ sgn, pack_bf16(a[2], a[3]) ^ sgn, pack_bf16(a[4], a[5]) ^ sgn, pack_bf16(a[6], a[7]) ^ sgn);
    }
    __syncwarp();
    if ((lane & 7) < 6) {
      uint4 v[4];
#pragma unroll
      for (int t = 0; t < 4; t++) { const int row = t * 4 + (lane >> 3); v[t] = lds128(stg + row * 128 + (((lane & 7) ^ (row & 7)) * 16)); }
      __nv_bfloat16* o = outp + (size_t)(row0 + (lane >> 3)) * 448 + 64 + (lane & 7) * 8;
#pragma unroll
      for (int t = 0; t < 4; t++) stg128(o + t * 4 * 448, v[t]);
    }
    __syncwarp();
  }
}

template <bool HALF, int UNIT>
__device__ __forceinline__ void k1_unit_gu(const K1Ctx& c, int warp, int lane, int mt, int fb, int hsel) {
  const uint32_t stg = c.sb + K1_STG_OFF + warp * 2048;
  const int wq = warp & 3;
  const int st_row = (lane & 7) + 8 * ((lane >> 3) & 1);
  const int st_chunk = lane >> 4;
  constexpr int NH = HALF ? 1 : 2;
  constexpr int unit = UNIT;
  float acc[NH][64];
  const uint32_t dA0 = c.dA + (HALF ? hsel * 512 : 0);
  named_bar(2 + ((UNIT - 1) & 1), 256);
#pragma unroll
  for (int kb = 0; kb < 7; kb++) {
    constexpr int NS = K1_NS;
    const int s = UNIT * 7 + kb;
    const int slot = s % NS; const uint32_t ph = (s / NS) & 1;
    const int pslot = (s + NS - 1) % NS;
    bool released = (kb == 0);
    if (!mbar_test(c.bar_full + 8 * slot, ph)) {
      if (kb > 0) { wg_wait<0>(); k1_release(c, pslot); released = true; }
      mbar_wait(c.bar_full + 8 * slot, ph, 4 + UNIT);
    }
    if (kb == 6 && UNIT < 4) named_arrive(2 + (UNIT & 1), 256);
    if (kb == 0 && (threadIdx.x & 127) == 0) DBG(0, 4 + 3 * unit);
    wg_fence();
    const uint32_t da = dA0 + kb * 1024;
    const uint32_t db = c.dBn + slot * 1024;
#pragma unroll
    for (int k = 0; k < 4; k++) {
#pragma unroll
      for (int h = 0; h < NH; h++) wgmma_n128_tb(acc[h], da + h * 512 + k * 2, db + k * 128, (kb | k) != 0);
    }
    wg_commit();
    if (!released) { wg_wait<1>(); k1_release(c, pslot); }
  }
  wg_wait<0>();
  k1_release(c, (UNIT * 7 + 6) % K1_NS);
  if ((threadIdx.x & 127) == 0) DBG(0, 5 + 3 * unit);
  __nv_bfloat16* outp = g_h + (size_t)(mt * 128) * 1792 + fb * 64;
#pragma unroll
  for (int h = 0; h < NH; h++) {
    const int row0 = (HALF ? hsel : h) * 64 + wq * 16;
    uint32_t pk[16];
#pragma unroll
    for (int i = 0; i < 16; i++) {
      const uint32_t g2 = pack_bf16(acc[h][2 * i], acc[h][2 * i + 1]);
      const uint32_t u2 = pack_bf16(acc[h][32 + 2 * i], acc[h][32 + 2 * i + 1]);
      const uint32_t a2 = pack_bf16(gelu_tanh(bf_lo(g2)), gelu_tanh(bf_hi(g2)));
      pk[i] = hmul2_bf16(a2, u2);
    }
#pragma unroll
    for (int g = 0; g < 8; g += 2)
      stmatrix_x4(stg + st_row * 128 + (((g + st_chunk) ^ (st_row & 7)) * 16), pk[2 * g], pk[2 * g + 1], pk[2 * g + 2], pk[2 * g + 3]);
    __syncwarp();
    {
      uint4 v[4];
#pragma unroll
      for (int t = 0; t < 4; t++) { const int row = t * 4 + (lane >> 3); v[t] = lds128(stg + row * 128 + (((lane & 7) ^ (row & 7)) * 16)); }
      __nv_bfloat16* o = outp + (size_t)(row0 + (lane >> 3)) * 1792 + (lane & 7) * 8;
#pragma unroll
      for (int t = 0; t < 4; t++) stg128(o + t * 4 * 1792, v[t]);
    }
    __syncwarp();
  }
}

struct PfPtrs { const uint8_t* wr; const uint8_t* wi; const uint8_t* wg; const uint8_t* wu; const uint8_t* wd; const uint8_t* cr; const uint8_t* ci; };

__global__ void __cluster_dims__(2, 1, 1) __launch_bounds__(384, 1)
k1_kernel(const __grid_constant__ CUtensorMap tm_wr, const __grid_constant__ CUtensorMap tm_wi,
          const __grid_constant__ CUtensorMap tm_wg, const __grid_constant__ CUtensorMap tm_wu,
          const __nv_bfloat16* __restrict__ x, const PfPtrs pf) {
  extern __shared__ uint8_t smem_raw[];
  const uint32_t sb = (s2u(smem_raw) + 1023) & ~1023u;
  const int tid = threadIdx.x, warp = tid >> 5, lane = tid & 31;
  uint32_t rank;
  asm volatile("mov.u32 %0, %%cluster_ctarank;" : "=r"(rank));
  const int cid = blockIdx.x >> 1;
  const int p = cid >> 3, j = cid & 7;
  const int mt = 2 * p + (int)rank;
  const uint32_t bar_full = sb + K1_BAR_OFF;
  const uint32_t bar_empty = bar_full + 8 * K1_NS;
  const int fb_base = 7 * (j >> 1);
  const int fb0 = fb_base + ((j & 1) ? 4 : 0);
  const int fbh = fb_base + 3;
  const CUtensorMap* tw = (j < 4) ? &tm_wr : &tm_wi;
  const CUtensorMap* tgu = rank ? &tm_wu : &tm_wg;

  if (tid == 0) DBG(0, 0);
  if (tid == 256) {
    for (int i = 0; i < K1_NS; i++) { mbar_init(bar_full + 8 * i, 1); mbar_init(bar_empty + 8 * i, 8); }
    asm volatile("fence.mbarrier_init.release.cluster;" ::: "memory");
    prefetch_tmap(tw);
    prefetch_tmap(tgu);
    if (blockIdx.x < 64) g_flags[blockIdx.x] = 0;
  }
  __syncwarp();
  cluster_arrive_relaxed();
  pdl_launch();

  if (warp >= 8) {
    reg_dec<40>();
    cluster_wait();
    if (tid == 256) {
      int slot = 0; uint32_t ph = 0;
      for (int s = 0; s < 35; s++) {
        const int unit = s / 7, kb = s - unit * 7;
        if (s >= K1_NS) mbar_wait(bar_empty + 8 * slot, ph ^ 1, 2);
        DBG(0, 20 + s);
        const uint32_t dst = sb + K1_B_OFF + slot * 16384;
        if (unit == 0) {
          mbar_expect(bar_full + 8 * slot, 14336);
          tma2d_mc(dst + rank * 7168, tw, kb * 64, (j & 3) * 112 + rank * 56, bar_full + 8 * slot, 3);
        } else {
          const int fb = (unit == 4) ? fbh : (fb0 + unit - 1);
          mbar_expect(bar_full + 8 * slot, 16384);
          tma2d_mc(dst + rank * 8192, tgu, fb * 64, kb * 64, bar_full + 8 * slot, 3);
        }
        if (s >= K1_NS && s < K1_NS + 16) {
          const int i = s - K1_NS;
          l2_prefetch(pf.cr + (size_t)blockIdx.x * 65536 + i * 4096, 4096);
          l2_prefetch(pf.ci + (size_t)blockIdx.x * 65536 + i * 4096, 4096);
          if (i == 0) l2_prefetch(pf.wd + blockIdx.x * 12544, 12544);
        }
        if (++slot == K1_NS) { slot = 0; ph ^= 1; }
      }
    }
  } else {
    reg_inc<232>();
    const int wg = warp >> 2;
    {
      const int c = lane & 7;
      uint4 v[4][7];
#pragma unroll
      for (int pass = 0; pass < 4; pass++) {
        const int r = warp * 16 + pass * 4 + (lane >> 3);
        const uint4* src = reinterpret_cast<const uint4*>(x + (size_t)(mt * 128 + r) * 448) + c;
#pragma unroll
        for (int b = 0; b < 7; b++)
          asm volatile("ld.global.nc.v4.u32 {%0,%1,%2,%3}, [%4];" : "=r"(v[pass][b].x), "=r"(v[pass][b].y), "=r"(v[pass][b].z), "=r"(v[pass][b].w) : "l"(src + b * 8) : "memory");
      }
      if (tid == 0) {
        const int b = blockIdx.x;
        l2_prefetch(pf.wr + b * 3136, 3136);
        l2_prefetch(pf.wi + b * 3136, 3136);
        l2_prefetch(pf.wg + b * 12544, 12544);
        l2_prefetch(pf.wu + b * 12544, 12544);
      }
      float mean[4], rinv[4];
#pragma unroll
      for (int pass = 0; pass < 4; pass++) {
        float s0 = 0.f, s1 = 0.f, s2 = 0.f, s3 = 0.f;
#pragma unroll
        for (int b = 0; b < 7; b++) {
          s0 += bf_lo(v[pass][b].x) + bf_hi(v[pass][b].x); s1 += bf_lo(v[pass][b].y) + bf_hi(v[pass][b].y);
          s2 += bf_lo(v[pass][b].z) + bf_hi(v[pass][b].z); s3 += bf_lo(v[pass][b].w) + bf_hi(v[pass][b].w);
        }
        mean[pass] = (s0 + s1) + (s2 + s3);
      }
      if (lane == 0) DBG(0, 55 + (warp & 3));
      if (tid == 32) DBGC(1, 60);
#pragma unroll
      for (int o = 1; o < 8; o <<= 1) {
#pragma unroll
        for (int pass = 0; pass < 4; pass++) mean[pass] += __shfl_xor_sync(0xffffffffu, mean[pass], o);
      }
#pragma unroll
      for (int pass = 0; pass < 4; pass++) {
        mean[pass] *= (1.0f / 448.0f);
        const float m = mean[pass];
        float q0 = 0.f, q1 = 0.f, q2 = 0.f, q3 = 0.f;
#pragma unroll
        for (int b = 0; b < 7; b++) {
          float d;
          d = bf_lo(v[pass][b].x) - m; q0 = fmaf(d, d, q0); d = bf_hi(v[pass][b].x) - m; q1 = fmaf(d, d, q1);
          d = bf_lo(v[pass][b].y) - m; q2 = fmaf(d, d, q2); d = bf_hi(v[pass][b].y) - m; q3 = fmaf(d, d, q3);
          d = bf_lo(v[pass][b].z) - m; q0 = fmaf(d, d, q0); d = bf_hi(v[pass][b].z) - m; q1 = fmaf(d, d, q1);
          d = bf_lo(v[pass][b].w) - m; q2 = fmaf(d, d, q2); d = bf_hi(v[pass][b].w) - m; q3 = fmaf(d, d, q3);
        }
        rinv[pass] = (q0 + q1) + (q2 + q3);
      }
#pragma unroll
      for (int o = 1; o < 8; o <<= 1) {
#pragma unroll
        for (int pass = 0; pass < 4; pass++) rinv[pass] += __shfl_xor_sync(0xffffffffu, rinv[pass], o);
      }
#pragma unroll
      for (int pass = 0; pass < 4; pass++) {
        const float var_b = rbf(rinv[pass] * (1.0f / 448.0f));
        const float den = rbf(sqrtf(rbf(var_b + 1e-5f)));
        const float ri = 1.0f / den;
        const float rih = rbf(ri);
        const uint32_t rhi2 = pack_bf16(rih, rih), rlo2 = pack_bf16(ri - rih, ri - rih);
        const uint32_t m2 = pack_bf16(mean[pass], mean[pass]);
        const int r = warp * 16 + pass * 4 + (lane >> 3);
        const uint32_t a0 = sb + r * 128 + ((c ^ (r & 7)) * 16);
#pragma unroll
        for (int b = 0; b < 7; b++) {
          uint32_t w4[4] = {v[pass][b].x, v[pass][b].y, v[pass][b].z, v[pass][b].w};
#pragma unroll
          for (int q = 0; q < 4; q++) {
            const uint32_t dw = hsub2_bf16(w4[q], m2);
            w4[q] = hfma2_bf16(dw, rhi2, hmul2_bf16(dw, rlo2));
          }
          sts128(a0 + b * 16384, make_uint4(w4[0], w4[1], w4[2], w4[3]));
        }
      }
    }
    if (lane == 0) DBG(0, 59 + (warp & 3));
    if (tid == 32) DBGC(1, 61);
    asm volatile("fence.proxy.async.shared::cta;" ::: "memory");
    named_bar(1, 256);
    if (tid == 0) DBG(0, 2);
    cluster_wait();
    if (tid == 0) DBG(0, 3);

    K1Ctx c;
    c.sb = sb; c.bar_full = bar_full; c.lane0 = (lane == 0);
    asm volatile("mapa.shared::cluster.u32 %0, %1, %2;" : "=r"(c.rel0) : "r"(bar_empty), "r"(0));
    asm volatile("mapa.shared::cluster.u32 %0, %1, %2;" : "=r"(c.rel1) : "r"(bar_empty), "r"(1));
    c.dA = make_desc(sb, 16, 1024);
    c.dBk = make_desc(sb + K1_B_OFF, 16, 1024);
    c.dBn = make_desc(sb + K1_B_OFF, 8192, 1024);
    if (wg == 0) {
      k1_unit_ab(c, warp, lane, mt, j);
      if (tid == 0) DBG(0, 6);
      k1_unit_gu<false, 2>(c, warp, lane, mt, fb0 + 1, 0);
      if (tid == 0) DBG(0, 12);
      k1_unit_gu<true, 4>(c, warp, lane, mt, fbh, j & 1);
      if (tid == 0) DBG(0, 18);
    } else {
      k1_unit_gu<false, 1>(c, warp, lane, mt, fb0, 0);
      if (tid == 128) DBG(0, 9);
      k1_unit_gu<false, 3>(c, warp, lane, mt, fb0 + 2, 0);
      if (tid == 128) DBG(0, 15);
    }
  }
  __syncwarp();
  cluster_arrive_relaxed();
  cluster_wait();
}

constexpr int K2_NS = 4;
constexpr int K2_STAGE = 16384 + 32768;
constexpr int K2_BAR_OFF = K2_NS * K2_STAGE;
constexpr int K2_SMEM = K2_BAR_OFF + 256 + 1024;

__device__ __forceinline__ void flag_signal_wait(unsigned int* flag, unsigned int target, bool do_wait) {
  __threadfence();
  named_bar(1, 256);
  if (threadIdx.x == 0) {
    atomicAdd(flag, 1u);
    if (do_wait) {
      int it = 0;
      while (true) {
        unsigned int v;
        asm volatile("ld.acquire.gpu.global.u32 %0, [%1];" : "=r"(v) : "l"(flag) : "memory");
        if (v >= target) break;
        if (++it > SPIN_LIMIT) { TIMEOUT(20); break; }
      }
    }
  }
  if (do_wait) named_bar(1, 256);
}

constexpr int K2_PITCH = 464;

template <int Q>
__device__ __forceinline__ void k2_y_epilogue(float (&acc)[112], int tile, int tid, uint32_t sb, int mt, int n) {
  constexpr int G0 = (Q == 0) ? 0 : (Q == 1 ? 10 : 20);
  constexpr int G1 = (Q == 0) ? 10 : (Q == 1 ? 20 : 28);
  float4* part = g_part + (size_t)tile * (3 * 28 * 256) + tid;
#pragma unroll
  for (int g = 0; g < 28; g++) {
    if (g < G0 || g >= G1) part[(Q * 28 + g) * 256] = make_float4(acc[4 * g], acc[4 * g + 1], acc[4 * g + 2], acc[4 * g + 3]);
  }
  flag_signal_wait(&g_flags[tile], 3u, true);
  if (tid == 0) DBG(1, 30);
  constexpr int QA = (Q + 1) % 3, QB = (Q + 2) % 3;
  float4 va[G1 - G0], vb[G1 - G0];
#pragma unroll
  for (int g = G0; g < G1; g++) { va[g - G0] = __ldcg(&part[(QA * 28 + g) * 256]); vb[g - G0] = __ldcg(&part[(QB * 28 + g) * 256]); }
  const int warp = tid >> 5, lane = tid & 31;
  const uint32_t stg = sb + warp * 16 * K2_PITCH;
  const int st_row = (lane & 7) + 8 * ((lane >> 3) & 1);
  const int st_chunk = lane >> 4;
#pragma unroll
  for (int g = G0; g < G1; g += 2) {
    uint32_t pk[4];
#pragma unroll
    for (int e = 0; e < 2; e++) {
      const float4 a = va[g + e - G0], b = vb[g + e - G0];
      const float* c = &acc[4 * (g + e)];
      pk[2 * e] = pack_bf16(c[0] + a.x + b.x, c[1] + a.y + b.y);
      pk[2 * e + 1] = pack_bf16(c[2] + a.z + b.z, c[3] + a.w + b.w);
    }
    stmatrix_x4(stg + st_row * K2_PITCH + (g - G0 + st_chunk) * 16, pk[0], pk[1], pk[2], pk[3]);
  }
  __syncwarp();
  constexpr int NCH2 = (G1 - G0) / 2;
  __nv_bfloat16* sp = g_s + (size_t)(mt * 128 + warp * 16 + (lane >> 1)) * 448 + n * 224 + (G0 + (lane & 1) * NCH2) * 8;
  const uint32_t lp = stg + (lane >> 1) * K2_PITCH + (lane & 1) * NCH2 * 16;
#pragma unroll
  for (int t = 0; t < NCH2; t++) stg128(sp + t * 8, lds128(lp + t * 16));
  flag_signal_wait(&g_flags[32 + tile], 0u, false);
}

__global__ void __cluster_dims__(2, 1, 1) __launch_bounds__(384, 1)
k2_kernel(const __grid_constant__ CUtensorMap tm_cr, const __grid_constant__ CUtensorMap tm_ci, const __grid_constant__ CUtensorMap tm_h,
          const __grid_constant__ CUtensorMap tm_ab, const __grid_constant__ CUtensorMap tm_wd,
          const __nv_bfloat16* __restrict__ x, __nv_bfloat16* __restrict__ out) {
  extern __shared__ uint8_t smem_raw[];
  const uint32_t sb = (s2u(smem_raw) + 1023) & ~1023u;
  const int tid = threadIdx.x, warp = tid >> 5, lane = tid & 31;
  uint32_t rank;
  asm volatile("mov.u32 %0, %%cluster_ctarank;" : "=r"(rank));
  const int cid = blockIdx.x >> 1;
  const int q = cid & 3, n = (cid >> 2) & 1, p = cid >> 3;
  const int mt = 2 * p + (int)rank;
  const int tile = mt * 2 + n;
  const uint32_t bar_full = sb + K2_BAR_OFF;
  const uint32_t bar_empty = bar_full + 8 * K2_NS;
  const int g0 = (q == 0) ? 0 : (q == 1 ? 22 : (q == 2 ? 43 : 64));
  const int nkb = (q == 0) ? 22 : (q == 3 ? 28 : 21);

  if (tid == 0) DBG(1, 0);
  if (tid == 256) {
    for (int i = 0; i < K2_NS; i++) { mbar_init(bar_full + 8 * i, 1); mbar_init(bar_empty + 8 * i, 16); }
    asm volatile("fence.mbarrier_init.release.cluster;" ::: "memory");
    if (q == 3) { prefetch_tmap(&tm_h); prefetch_tmap(&tm_wd); }
    else { prefetch_tmap(&tm_cr); prefetch_tmap(&tm_ci); prefetch_tmap(&tm_ab); }
  }
  __syncwarp();
  cluster_arrive_relaxed();
  cluster_wait();

  if (warp >= 8) {
    reg_dec<40>();
    if (tid == 256) {
      auto load_a = [&](int g, uint32_t dst, uint32_t fb) {
        if (g < 32) tma2d(dst, &tm_cr, g * 64, mt * 128, fb);
        else if (g < 64) tma2d(dst, &tm_ci, (g - 32) * 64, mt * 128, fb);
        else tma2d(dst, &tm_h, (g - 64) * 64, mt * 128, fb);
      };
      auto load_b = [&](int g, uint32_t dst, uint32_t fb) {
        const CUtensorMap* tb = (g < 64) ? &tm_ab : &tm_wd;
        const int kbrow = (g < 64) ? g * 64 : (g - 64) * 64;
        tma3d_mc(dst + 16384 + (2 * rank) * 8192, tb, (2 * rank) * 64, n, kbrow, fb, 3);
        tma3d_mc(dst + 16384 + (2 * rank + 1) * 8192, tb, (2 * rank + 1) * 64, n, kbrow, fb, 3);
      };
      for (int s = 0; s < K2_NS; s++) {
        mbar_expect(bar_full + 8 * s, K2_STAGE);
        if (q < 3) load_a(g0 + s, sb + s * K2_STAGE, bar_full + 8 * s); else load_b(g0 + s, sb + s * K2_STAGE, bar_full + 8 * s);
      }
      pdl_wait();
      DBG(1, 31);
      for (int s = 0; s < K2_NS; s++) {
        if (q < 3) load_b(g0 + s, sb + s * K2_STAGE, bar_full + 8 * s); else load_a(g0 + s, sb + s * K2_STAGE, bar_full + 8 * s);
      }
      int slot = 0; uint32_t ph = 0;
      for (int s = K2_NS; s < nkb; s++) {
        mbar_wait(bar_empty + 8 * slot, ph, 10);
        const uint32_t dst = sb + slot * K2_STAGE;
        const uint32_t fb = bar_full + 8 * slot;
        mbar_expect(fb, K2_STAGE);
        load_a(g0 + s, dst, fb);
        load_b(g0 + s, dst, fb);
        if (++slot == K2_NS) { slot = 0; ph ^= 1; }
      }
    }
  } else {
    reg_inc<232>();
    const int wg = warp >> 2;
    float acc[112];
    int slot = 0; uint32_t ph = 0;
#pragma unroll 1
    for (int s = 0; s < nkb; s++) {
      mbar_wait(bar_full + 8 * slot, ph, 11);
      if (tid == 0) DBG(1, 1 + s);
      if (tid == 0 && (s == 5 || s == 15)) DBGC(1, 53 + (s == 15));
      if (tid == 0 && (s == 23 || s == 27)) DBGC(1, 55 + (s == 27));
      wg_fence();
      const uint32_t da = make_desc(sb + slot * K2_STAGE + wg * 8192, 16, 1024);
      const uint32_t db = make_desc(sb + slot * K2_STAGE + 16384, 8192, 1024);
#pragma unroll
      for (int k = 0; k < 4; k++) wgmma_n224_tb(acc, da + k * 2, db + k * 128, (s | k) != 0);
      wg_commit();
      if (s > 0) {
        wg_wait<1>();
        const int ps = (slot + K2_NS - 1) % K2_NS;
        if (lane == 0) { mbar_arrive_cluster(bar_empty + 8 * ps, 0); mbar_arrive_cluster(bar_empty + 8 * ps, 1); }
      }
      if (++slot == K2_NS) { slot = 0; ph ^= 1; }
    }
    wg_wait<0>();
    pdl_wait();
    named_bar(1, 256);
    if (tid == 0) DBG(1, 29);
    if (q == 0) k2_y_epilogue<0>(acc, tile, tid, sb, mt, n);
    else if (q == 1) k2_y_epilogue<1>(acc, tile, tid, sb, mt, n);
    else if (q == 2) k2_y_epilogue<2>(acc, tile, tid, sb, mt, n);
    else {
      const uint32_t stg = sb + warp * 16 * K2_PITCH;
      const int st_row = (lane & 7) + 8 * ((lane >> 3) & 1);
      const int st_chunk = lane >> 4;
#pragma unroll
      for (int g = 0; g < 28; g += 2) {
        uint32_t pk[4];
#pragma unroll
        for (int e = 0; e < 4; e++) {
          const uint32_t f2 = pack_bf16(acc[4 * g + 2 * e], acc[4 * g + 2 * e + 1]);
          pk[e] = pack_bf16(silu_f(bf_lo(f2)), silu_f(bf_hi(f2)));
        }
        stmatrix_x4(stg + st_row * K2_PITCH + (g + st_chunk) * 16, pk[0], pk[1], pk[2], pk[3]);
      }
      const size_t gbase = (size_t)(mt * 128 + warp * 16) * 448 + n * 224 + (lane < 28 ? lane : 0) * 8;
      const __nv_bfloat16* xp = x + gbase;
      uint4 xv[16];
#pragma unroll
      for (int t = 0; t < 16; t++) xv[t] = ldg128_cg(xp + t * 448);
      if (lane == 0) {
        int it = 0;
        while (true) {
          unsigned int v;
          asm volatile("ld.acquire.gpu.global.u32 %0, [%1];" : "=r"(v) : "l"(&g_flags[32 + tile]) : "memory");
          if (v >= 3u) break;
          if (++it > SPIN_LIMIT) { TIMEOUT(21); break; }
        }
      }
      __syncwarp();
      if (tid == 0) DBG(1, 30);
      const __nv_bfloat16* sp = g_s + gbase;
      uint4 sv[16];
#pragma unroll
      for (int t = 0; t < 16; t++) sv[t] = ldg128_cg(sp + t * 448);
      __nv_bfloat16* op = out + gbase;
      const uint32_t lp = stg + (lane < 28 ? lane : 0) * 16;
#pragma unroll
      for (int t = 0; t < 16; t++) {
        const uint4 gv = lds128(lp + t * K2_PITCH);
        uint4 o;
        o.x = hadd2_bf16(xv[t].x, hmul2_bf16(sv[t].x, gv.x));
        o.y = hadd2_bf16(xv[t].y, hmul2_bf16(sv[t].y, gv.y));
        o.z = hadd2_bf16(xv[t].z, hmul2_bf16(sv[t].z, gv.z));
        o.w = hadd2_bf16(xv[t].w, hmul2_bf16(sv[t].w, gv.w));
        if (lane < 28) stg128(op + t * 448, o);
      }
    }
    if (tid == 0) DBG(1, 63);
  }
  __syncwarp();
  cluster_arrive_relaxed();
  cluster_wait();
}

typedef CUresult (*EncFn)(CUtensorMap*, CUtensorMapDataType, cuuint32_t, void*, const cuuint64_t*, const cuuint64_t*, const cuuint32_t*,
                          const cuuint32_t*, CUtensorMapInterleave, CUtensorMapSwizzle, CUtensorMapL2promotion, CUtensorMapFloatOOBfill);

void make2d(EncFn enc, CUtensorMap* tm, const void* ptr, uint64_t cols, uint64_t rows, uint32_t bc, uint32_t br) {
  cuuint64_t gd[2] = {cols, rows};
  cuuint64_t gs[1] = {cols * 2};
  cuuint32_t bd[2] = {bc, br};
  cuuint32_t es[2] = {1, 1};
  enc(tm, CU_TENSOR_MAP_DATA_TYPE_BFLOAT16, 2, const_cast<void*>(ptr), gd, gs, bd, es, CU_TENSOR_MAP_INTERLEAVE_NONE,
      CU_TENSOR_MAP_SWIZZLE_128B, CU_TENSOR_MAP_L2_PROMOTION_L2_128B, CU_TENSOR_MAP_FLOAT_OOB_FILL_NONE);
}
void make3d_half(EncFn enc, CUtensorMap* tm, const void* ptr, uint64_t rows) {
  cuuint64_t gd[3] = {224, 2, rows};
  cuuint64_t gs[2] = {448, 896};
  cuuint32_t bd[3] = {64, 1, 64};
  cuuint32_t es[3] = {1, 1, 1};
  enc(tm, CU_TENSOR_MAP_DATA_TYPE_BFLOAT16, 3, const_cast<void*>(ptr), gd, gs, bd, es, CU_TENSOR_MAP_INTERLEAVE_NONE,
      CU_TENSOR_MAP_SWIZZLE_128B, CU_TENSOR_MAP_L2_PROMOTION_L2_128B, CU_TENSOR_MAP_FLOAT_OOB_FILL_NONE);
}

struct Maps { CUtensorMap wr, wi, wg, wu, cr, ci, h, ab, wd; };

}

extern "C" void kernel_launch(void* const* d_in, const int* in_sizes, int n_in, void* d_out, int out_size) {
  (void)in_sizes; (void)n_in; (void)out_size;
  static Maps maps;
  static const void* cached[9] = {nullptr};
  static bool attr_done = false;
  bool same = true;
  for (int i = 0; i < 9; i++) same = same && (cached[i] == d_in[i]);
  if (!same) {
    void* fn = nullptr;
    cudaDriverEntryPointQueryResult qr;
    cudaGetDriverEntryPoint("cuTensorMapEncodeTiled", &fn, cudaEnableDefault, &qr);
    EncFn enc = (EncFn)fn;
    void *p_ab = nullptr, *p_h = nullptr;
    cudaGetSymbolAddress(&p_ab, g_ab);
    cudaGetSymbolAddress(&p_h, g_h);
    make2d(enc, &maps.cr, d_in[1], 2048, 2048, 64, 128);
    make2d(enc, &maps.ci, d_in[2], 2048, 2048, 64, 128);
    make2d(enc, &maps.wr, d_in[3], 448, 448, 64, 56);
    make2d(enc, &maps.wi, d_in[4], 448, 448, 64, 56);
    make2d(enc, &maps.wg, d_in[6], 1792, 448, 64, 64);
    make2d(enc, &maps.wu, d_in[7], 1792, 448, 64, 64);
    make3d_half(enc, &maps.wd, d_in[8], 1792);
    make2d(enc, &maps.h, p_h, 1792, 2048, 64, 128);
    make3d_half(enc, &maps.ab, p_ab, 4096);
    for (int i = 0; i < 9; i++) cached[i] = d_in[i];
  }
  if (!attr_done) {
    cudaFuncSetAttribute(k1_kernel, cudaFuncAttributeMaxDynamicSharedMemorySize, K1_SMEM);
    cudaFuncSetAttribute(k2_kernel, cudaFuncAttributeMaxDynamicSharedMemorySize, K2_SMEM);
    attr_done = true;
  }
  PfPtrs pf;
  pf.wr = (const uint8_t*)d_in[3]; pf.wi = (const uint8_t*)d_in[4]; pf.wg = (const uint8_t*)d_in[6]; pf.wu = (const uint8_t*)d_in[7];
  pf.wd = (const uint8_t*)d_in[8]; pf.cr = (const uint8_t*)d_in[1]; pf.ci = (const uint8_t*)d_in[2];
  k1_kernel<<<128, 384, K1_SMEM>>>(maps.wr, maps.wi, maps.wg, maps.wu, (const __nv_bfloat16*)d_in[0], pf);

  cudaLaunchConfig_t cfg = {};
  cfg.gridDim = dim3(128); cfg.blockDim = dim3(384); cfg.dynamicSmemBytes = K2_SMEM; cfg.stream = cudaStreamPerThread;
  cudaLaunchAttribute at[1];
  at[0].id = cudaLaunchAttributeProgrammaticStreamSerialization;
  at[0].val.programmaticStreamSerializationAllowed = 1;
  cfg.attrs = at; cfg.numAttrs = 1;
  cudaLaunchKernelEx(&cfg, k2_kernel, maps.cr, maps.ci, maps.h, maps.ab, maps.wd, (const __nv_bfloat16*)d_in[0], (__nv_bfloat16*)d_out);
}
```

```cpp
#include <cuda_runtime.h>
#include <cuda_bf16.h>
#include <cuda.h>
#include <stdint.h>

namespace {

__device__ __align__(1024) __nv_bfloat16 g_ab[4096 * 448];
__device__ __align__(1024) __nv_bfloat16 g_h[2048 * 1792];
__device__ float4 g_part[32 * 3 * 28 * 256];
__device__ __align__(1024) __nv_bfloat16 g_s[2048 * 448];
__device__ unsigned int g_flags[64];

#define DBG(k, i) do {} while (0)
#define DBGC(k, i) do {} while (0)

#define TIMEOUT(code) __trap()
#define SPIN_LIMIT (1 << 22)
__device__ __forceinline__ uint32_t s2u(const void* p) { return (uint32_t)__cvta_generic_to_shared(p); }
__device__ __forceinline__ void mbar_init(uint32_t b, int c) { asm volatile("mbarrier.init.shared::cta.b64 [%0], %1;" ::"r"(b), "r"(c)); }
__device__ __forceinline__ void mbar_expect(uint32_t b, uint32_t bytes) {
  asm volatile("mbarrier.arrive.expect_tx.shared::cta.b64 _, [%0], %1;" ::"r"(b), "r"(bytes) : "memory");
}
__device__ __forceinline__ void mbar_wait(uint32_t b, uint32_t ph, int code = 1) {
  uint32_t done = 0;
  int it = 0;
  while (true) {
    asm volatile("{.reg .pred p; mbarrier.try_wait.parity.shared::cta.b64 p, [%1], %2; selp.u32 %0,1,0,p;}" : "=r"(done) : "r"(b), "r"(ph) : "memory");
    if (done) break;
    if (++it > SPIN_LIMIT) { TIMEOUT(code); break; }
  }
}
__device__ __forceinline__ void mbar_arrive_cluster(uint32_t b, uint32_t cta) {
  uint32_t r;
  asm volatile("mapa.shared::cluster.u32 %0, %1, %2;" : "=r"(r) : "r"(b), "r"(cta));
  asm volatile("mbarrier.arrive.shared::cluster.b64 _, [%0];" ::"r"(r) : "memory");
}
__device__ __forceinline__ void tma2d(uint32_t dst, const CUtensorMap* m, int c0, int c1, uint32_t bar) {
  asm volatile("cp.async.bulk.tensor.2d.shared::cluster.global.mbarrier::complete_tx::bytes [%0], [%1, {%3,%4}], [%2];" ::"r"(dst), "l"(m), "r"(bar), "r"(c0), "r"(c1) : "memory");
}
__device__ __forceinline__ void tma2d_mc(uint32_t dst, const CUtensorMap* m, int c0, int c1, uint32_t bar, uint16_t mask) {
  asm volatile("cp.async.bulk.tensor.2d.shared::cluster.global.mbarrier::complete_tx::bytes.multicast::cluster [%0], [%1, {%3,%4}], [%2], %5;" ::"r"(dst), "l"(m), "r"(bar), "r"(c0), "r"(c1), "h"(mask) : "memory");
}
__device__ __forceinline__ void tma3d_mc(uint32_t dst, const CUtensorMap* m, int c0, int c1, int c2, uint32_t bar, uint16_t mask) {
  asm volatile("cp.async.bulk.tensor.3d.shared::cluster.global.mbarrier::complete_tx::bytes.multicast::cluster [%0], [%1, {%3,%4,%5}], [%2], %6;" ::"r"(dst), "l"(m), "r"(bar), "r"(c0), "r"(c1), "r"(c2), "h"(mask) : "memory");
}
__device__ __forceinline__ void prefetch_tmap(const CUtensorMap* m) { asm volatile("prefetch.tensormap [%0];" ::"l"(m) : "memory"); }
__device__ __forceinline__ void l2_prefetch(const void* p, uint32_t bytes) {
  asm volatile("cp.async.bulk.prefetch.L2.global [%0], %1;" ::"l"(p), "r"(bytes) : "memory");
}
__device__ __forceinline__ void cluster_arrive_relaxed() { asm volatile("barrier.cluster.arrive.relaxed.aligned;" ::: "memory"); }
__device__ __forceinline__ void cluster_wait() { asm volatile("barrier.cluster.wait.aligned;" ::: "memory"); }
__device__ __forceinline__ void wg_fence() { __syncwarp(); asm volatile("wgmma.fence.sync.aligned;" ::: "memory"); }
__device__ __forceinline__ void wg_commit() { asm volatile("wgmma.commit_group.sync.aligned;" ::: "memory"); }
template <int N> __device__ __forceinline__ void wg_wait() { __syncwarp(); asm volatile("wgmma.wait_group.sync.aligned %0;" ::"n"(N) : "memory"); }
__device__ __forceinline__ void named_bar(int id, int n) { asm volatile("bar.sync %0, %1;" ::"r"(id), "r"(n) : "memory"); }
__device__ __forceinline__ void named_arrive(int id, int n) { asm volatile("bar.arrive %0, %1;" ::"r"(id), "r"(n) : "memory"); }
template <int N> __device__ __forceinline__ void reg_inc() { asm volatile("setmaxnreg.inc.sync.aligned.u32 %0;" ::"n"(N)); }
template <int N> __device__ __forceinline__ void reg_dec() { asm volatile("setmaxnreg.dec.sync.aligned.u32 %0;" ::"n"(N)); }
__device__ __forceinline__ void pdl_wait() { asm volatile("griddepcontrol.wait;" ::: "memory"); }
__device__ __forceinline__ void pdl_launch() { asm volatile("griddepcontrol.launch_dependents;" ::: "memory"); }

__device__ __forceinline__ uint32_t make_desc(uint32_t addr, uint32_t lbo, uint32_t  ) {
  return ((addr & 0x3FFFF) >> 4) | ((lbo >> 4) << 16);
}
__device__ __forceinline__ void stmatrix_x4(uint32_t addr, uint32_t r0, uint32_t r1, uint32_t r2, uint32_t r3) {
  asm volatile("stmatrix.sync.aligned.m8n8.x4.shared.b16 [%0], {%1,%2,%3,%4};" ::"r"(addr), "r"(r0), "r"(r1), "r"(r2), "r"(r3) : "memory");
}
__device__ __forceinline__ uint4 lds128(uint32_t a) {
  uint4 v;
  asm volatile("ld.shared.v4.u32 {%0,%1,%2,%3}, [%4];" : "=r"(v.x), "=r"(v.y), "=r"(v.z), "=r"(v.w) : "r"(a) : "memory");
  return v;
}
__device__ __forceinline__ void sts128(uint32_t a, uint4 v) {
  asm volatile("st.shared.v4.u32 [%0], {%1,%2,%3,%4};" ::"r"(a), "r"(v.x), "r"(v.y), "r"(v.z), "r"(v.w) : "memory");
}
__device__ __forceinline__ void stg128(void* p, uint4 v) {
  asm volatile("st.global.v4.u32 [%0], {%1,%2,%3,%4};" ::"l"(p), "r"(v.x), "r"(v.y), "r"(v.z), "r"(v.w) : "memory");
}
__device__ __forceinline__ uint32_t pack_bf16(float lo, float hi) {
  uint32_t r;
  asm("cvt.rn.bf16x2.f32 %0, %1, %2;" : "=r"(r) : "f"(hi), "f"(lo));
  return r;
}
__device__ __forceinline__ uint32_t hmul2_bf16(uint32_t a, uint32_t b) {
  uint32_t r;
  asm("mul.rn.bf16x2 %0, %1, %2;" : "=r"(r) : "r"(a), "r"(b));
  return r;
}
__device__ __forceinline__ uint32_t hsub2_bf16(uint32_t a, uint32_t b) {
  uint32_t r;
  asm("sub.rn.bf16x2 %0, %1, %2;" : "=r"(r) : "r"(a), "r"(b));
  return r;
}
__device__ __forceinline__ uint32_t hadd2_bf16(uint32_t a, uint32_t b) {
  uint32_t r;
  asm("add.rn.bf16x2 %0, %1, %2;" : "=r"(r) : "r"(a), "r"(b));
  return r;
}
__device__ __forceinline__ uint32_t hfma2_bf16(uint32_t a, uint32_t b, uint32_t c) {
  uint32_t r;
  asm("fma.rn.bf16x2 %0, %1, %2, %3;" : "=r"(r) : "r"(a), "r"(b), "r"(c));
  return r;
}
__device__ __forceinline__ bool mbar_test(uint32_t b, uint32_t ph) {
  uint32_t done;
  asm volatile("{.reg .pred p; mbarrier.test_wait.parity.shared::cta.b64 p, [%1], %2; selp.u32 %0,1,0,p;}" : "=r"(done) : "r"(b), "r"(ph) : "memory");
  return __all_sync(0xffffffffu, done != 0);
}
__device__ __forceinline__ uint4 ldg128_cg(const void* p) {
  uint4 v;
  asm volatile("ld.global.cg.v4.u32 {%0,%1,%2,%3}, [%4];" : "=r"(v.x), "=r"(v.y), "=r"(v.z), "=r"(v.w) : "l"(p) : "memory");
  return v;
}
__device__ __forceinline__ float bf_lo(uint32_t w) { return __uint_as_float(w << 16); }
__device__ __forceinline__ float bf_hi(uint32_t w) { return __uint_as_float(w & 0xffff0000u); }
__device__ __forceinline__ float rbf(float x) { return __bfloat162float(__float2bfloat16_rn(x)); }
__device__ __forceinline__ float ex2f(float x) { float r; asm("ex2.approx.ftz.f32 %0, %1;" : "=f"(r) : "f"(x)); return r; }
__device__ __forceinline__ float rcpf(float x) { float r; asm("rcp.approx.ftz.f32 %0, %1;" : "=f"(r) : "f"(x)); return r; }
__device__ __forceinline__ float gelu_tanh(float x) {
  const float c1 = -2.0f * 0.7978845608028654f * 1.4426950408889634f;
  const float c2 = c1 * 0.044715f;
  const float e = ex2f(x * fmaf(c2, x * x, c1));
  return x * rcpf(1.0f + e);
}
__device__ __forceinline__ float silu_f(float x) {
  const float e = ex2f(-1.4426950408889634f * x);
  return x * rcpf(1.0f + e);
}

__device__ __forceinline__ void wgmma_n128_tb(float (&d)[64], uint32_t da, uint32_t db, int scale_d) {
  asm volatile(
    "{\n.reg .pred p;\n.reg .b64 da, db;\nsetp.ne.b32 p, %66, 0;\n"
    "mov.b64 da, {%64, 0x40000040};\nmov.b64 db, {%65, 0x40000040};\n"
    "wgmma.mma_async.sync.aligned.m64n128k16.f32.bf16.bf16 {%0, %1, %2, %3, %4, %5, %6, %7, %8, %9, %10, %11, %12, %13, %14, %15, %16, %17, %18, %19, %20, %21, %22, %23, %24, %25, %26, %27, %28, %29, %30, %31, %32, %33, %34, %35, %36, %37, %38, %39, %40, %41, %42, %43, %44, %45, %46, %47, %48, %49, %50, %51, %52, %53, %54, %55, %56, %57, %58, %59, %60, %61, %62, %63}, da, db, p, 1, 1, 0, 1;\n}\n"
    : "+f"(d[0]), "+f"(d[1]), "+f"(d[2]), "+f"(d[3]), "+f"(d[4]), "+f"(d[5]), "+f"(d[6]), "+f"(d[7]), "+f"(d[8]), "+f"(d[9]), "+f"(d[10]), "+f"(d[11]), "+f"(d[12]), "+f"(d[13]), "+f"(d[14]), "+f"(d[15]), "+f"(d[16]), "+f"(d[17]), "+f"(d[18]), "+f"(d[19]), "+f"(d[20]), "+f"(d[21]), "+f"(d[22]), "+f"(d[23]), "+f"(d[24]), "+f"(d[25]), "+f"(d[26]), "+f"(d[27]), "+f"(d[28]), "+f"(d[29]), "+f"(d[30]), "+f"(d[31]), "+f"(d[32]), "+f"(d[33]), "+f"(d[34]), "+f"(d[35]), "+f"(d[36]), "+f"(d[37]), "+f"(d[38]), "+f"(d[39]), "+f"(d[40]), "+f"(d[41]), "+f"(d[42]), "+f"(d[43]), "+f"(d[44]), "+f"(d[45]), "+f"(d[46]), "+f"(d[47]), "+f"(d[48]), "+f"(d[49]), "+f"(d[50]), "+f"(d[51]), "+f"(d[52]), "+f"(d[53]), "+f"(d[54]), "+f"(d[55]), "+f"(d[56]), "+f"(d[57]), "+f"(d[58]), "+f"(d[59]), "+f"(d[60]), "+f"(d[61]), "+f"(d[62]), "+f"(d[63])
    : "r"(da), "r"(db), "r"(scale_d));
}
__device__ __forceinline__ void wgmma_n128_tb_p(float (&d)[64], uint32_t da, uint32_t db, int scale_d, int enable) {
  asm volatile(
    "{\n.reg .pred p;\n.reg .b64 da, db;\nsetp.ne.b32 p, %66, 0;\n.reg .pred q;\nsetp.ne.b32 q, %67, 0;\n"
    "mov.b64 da, {%64, 0x40000040};\nmov.b64 db, {%65, 0x40000040};\n"
    "@q wgmma.mma_async.sync.aligned.m64n128k16.f32.bf16.bf16 {%0, %1, %2, %3, %4, %5, %6, %7, %8, %9, %10, %11, %12, %13, %14, %15, %16, %17, %18, %19, %20, %21, %22, %23, %24, %25, %26, %27, %28, %29, %30, %31, %32, %33, %34, %35, %36, %37, %38, %39, %40, %41, %42, %43, %44, %45, %46, %47, %48, %49, %50, %51, %52, %53, %54, %55, %56, %57, %58, %59, %60, %61, %62, %63}, da, db, p, 1, 1, 0, 1;\n}\n"
    : "+f"(d[0]), "+f"(d[1]), "+f"(d[2]), "+f"(d[3]), "+f"(d[4]), "+f"(d[5]), "+f"(d[6]), "+f"(d[7]), "+f"(d[8]), "+f"(d[9]), "+f"(d[10]), "+f"(d[11]), "+f"(d[12]), "+f"(d[13]), "+f"(d[14]), "+f"(d[15]), "+f"(d[16]), "+f"(d[17]), "+f"(d[18]), "+f"(d[19]), "+f"(d[20]), "+f"(d[21]), "+f"(d[22]), "+f"(d[23]), "+f"(d[24]), "+f"(d[25]), "+f"(d[26]), "+f"(d[27]), "+f"(d[28]), "+f"(d[29]), "+f"(d[30]), "+f"(d[31]), "+f"(d[32]), "+f"(d[33]), "+f"(d[34]), "+f"(d[35]), "+f"(d[36]), "+f"(d[37]), "+f"(d[38]), "+f"(d[39]), "+f"(d[40]), "+f"(d[41]), "+f"(d[42]), "+f"(d[43]), "+f"(d[44]), "+f"(d[45]), "+f"(d[46]), "+f"(d[47]), "+f"(d[48]), "+f"(d[49]), "+f"(d[50]), "+f"(d[51]), "+f"(d[52]), "+f"(d[53]), "+f"(d[54]), "+f"(d[55]), "+f"(d[56]), "+f"(d[57]), "+f"(d[58]), "+f"(d[59]), "+f"(d[60]), "+f"(d[61]), "+f"(d[62]), "+f"(d[63])
    : "r"(da), "r"(db), "r"(scale_d), "r"(enable));
}
__device__ __forceinline__ void wgmma_n112(float (&d)[56], uint32_t da, uint32_t db, int scale_d) {
  asm volatile(
    "{\n.reg .pred p;\n.reg .b64 da, db;\nsetp.ne.b32 p, %58, 0;\n"
    "mov.b64 da, {%56, 0x40000040};\nmov.b64 db, {%57, 0x40000040};\n"
    "wgmma.mma_async.sync.aligned.m64n112k16.f32.bf16.bf16 {%0, %1, %2, %3, %4, %5, %6, %7, %8, %9, %10, %11, %12, %13, %14, %15, %16, %17, %18, %19, %20, %21, %22, %23, %24, %25, %26, %27, %28, %29, %30, %31, %32, %33, %34, %35, %36, %37, %38, %39, %40, %41, %42, %43, %44, %45, %46, %47, %48, %49, %50, %51, %52, %53, %54, %55}, da, db, p, 1, 1, 0, 0;\n}\n"
    : "+f"(d[0]), "+f"(d[1]), "+f"(d[2]), "+f"(d[3]), "+f"(d[4]), "+f"(d[5]), "+f"(d[6]), "+f"(d[7]), "+f"(d[8]), "+f"(d[9]), "+f"(d[10]), "+f"(d[11]), "+f"(d[12]), "+f"(d[13]), "+f"(d[14]), "+f"(d[15]), "+f"(d[16]), "+f"(d[17]), "+f"(d[18]), "+f"(d[19]), "+f"(d[20]), "+f"(d[21]), "+f"(d[22]), "+f"(d[23]), "+f"(d[24]), "+f"(d[25]), "+f"(d[26]), "+f"(d[27]), "+f"(d[28]), "+f"(d[29]), "+f"(d[30]), "+f"(d[31]), "+f"(d[32]), "+f"(d[33]), "+f"(d[34]), "+f"(d[35]), "+f"(d[36]), "+f"(d[37]), "+f"(d[38]), "+f"(d[39]), "+f"(d[40]), "+f"(d[41]), "+f"(d[42]), "+f"(d[43]), "+f"(d[44]), "+f"(d[45]), "+f"(d[46]), "+f"(d[47]), "+f"(d[48]), "+f"(d[49]), "+f"(d[50]), "+f"(d[51]), "+f"(d[52]), "+f"(d[53]), "+f"(d[54]), "+f"(d[55])
    : "r"(da), "r"(db), "r"(scale_d));
}
__device__ __forceinline__ void wgmma_n224_tb(float (&d)[112], uint32_t da, uint32_t db, int scale_d) {
  asm volatile(
    "{\n.reg .pred p;\n.reg .b64 da, db;\nsetp.ne.b32 p, %114, 0;\n"
    "mov.b64 da, {%112, 0x40000040};\nmov.b64 db, {%113, 0x40000040};\n"
    "wgmma.mma_async.sync.aligned.m64n224k16.f32.bf16.bf16 {%0, %1, %2, %3, %4, %5, %6, %7, %8, %9, %10, %11, %12, %13, %14, %15, %16, %17, %18, %19, %20, %21, %22, %23, %24, %25, %26, %27, %28, %29, %30, %31, %32, %33, %34, %35, %36, %37, %38, %39, %40, %41, %42, %43, %44, %45, %46, %47, %48, %49, %50, %51, %52, %53, %54, %55, %56, %57, %58, %59, %60, %61, %62, %63, %64, %65, %66, %67, %68, %69, %70, %71, %72, %73, %74, %75, %76, %77, %78, %79, %80, %81, %82, %83, %84, %85, %86, %87, %88, %89, %90, %91, %92, %93, %94, %95, %96, %97, %98, %99, %100, %101, %102, %103, %104, %105, %106, %107, %108, %109, %110, %111}, da, db, p, 1, 1, 0, 1;\n}\n"
    : "+f"(d[0]), "+f"(d[1]), "+f"(d[2]), "+f"(d[3]), "+f"(d[4]), "+f"(d[5]), "+f"(d[6]), "+f"(d[7]), "+f"(d[8]), "+f"(d[9]), "+f"(d[10]), "+f"(d[11]), "+f"(d[12]), "+f"(d[13]), "+f"(d[14]), "+f"(d[15]), "+f"(d[16]), "+f"(d[17]), "+f"(d[18]), "+f"(d[19]), "+f"(d[20]), "+f"(d[21]), "+f"(d[22]), "+f"(d[23]), "+f"(d[24]), "+f"(d[25]), "+f"(d[26]), "+f"(d[27]), "+f"(d[28]), "+f"(d[29]), "+f"(d[30]), "+f"(d[31]), "+f"(d[32]), "+f"(d[33]), "+f"(d[34]), "+f"(d[35]), "+f"(d[36]), "+f"(d[37]), "+f"(d[38]), "+f"(d[39]), "+f"(d[40]), "+f"(d[41]), "+f"(d[42]), "+f"(d[43]), "+f"(d[44]), "+f"(d[45]), "+f"(d[46]), "+f"(d[47]), "+f"(d[48]), "+f"(d[49]), "+f"(d[50]), "+f"(d[51]), "+f"(d[52]), "+f"(d[53]), "+f"(d[54]), "+f"(d[55]), "+f"(d[56]), "+f"(d[57]), "+f"(d[58]), "+f"(d[59]), "+f"(d[60]), "+f"(d[61]), "+f"(d[62]), "+f"(d[63]), "+f"(d[64]), "+f"(d[65]), "+f"(d[66]), "+f"(d[67]), "+f"(d[68]), "+f"(d[69]), "+f"(d[70]), "+f"(d[71]), "+f"(d[72]), "+f"(d[73]), "+f"(d[74]), "+f"(d[75]), "+f"(d[76]), "+f"(d[77]), "+f"(d[78]), "+f"(d[79]), "+f"(d[80]), "+f"(d[81]), "+f"(d[82]), "+f"(d[83]), "+f"(d[84]), "+f"(d[85]), "+f"(d[86]), "+f"(d[87]), "+f"(d[88]), "+f"(d[89]), "+f"(d[90]), "+f"(d[91]), "+f"(d[92]), "+f"(d[93]), "+f"(d[94]), "+f"(d[95]), "+f"(d[96]), "+f"(d[97]), "+f"(d[98]), "+f"(d[99]), "+f"(d[100]), "+f"(d[101]), "+f"(d[102]), "+f"(d[103]), "+f"(d[104]), "+f"(d[105]), "+f"(d[106]), "+f"(d[107]), "+f"(d[108]), "+f"(d[109]), "+f"(d[110]), "+f"(d[111])
    : "r"(da), "r"(db), "r"(scale_d));
}

constexpr int K1_NS = 6;
constexpr int K1_A_BYTES = 7 * 16384;
constexpr int K1_B_OFF = K1_A_BYTES;
constexpr int K1_STG_OFF = K1_B_OFF + K1_NS * 16384;
constexpr int K1_BAR_OFF = K1_STG_OFF + 8 * 2048;
constexpr int K1_SMEM = K1_BAR_OFF + 256 + 1024;

struct K1Ctx {
  uint32_t sb, bar_full, rel0, rel1;
  uint32_t dA, dBk, dBn;
  bool lane0;
};
__device__ __forceinline__ void k1_release(const K1Ctx& c, int slot) {
  if (c.lane0) {
    asm volatile("mbarrier.arrive.shared::cluster.b64 _, [%0];" ::"r"(c.rel0 + 8 * slot) : "memory");
    asm volatile("mbarrier.arrive.shared::cluster.b64 _, [%0];" ::"r"(c.rel1 + 8 * slot) : "memory");
  }
}

__device__ __noinline__ void geglu_tile(uint32_t stg, __nv_bfloat16* gptr  , int lane) {
  const int row = lane >> 1;
  const uint32_t base = stg + row * 64;
  const int sw = (row >> 1) & 3;
#pragma unroll 1
  for (int i = 0; i < 2; i++) {
    const uint32_t a = base + ((((lane & 1) * 2 + i) ^ sw) * 16);
    const uint4 g = lds128(a), u = lds128(a + 1024);
    uint4 o;
    o.x = hmul2_bf16(pack_bf16(gelu_tanh(bf_lo(g.x)), gelu_tanh(bf_hi(g.x))), u.x);
    o.y = hmul2_bf16(pack_bf16(gelu_tanh(bf_lo(g.y)), gelu_tanh(bf_hi(g.y))), u.y);
    o.z = hmul2_bf16(pack_bf16(gelu_tanh(bf_lo(g.z)), gelu_tanh(bf_hi(g.z))), u.z);
    o.w = hmul2_bf16(pack_bf16(gelu_tanh(bf_lo(g.w)), gelu_tanh(bf_hi(g.w))), u.w);
    stg128(gptr + i * 8, o);
  }
}

__device__ __forceinline__ void k1_unit_ab(const K1Ctx& c, int warp, int lane, int mt, int j) {
  const uint32_t stg = c.sb + K1_STG_OFF + warp * 2048;
  const int wq = warp & 3;
  const int st_row = (lane & 7) + 8 * ((lane >> 3) & 1);
  const int st_chunk = lane >> 4;
  float acc[2][56];
  int slot = 0; uint32_t ph = 0;
#pragma unroll 1
  for (int kb = 0; kb < 7; kb++) {
    const int pslot = (slot == 0) ? K1_NS - 1 : slot - 1;
    mbar_wait(c.bar_full + 8 * slot, ph, 3);
    if (kb == 6) named_arrive(2, 256);
    if (kb == 0 && (threadIdx.x & 127) == 0) DBG(0, 4);
    if ((threadIdx.x & 127) == 0) DBGC(1, 46 + kb);
    wg_fence();
    const uint32_t da = c.dA + kb * 1024;
    const uint32_t db = c.dBk + slot * 1024;
#pragma unroll
    for (int k = 0; k < 4; k++) {
      wgmma_n112(acc[0], da + k * 2, db + k * 2, (kb | k) != 0);
      wgmma_n112(acc[1], da + 512 + k * 2, db + k * 2, (kb | k) != 0);
    }
    wg_commit();
    if (kb > 0) { wg_wait<1>(); k1_release(c, pslot); }
    if (++slot == K1_NS) { slot = 0; ph ^= 1; }
  }
  wg_wait<0>();
  k1_release(c, 6 % K1_NS);
  if ((threadIdx.x & 127) == 0) DBG(0, 5);
  const uint32_t sgn = (j < 4) ? 0u : 0x80008000u;
  __nv_bfloat16* outp = g_ab + (size_t)((j < 4 ? 0 : 2048) + mt * 128 + wq * 16 + (lane >> 3)) * 448 + (j & 3) * 112 + (lane & 7) * 8;
  const uint32_t sa = stg + st_row * 128;
  const uint32_t la = stg + (lane >> 3) * 128;
#pragma unroll
  for (int h = 0; h < 2; h++) {
#pragma unroll
    for (int rnd = 0; rnd < 2; rnd++) {
#pragma unroll
      for (int g = 0; g < (rnd ? 6 : 8); g += 2) {
        const float* a = &acc[h][4 * (g + 8 * rnd)];
        stmatrix_x4(sa + (((g + st_chunk) ^ (st_row & 7)) * 16),
                    pack_bf16(a[0], a[1]) ^ sgn, pack_bf16(a[2], a[3]) ^ sgn, pack_bf16(a[4], a[5]) ^ sgn, pack_bf16(a[6], a[7]) ^ sgn);
      }
      __syncwarp();
      if (rnd == 0 || (lane & 7) < 6) {
#pragma unroll
        for (int t = 0; t < 4; t++) {
          const int r7 = (t * 4 + (lane >> 3)) & 7;
          stg128(outp + (h * 64 + t * 4) * 448 + rnd * 64, lds128(la + t * 512 + (((lane & 7) ^ r7) * 16)));
        }
      }
      __syncwarp();
    }
  }
}

__device__ __forceinline__ void k1_unit_gu(const K1Ctx& c, int warp, int lane, int mt, int unit, int fb, int hsel) {
  const uint32_t stg = c.sb + K1_STG_OFF + warp * 2048;
  const int wq = warp & 3;
  const int full = (unit < 4);
  float acc[2][64];
  const uint32_t dA0 = c.dA + (full ? 0 : hsel * 512);
  int slot = (unit * 7) % K1_NS; uint32_t ph = ((unit * 7) / K1_NS) & 1;
  named_bar(2 + ((unit - 1) & 1), 256);
  if (full) {
#pragma unroll 1
    for (int kb = 0; kb < 7; kb++) {
      const int pslot = (slot == 0) ? K1_NS - 1 : slot - 1;
      mbar_wait(c.bar_full + 8 * slot, ph, 4);
      if (kb == 6) named_arrive(2 + (unit & 1), 256);
      if (kb == 0 && (threadIdx.x & 127) == 0) DBG(0, 4 + 3 * unit);
      wg_fence();
      const uint32_t da = dA0 + kb * 1024;
      const uint32_t db = c.dBn + slot * 1024;
#pragma unroll
      for (int k = 0; k < 4; k++) {
        wgmma_n128_tb(acc[0], da + k * 2, db + k * 128, (kb | k) != 0);
        wgmma_n128_tb(acc[1], da + 512 + k * 2, db + k * 128, (kb | k) != 0);
      }
      wg_commit();
      if (kb > 0) { wg_wait<1>(); k1_release(c, pslot); }
      if (++slot == K1_NS) { slot = 0; ph ^= 1; }
    }
  } else {
#pragma unroll 1
    for (int kb = 0; kb < 7; kb++) {
      const int pslot = (slot == 0) ? K1_NS - 1 : slot - 1;
      mbar_wait(c.bar_full + 8 * slot, ph, 5);
      if (kb == 0 && (threadIdx.x & 127) == 0) DBG(0, 4 + 3 * unit);
      wg_fence();
      const uint32_t da = dA0 + kb * 1024;
      const uint32_t db = c.dBn + slot * 1024;
#pragma unroll
      for (int k = 0; k < 4; k++) wgmma_n128_tb(acc[0], da + k * 2, db + k * 128, (kb | k) != 0);
      wg_commit();
      if (kb > 0) { wg_wait<1>(); k1_release(c, pslot); }
      if (++slot == K1_NS) { slot = 0; ph ^= 1; }
    }
  }
  wg_wait<0>();
  k1_release(c, (slot == 0) ? K1_NS - 1 : slot - 1);
  if ((threadIdx.x & 127) == 0) DBG(0, 5 + 3 * unit);
  const int st_row = (lane & 7) + 8 * ((lane >> 3) & 1);
  const int st_chunk = lane >> 4;
  const uint32_t sa = stg + st_row * 64;
  const int sw = (st_row >> 1) & 3;
  __nv_bfloat16* outp = g_h + (size_t)(mt * 128 + (full ? 0 : hsel * 64) + wq * 16 + (lane >> 1)) * 1792 + fb * 64 + (lane & 1) * 16;
#pragma unroll
  for (int h = 0; h < 2; h++) {
    if (h == 1 && !full) break;
#pragma unroll
    for (int ch = 0; ch < 2; ch++) {
#pragma unroll
      for (int g = 0; g < 4; g += 2) {
        const float* a = &acc[h][4 * (4 * ch + g)];
        const float* u = a + 32;
        const uint32_t ad = sa + (((g + st_chunk) ^ sw) * 16);
        stmatrix_x4(ad, pack_bf16(a[0], a[1]), pack_bf16(a[2], a[3]), pack_bf16(a[4], a[5]), pack_bf16(a[6], a[7]));
        stmatrix_x4(ad + 1024, pack_bf16(u[0], u[1]), pack_bf16(u[2], u[3]), pack_bf16(u[4], u[5]), pack_bf16(u[6], u[7]));
      }
      __syncwarp();
      geglu_tile(stg, outp + (size_t)h * 64 * 1792 + ch * 32, lane);
      __syncwarp();
    }
  }
}

struct PfPtrs { const uint8_t* wr; const uint8_t* wi; const uint8_t* wg; const uint8_t* wu; const uint8_t* wd; const uint8_t* cr; const uint8_t* ci; };

__global__ void __cluster_dims__(2, 1, 1) __launch_bounds__(384, 1)
k1_kernel(const __grid_constant__ CUtensorMap tm_wr, const __grid_constant__ CUtensorMap tm_wi,
          const __grid_constant__ CUtensorMap tm_wg, const __grid_constant__ CUtensorMap tm_wu,
          const __nv_bfloat16* __restrict__ x, const PfPtrs pf) {
  extern __shared__ uint8_t smem_raw[];
  const uint32_t sb = (s2u(smem_raw) + 1023) & ~1023u;
  const int tid = threadIdx.x, warp = tid >> 5, lane = tid & 31;
  uint32_t rank;
  asm volatile("mov.u32 %0, %%cluster_ctarank;" : "=r"(rank));
  const int cid = blockIdx.x >> 1;
  const int p = cid >> 3, j = cid & 7;
  const int mt = 2 * p + (int)rank;
  const uint32_t bar_full = sb + K1_BAR_OFF;
  const uint32_t bar_empty = bar_full + 8 * K1_NS;
  const int fb_base = 7 * (j >> 1);
  const int fb0 = fb_base + ((j & 1) ? 4 : 0);
  const int fbh = fb_base + 3;
  const CUtensorMap* tw = (j < 4) ? &tm_wr : &tm_wi;
  const CUtensorMap* tgu = rank ? &tm_wu : &tm_wg;

  if (tid == 0) DBG(0, 0);
  if (tid == 256) {
    for (int i = 0; i < K1_NS; i++) { mbar_init(bar_full + 8 * i, 1); mbar_init(bar_empty + 8 * i, 8); }
    asm volatile("fence.mbarrier_init.release.cluster;" ::: "memory");
    prefetch_tmap(tw);
    prefetch_tmap(tgu);
    if (blockIdx.x < 64) g_flags[blockIdx.x] = 0;
  }
  __syncwarp();
  cluster_arrive_relaxed();
  pdl_launch();

  if (warp >= 8) {
    reg_dec<40>();
    cluster_wait();
    if (tid == 256) {
      int slot = 0; uint32_t ph = 0;
      int kb = 0, unit = 0;
#pragma unroll 1
      for (int s = 0; s < 35; s++) {
        if (s >= K1_NS) mbar_wait(bar_empty + 8 * slot, ph ^ 1, 2);
        DBG(0, 20 + s);
        const uint32_t dst = sb + K1_B_OFF + slot * 16384;
        if (unit == 0) {
          mbar_expect(bar_full + 8 * slot, 14336);
          tma2d_mc(dst + rank * 7168, tw, kb * 64, (j & 3) * 112 + rank * 56, bar_full + 8 * slot, 3);
        } else {
          const int fb = (unit == 4) ? fbh : (fb0 + unit - 1);
          mbar_expect(bar_full + 8 * slot, 16384);
          tma2d_mc(dst + rank * 8192, tgu, fb * 64, kb * 64, bar_full + 8 * slot, 3);
        }
        if (++kb == 7) { kb = 0; unit++; }
        if (++slot == K1_NS) { slot = 0; ph ^= 1; }
      }
    } else if (tid == 288) {
      const int b = blockIdx.x;
      l2_prefetch(pf.wg + b * 12544, 12544);
      l2_prefetch(pf.wu + b * 12544, 12544);
    }
  } else {
    reg_inc<232>();
    const int wg = warp >> 2;
    {
      const int c = lane & 7;
      const int r0 = warp * 16 + (lane >> 3);
      const uint4* src = reinterpret_cast<const uint4*>(x + (size_t)(mt * 128 + r0) * 448) + c;
      uint4 nx[7];
#pragma unroll
      for (int b = 0; b < 7; b++)
        asm volatile("ld.global.nc.v4.u32 {%0,%1,%2,%3}, [%4];" : "=r"(nx[b].x), "=r"(nx[b].y), "=r"(nx[b].z), "=r"(nx[b].w) : "l"(src + b * 8) : "memory");
#pragma unroll
      for (int pass = 1; pass < 4; pass++) asm volatile("prefetch.global.L2 [%0];" ::"l"(src + pass * 4 * 56 + c * 7 - c) : "memory");
#pragma unroll 1
      for (int pass = 0; pass < 4; pass++) {
        uint4 v[7];
#pragma unroll
        for (int b = 0; b < 7; b++) v[b] = nx[b];
        if (pass < 3) {
          const uint4* s2 = src + (pass + 1) * 4 * 56;
#pragma unroll
          for (int b = 0; b < 7; b++)
            asm volatile("ld.global.nc.v4.u32 {%0,%1,%2,%3}, [%4];" : "=r"(nx[b].x), "=r"(nx[b].y), "=r"(nx[b].z), "=r"(nx[b].w) : "l"(s2 + b * 8) : "memory");
        }
        float s0 = 0.f, s1 = 0.f, s2v = 0.f, s3 = 0.f;
#pragma unroll
        for (int b = 0; b < 7; b++) {
          s0 += bf_lo(v[b].x) + bf_hi(v[b].x); s1 += bf_lo(v[b].y) + bf_hi(v[b].y);
          s2v += bf_lo(v[b].z) + bf_hi(v[b].z); s3 += bf_lo(v[b].w) + bf_hi(v[b].w);
        }
        float m = (s0 + s1) + (s2v + s3);
        m += __shfl_xor_sync(0xffffffffu, m, 1);
        m += __shfl_xor_sync(0xffffffffu, m, 2);
        m += __shfl_xor_sync(0xffffffffu, m, 4);
        m *= (1.0f / 448.0f);
        float q0 = 0.f, q1 = 0.f, q2 = 0.f, q3 = 0.f;
#pragma unroll
        for (int b = 0; b < 7; b++) {
          float d;
          d = bf_lo(v[b].x) - m; q0 = fmaf(d, d, q0); d = bf_hi(v[b].x) - m; q1 = fmaf(d, d, q1);
          d = bf_lo(v[b].y) - m; q2 = fmaf(d, d, q2); d = bf_hi(v[b].y) - m; q3 = fmaf(d, d, q3);
          d = bf_lo(v[b].z) - m; q0 = fmaf(d, d, q0); d = bf_hi(v[b].z) - m; q1 = fmaf(d, d, q1);
          d = bf_lo(v[b].w) - m; q2 = fmaf(d, d, q2); d = bf_hi(v[b].w) - m; q3 = fmaf(d, d, q3);
        }
        float q = (q0 + q1) + (q2 + q3);
        q += __shfl_xor_sync(0xffffffffu, q, 1);
        q += __shfl_xor_sync(0xffffffffu, q, 2);
        q += __shfl_xor_sync(0xffffffffu, q, 4);
        const float var_b = rbf(q * (1.0f / 448.0f));
        const float den = rbf(sqrtf(rbf(var_b + 1e-5f)));
        const float ri = 1.0f / den;
        const float rih = rbf(ri);
        const uint32_t rhi2 = pack_bf16(rih, rih), rlo2 = pack_bf16(ri - rih, ri - rih);
        const uint32_t m2 = pack_bf16(m, m);
        const int r = r0 + pass * 4;
        const uint32_t a0 = sb + r * 128 + ((c ^ (r & 7)) * 16);
#pragma unroll
        for (int b = 0; b < 7; b++) {
          uint32_t w4[4] = {v[b].x, v[b].y, v[b].z, v[b].w};
#pragma unroll
          for (int qq = 0; qq < 4; qq++) {
            const uint32_t dw = hsub2_bf16(w4[qq], m2);
            w4[qq] = hfma2_bf16(dw, rhi2, hmul2_bf16(dw, rlo2));
          }
          sts128(a0 + b * 16384, make_uint4(w4[0], w4[1], w4[2], w4[3]));
        }
      }
    }
    if (lane == 0) DBG(0, 59 + (warp & 3));
    asm volatile("fence.proxy.async.shared::cta;" ::: "memory");
    named_bar(1, 256);
    cluster_wait();
    if (tid == 0) DBG(0, 3);

    K1Ctx c;
    c.sb = sb; c.bar_full = bar_full; c.lane0 = (lane == 0);
    asm volatile("mapa.shared::cluster.u32 %0, %1, %2;" : "=r"(c.rel0) : "r"(bar_empty), "r"(0));
    asm volatile("mapa.shared::cluster.u32 %0, %1, %2;" : "=r"(c.rel1) : "r"(bar_empty), "r"(1));
    c.dA = make_desc(sb, 16, 1024);
    c.dBk = make_desc(sb + K1_B_OFF, 16, 1024);
    c.dBn = make_desc(sb + K1_B_OFF, 8192, 1024);
    if (wg == 0) {
      k1_unit_ab(c, warp, lane, mt, j);
      if (tid == 0) DBG(0, 6);
    }
#pragma unroll 1
    for (int unit = 2 - wg; unit < 5; unit += 2) {
      k1_unit_gu(c, warp, lane, mt, unit, (unit == 4) ? fbh : fb0 + unit - 1, j & 1);
      if ((tid & 127) == 0) DBG(0, 6 + 3 * unit);
    }
  }
  __syncwarp();
  cluster_arrive_relaxed();
  cluster_wait();
}

constexpr int K2_NS = 4;
constexpr int K2_STAGE = 16384 + 32768;
constexpr int K2_BAR_OFF = K2_NS * K2_STAGE;
constexpr int K2_SMEM = K2_BAR_OFF + 256 + 1024;
constexpr int K2_PITCH = 464;

__device__ __forceinline__ void spin_flag(const unsigned int* flag, unsigned int target) {
  int it = 0;
  while (true) {
    unsigned int v;
    asm volatile("ld.acquire.gpu.global.u32 %0, [%1];" : "=r"(v) : "l"(flag) : "memory");
    if (v >= target) break;
    if (++it > SPIN_LIMIT) { TIMEOUT(20); break; }
  }
}

__global__ void __cluster_dims__(2, 1, 1) __launch_bounds__(384, 1)
k2_kernel(const __grid_constant__ CUtensorMap tm_cr, const __grid_constant__ CUtensorMap tm_ci, const __grid_constant__ CUtensorMap tm_h,
          const __grid_constant__ CUtensorMap tm_ab, const __grid_constant__ CUtensorMap tm_wd,
          const __nv_bfloat16* __restrict__ x, __nv_bfloat16* __restrict__ out) {
  extern __shared__ uint8_t smem_raw[];
  const uint32_t sb = (s2u(smem_raw) + 1023) & ~1023u;
  const int tid = threadIdx.x, warp = tid >> 5, lane = tid & 31;
  uint32_t rank;
  asm volatile("mov.u32 %0, %%cluster_ctarank;" : "=r"(rank));
  const int cid = blockIdx.x >> 1;
  const int q = cid & 3, n = (cid >> 2) & 1, p = cid >> 3;
  const int mt = 2 * p + (int)rank;
  const int tile = mt * 2 + n;
  const uint32_t bar_full = sb + K2_BAR_OFF;
  const uint32_t bar_empty = bar_full + 8 * K2_NS;
  const int g0 = (q == 0) ? 0 : (q == 1 ? 22 : (q == 2 ? 43 : 64));
  const int nkb = (q == 0) ? 22 : (q == 3 ? 28 : 21);

  if (tid == 0) DBG(1, 0);
  if (tid == 256) {
    for (int i = 0; i < K2_NS; i++) { mbar_init(bar_full + 8 * i, 1); mbar_init(bar_empty + 8 * i, 16); }
    asm volatile("fence.mbarrier_init.release.cluster;" ::: "memory");
    if (q == 3) { prefetch_tmap(&tm_h); prefetch_tmap(&tm_wd); }
    else { prefetch_tmap(&tm_cr); prefetch_tmap(&tm_ci); prefetch_tmap(&tm_ab); }
  }
  __syncwarp();
  cluster_arrive_relaxed();
  cluster_wait();

  if (warp >= 8) {
    reg_dec<40>();
    if (tid == 256) {
      const CUtensorMap* tb = (q < 3) ? &tm_ab : &tm_wd;
      const int kb0 = (q < 3) ? g0 : 0;
      int slot = 0; uint32_t ph = 0;
#pragma unroll 1
      for (int it = 0; it < nkb + K2_NS; it++) {
        const int s = (it < K2_NS) ? it : it - K2_NS;
        const bool pre = (it < K2_NS), post = (!pre && s < K2_NS);
        if (it == K2_NS) { pdl_wait(); DBG(1, 31); slot = 0; }
        if (!pre && !post) mbar_wait(bar_empty + 8 * slot, ph, 10);
        const uint32_t dst = sb + slot * K2_STAGE;
        const uint32_t fb = bar_full + 8 * slot;
        if (!post) mbar_expect(fb, K2_STAGE);
        const bool doA = pre ? (q < 3) : (post ? (q == 3) : true);
        const bool doB = pre ? (q == 3) : (post ? (q < 3) : true);
        if (doA) {
          const int g = g0 + s;
          const CUtensorMap* ta = (g < 32) ? &tm_cr : (g < 64 ? &tm_ci : &tm_h);
          tma2d(dst, ta, (g & 31) * 64 + ((g >= 96) ? 2048 : 0), mt * 128, fb);
        }
        if (doB) {
          tma3d_mc(dst + 16384 + (2 * rank) * 8192, tb, (2 * rank) * 64, n, (kb0 + s) * 64, fb, 3);
          tma3d_mc(dst + 16384 + (2 * rank + 1) * 8192, tb, (2 * rank + 1) * 64, n, (kb0 + s) * 64, fb, 3);
        }
        if (++slot == K2_NS) { slot = 0; if (!pre && !post) ph ^= 1; }
      }
    }
  } else {
    reg_inc<232>();
    const int wg = warp >> 2;
    float acc[112];
    uint32_t rel0, rel1;
    asm volatile("mapa.shared::cluster.u32 %0, %1, %2;" : "=r"(rel0) : "r"(bar_empty), "r"(0));
    asm volatile("mapa.shared::cluster.u32 %0, %1, %2;" : "=r"(rel1) : "r"(bar_empty), "r"(1));
    const uint32_t dA0 = make_desc(sb + wg * 8192, 16, 1024);
    const uint32_t dB0 = make_desc(sb + 16384, 8192, 1024);
    int slot = 0; uint32_t ph = 0;
#pragma unroll 1
    for (int s = 0; s < nkb; s++) {
      mbar_wait(bar_full + 8 * slot, ph, 11);
      if (tid == 0) DBG(1, 1 + s);
      if (tid == 0 && (s == 5 || s == 15)) DBGC(1, 53 + (s == 15));
      if (tid == 0 && (s == 23 || s == 27)) DBGC(1, 55 + (s == 27));
      wg_fence();
      const uint32_t da = dA0 + slot * (K2_STAGE / 16);
      const uint32_t db = dB0 + slot * (K2_STAGE / 16);
#pragma unroll
      for (int k = 0; k < 4; k++) wgmma_n224_tb(acc, da + k * 2, db + k * 128, (s | k) != 0);
      wg_commit();
      if (s > 0) {
        wg_wait<1>();
        const int ps = (slot == 0) ? K2_NS - 1 : slot - 1;
        if (lane == 0) {
          asm volatile("mbarrier.arrive.shared::cluster.b64 _, [%0];" ::"r"(rel0 + 8 * ps) : "memory");
          asm volatile("mbarrier.arrive.shared::cluster.b64 _, [%0];" ::"r"(rel1 + 8 * ps) : "memory");
        }
      }
      if (++slot == K2_NS) { slot = 0; ph ^= 1; }
    }
    wg_wait<0>();
    pdl_wait();
    if (tid == 0) DBG(1, 29);
    if (q < 3) {
      float4* part = g_part + (size_t)tile * (3 * 28 * 256) + tid;
#pragma unroll
      for (int g = 0; g < 28; g++) part[(q * 28 + g) * 256] = make_float4(acc[4 * g], acc[4 * g + 1], acc[4 * g + 2], acc[4 * g + 3]);
      __threadfence();
      named_bar(1, 256);
      if (tid == 0) { atomicAdd(&g_flags[tile], 1u); spin_flag(&g_flags[tile], 3u); }
      named_bar(1, 256);
      if (tid == 0) DBG(1, 30);
      const int G0 = q * 10, NG = (q == 2) ? 8 : 10;
      uint32_t* sp = reinterpret_cast<uint32_t*>(g_s + (size_t)(mt * 128 + warp * 16 + (lane >> 2)) * 448 + n * 224 + (lane & 3) * 2) + G0 * 4;
      const float4* pp = part + G0 * 256;
#pragma unroll 2
      for (int g = 0; g < NG; g++) {
        const float4 a = __ldcg(pp + g * 256), b = __ldcg(pp + (28 + g) * 256), cc = __ldcg(pp + (56 + g) * 256);
        sp[g * 4] = pack_bf16(a.x + b.x + cc.x, a.y + b.y + cc.y);
        sp[g * 4 + 8 * 224] = pack_bf16(a.z + b.z + cc.z, a.w + b.w + cc.w);
      }
      __threadfence();
      named_bar(1, 256);
      if (tid == 0) atomicAdd(&g_flags[32 + tile], 1u);
    } else {
      named_bar(1, 256);
      const uint32_t stg = sb + warp * 16 * K2_PITCH;
      const int st_row = (lane & 7) + 8 * ((lane >> 3) & 1);
      const uint32_t sa = stg + st_row * K2_PITCH + (lane >> 4) * 16;
#pragma unroll
      for (int g = 0; g < 28; g += 2) {
        const float* a = &acc[4 * g];
        stmatrix_x4(sa + g * 16, pack_bf16(a[0], a[1]), pack_bf16(a[2], a[3]), pack_bf16(a[4], a[5]), pack_bf16(a[6], a[7]));
      }
      if (lane == 0) spin_flag(&g_flags[32 + tile], 3u);
      __syncwarp();
      if (tid == 0) DBG(1, 30);
      const int lc = (lane < 28) ? lane : 27;
      const size_t gbase = (size_t)(mt * 128 + warp * 16) * 448 + n * 224 + lc * 8;
      const uint32_t lp = stg + lc * 16;
#pragma unroll 1
      for (int t0 = 0; t0 < 16; t0 += 4) {
        uint4 xv[4], sv[4];
#pragma unroll
        for (int t = 0; t < 4; t++) { xv[t] = ldg128_cg(x + gbase + (t0 + t) * 448); sv[t] = ldg128_cg(g_s + gbase + (t0 + t) * 448); }
#pragma unroll 1
        for (int t = 0; t < 4; t++) {
          const uint4 fv = lds128(lp + (t0 + t) * K2_PITCH);
          uint4 xx, ss;
          if (t == 0) { xx = xv[0]; ss = sv[0]; } else if (t == 1) { xx = xv[1]; ss = sv[1]; } else if (t == 2) { xx = xv[2]; ss = sv[2]; } else { xx = xv[3]; ss = sv[3]; }
          uint4 o;
          o.x = hadd2_bf16(xx.x, hmul2_bf16(ss.x, pack_bf16(silu_f(bf_lo(fv.x)), silu_f(bf_hi(fv.x)))));
          o.y = hadd2_bf16(xx.y, hmul2_bf16(ss.y, pack_bf16(silu_f(bf_lo(fv.y)), silu_f(bf_hi(fv.y)))));
          o.z = hadd2_bf16(xx.z, hmul2_bf16(ss.z, pack_bf16(silu_f(bf_lo(fv.z)), silu_f(bf_hi(fv.z)))));
          o.w = hadd2_bf16(xx.w, hmul2_bf16(ss.w, pack_bf16(silu_f(bf_lo(fv.w)), silu_f(bf_hi(fv.w)))));
          if (lane < 28) stg128(out + gbase + (t0 + t) * 448, o);
        }
      }
    }
    if (tid == 0) DBG(1, 63);
  }
  __syncwarp();
  cluster_arrive_relaxed();
  cluster_wait();
}

typedef CUresult (*EncFn)(CUtensorMap*, CUtensorMapDataType, cuuint32_t, void*, const cuuint64_t*, const cuuint64_t*, const cuuint32_t*,
                          const cuuint32_t*, CUtensorMapInterleave, CUtensorMapSwizzle, CUtensorMapL2promotion, CUtensorMapFloatOOBfill);

void make2d(EncFn enc, CUtensorMap* tm, const void* ptr, uint64_t cols, uint64_t rows, uint32_t bc, uint32_t br) {
  cuuint64_t gd[2] = {cols, rows};
  cuuint64_t gs[1] = {cols * 2};
  cuuint32_t bd[2] = {bc, br};
  cuuint32_t es[2] = {1, 1};
  enc(tm, CU_TENSOR_MAP_DATA_TYPE_BFLOAT16, 2, const_cast<void*>(ptr), gd, gs, bd, es, CU_TENSOR_MAP_INTERLEAVE_NONE,
      CU_TENSOR_MAP_SWIZZLE_128B, CU_TENSOR_MAP_L2_PROMOTION_L2_128B, CU_TENSOR_MAP_FLOAT_OOB_FILL_NONE);
}
void make3d_half(EncFn enc, CUtensorMap* tm, const void* ptr, uint64_t rows) {
  cuuint64_t gd[3] = {224, 2, rows};
  cuuint64_t gs[2] = {448, 896};
  cuuint32_t bd[3] = {64, 1, 64};
  cuuint32_t es[3] = {1, 1, 1};
  enc(tm, CU_TENSOR_MAP_DATA_TYPE_BFLOAT16, 3, const_cast<void*>(ptr), gd, gs, bd, es, CU_TENSOR_MAP_INTERLEAVE_NONE,
      CU_TENSOR_MAP_SWIZZLE_128B, CU_TENSOR_MAP_L2_PROMOTION_L2_128B, CU_TENSOR_MAP_FLOAT_OOB_FILL_NONE);
}

struct Maps { CUtensorMap wr, wi, wg, wu, cr, ci, h, ab, wd; };

}

extern "C" void kernel_launch(void* const* d_in, const int* in_sizes, int n_in, void* d_out, int out_size) {
  (void)in_sizes; (void)n_in; (void)out_size;
  static Maps maps;
  static const void* cached[9] = {nullptr};
  static bool attr_done = false;
  bool same = true;
  for (int i = 0; i < 9; i++) same = same && (cached[i] == d_in[i]);
  if (!same) {
    void* fn = nullptr;
    cudaDriverEntryPointQueryResult qr;
    cudaGetDriverEntryPoint("cuTensorMapEncodeTiled", &fn, cudaEnableDefault, &qr);
    EncFn enc = (EncFn)fn;
    void *p_ab = nullptr, *p_h = nullptr;
    cudaGetSymbolAddress(&p_ab, g_ab);
    cudaGetSymbolAddress(&p_h, g_h);
    make2d(enc, &maps.cr, d_in[1], 2048, 2048, 64, 128);
    make2d(enc, &maps.ci, d_in[2], 2048, 2048, 64, 128);
    make2d(enc, &maps.wr, d_in[3], 448, 448, 64, 56);
    make2d(enc, &maps.wi, d_in[4], 448, 448, 64, 56);
    make2d(enc, &maps.wg, d_in[6], 1792, 448, 64, 64);
    make2d(enc, &maps.wu, d_in[7], 1792, 448, 64, 64);
    make3d_half(enc, &maps.wd, d_in[8], 1792);
    make2d(enc, &maps.h, p_h, 1792, 2048, 64, 128);
    make3d_half(enc, &maps.ab, p_ab, 4096);
    for (int i = 0; i < 9; i++) cached[i] = d_in[i];
  }
  if (!attr_done) {
    cudaFuncSetAttribute(k1_kernel, cudaFuncAttributeMaxDynamicSharedMemorySize, K1_SMEM);
    cudaFuncSetAttribute(k2_kernel, cudaFuncAttributeMaxDynamicSharedMemorySize, K2_SMEM);
    attr_done = true;
  }
  PfPtrs pf;
  pf.wr = (const uint8_t*)d_in[3]; pf.wi = (const uint8_t*)d_in[4]; pf.wg = (const uint8_t*)d_in[6]; pf.wu = (const uint8_t*)d_in[7];
  pf.wd = (const uint8_t*)d_in[8]; pf.cr = (const uint8_t*)d_in[1]; pf.ci = (const uint8_t*)d_in[2];
  k1_kernel<<<128, 384, K1_SMEM>>>(maps.wr, maps.wi, maps.wg, maps.wu, (const __nv_bfloat16*)d_in[0], pf);

  cudaLaunchConfig_t cfg = {};
  cfg.gridDim = dim3(128); cfg.blockDim = dim3(384); cfg.dynamicSmemBytes = K2_SMEM; cfg.stream = cudaStreamPerThread;
  cudaLaunchAttribute at[1];
  at[0].id = cudaLaunchAttributeProgrammaticStreamSerialization;
  at[0].val.programmaticStreamSerializationAllowed = 1;
  cfg.attrs = at; cfg.numAttrs = 1;
  cudaLaunchKernelEx(&cfg, k2_kernel, maps.cr, maps.ci, maps.h, maps.ab, maps.wd, (const __nv_bfloat16*)d_in[0], (__nv_bfloat16*)d_out);
}
```

```cpp
#include <cuda_runtime.h>
#include <cuda_bf16.h>
#include <cuda.h>
#include <stdint.h>

namespace {

__device__ __align__(1024) __nv_bfloat16 g_ab[4096 * 448];
__device__ __align__(1024) __nv_bfloat16 g_h[2048 * 1792];
__device__ float4 g_part[32 * 3 * 28 * 256];
__device__ __align__(1024) __nv_bfloat16 g_s[2048 * 448];
__device__ unsigned int g_flags[64];

#define DBG(k, i) do {} while (0)
#define DBGC(k, i) do {} while (0)

#define TIMEOUT(code) __trap()
#define SPIN_LIMIT (1 << 22)
__device__ __forceinline__ uint32_t s2u(const void* p) { return (uint32_t)__cvta_generic_to_shared(p); }
__device__ __forceinline__ void mbar_init(uint32_t b, int c) { asm volatile("mbarrier.init.shared::cta.b64 [%0], %1;" ::"r"(b), "r"(c)); }
__device__ __forceinline__ void mbar_expect(uint32_t b, uint32_t bytes) {
  asm volatile("mbarrier.arrive.expect_tx.shared::cta.b64 _, [%0], %1;" ::"r"(b), "r"(bytes) : "memory");
}
__device__ __forceinline__ void mbar_wait(uint32_t b, uint32_t ph, int code = 1) {
  uint32_t done = 0;
  int it = 0;
  while (true) {
    asm volatile("{.reg .pred p; mbarrier.try_wait.parity.shared::cta.b64 p, [%1], %2; selp.u32 %0,1,0,p;}" : "=r"(done) : "r"(b), "r"(ph) : "memory");
    if (done) break;
    if (++it > SPIN_LIMIT) { TIMEOUT(code); break; }
  }
}
__device__ __forceinline__ void mbar_arrive_cluster(uint32_t b, uint32_t cta) {
  uint32_t r;
  asm volatile("mapa.shared::cluster.u32 %0, %1, %2;" : "=r"(r) : "r"(b), "r"(cta));
  asm volatile("mbarrier.arrive.shared::cluster.b64 _, [%0];" ::"r"(r) : "memory");
}
__device__ __forceinline__ void tma2d(uint32_t dst, const CUtensorMap* m, int c0, int c1, uint32_t bar) {
  asm volatile("cp.async.bulk.tensor.2d.shared::cluster.global.mbarrier::complete_tx::bytes [%0], [%1, {%3,%4}], [%2];" ::"r"(dst), "l"(m), "r"(bar), "r"(c0), "r"(c1) : "memory");
}
__device__ __forceinline__ void tma2d_mc(uint32_t dst, const CUtensorMap* m, int c0, int c1, uint32_t bar, uint16_t mask) {
  asm volatile("cp.async.bulk.tensor.2d.shared::cluster.global.mbarrier::complete_tx::bytes.multicast::cluster [%0], [%1, {%3,%4}], [%2], %5;" ::"r"(dst), "l"(m), "r"(bar), "r"(c0), "r"(c1), "h"(mask) : "memory");
}
__device__ __forceinline__ void tma3d_mc(uint32_t dst, const CUtensorMap* m, int c0, int c1, int c2, uint32_t bar, uint16_t mask) {
  asm volatile("cp.async.bulk.tensor.3d.shared::cluster.global.mbarrier::complete_tx::bytes.multicast::cluster [%0], [%1, {%3,%4,%5}], [%2], %6;" ::"r"(dst), "l"(m), "r"(bar), "r"(c0), "r"(c1), "r"(c2), "h"(mask) : "memory");
}
__device__ __forceinline__ void prefetch_tmap(const CUtensorMap* m) { asm volatile("prefetch.tensormap [%0];" ::"l"(m) : "memory"); }
__device__ __forceinline__ void l2_prefetch(const void* p, uint32_t bytes) {
  asm volatile("cp.async.bulk.prefetch.L2.global [%0], %1;" ::"l"(p), "r"(bytes) : "memory");
}
__device__ __forceinline__ void cluster_arrive_relaxed() { asm volatile("barrier.cluster.arrive.relaxed.aligned;" ::: "memory"); }
__device__ __forceinline__ void cluster_wait() { asm volatile("barrier.cluster.wait.aligned;" ::: "memory"); }
__device__ __forceinline__ void wg_fence() { __syncwarp(); asm volatile("wgmma.fence.sync.aligned;" ::: "memory"); }
__device__ __forceinline__ void wg_commit() { asm volatile("wgmma.commit_group.sync.aligned;" ::: "memory"); }
template <int N> __device__ __forceinline__ void wg_wait() { __syncwarp(); asm volatile("wgmma.wait_group.sync.aligned %0;" ::"n"(N) : "memory"); }
__device__ __forceinline__ void named_bar(int id, int n) { asm volatile("bar.sync %0, %1;" ::"r"(id), "r"(n) : "memory"); }
__device__ __forceinline__ void named_arrive(int id, int n) { asm volatile("bar.arrive %0, %1;" ::"r"(id), "r"(n) : "memory"); }
template <int N> __device__ __forceinline__ void reg_inc() { asm volatile("setmaxnreg.inc.sync.aligned.u32 %0;" ::"n"(N)); }
template <int N> __device__ __forceinline__ void reg_dec() { asm volatile("setmaxnreg.dec.sync.aligned.u32 %0;" ::"n"(N)); }
__device__ __forceinline__ void pdl_wait() { asm volatile("griddepcontrol.wait;" ::: "memory"); }
__device__ __forceinline__ void pdl_launch() { asm volatile("griddepcontrol.launch_dependents;" ::: "memory"); }

__device__ __forceinline__ uint32_t make_desc(uint32_t addr, uint32_t lbo, uint32_t  ) {
  return ((addr & 0x3FFFF) >> 4) | ((lbo >> 4) << 16);
}
__device__ __forceinline__ void stmatrix_x4(uint32_t addr, uint32_t r0, uint32_t r1, uint32_t r2, uint32_t r3) {
  asm volatile("stmatrix.sync.aligned.m8n8.x4.shared.b16 [%0], {%1,%2,%3,%4};" ::"r"(addr), "r"(r0), "r"(r1), "r"(r2), "r"(r3) : "memory");
}
__device__ __forceinline__ uint4 lds128(uint32_t a) {
  uint4 v;
  asm volatile("ld.shared.v4.u32 {%0,%1,%2,%3}, [%4];" : "=r"(v.x), "=r"(v.y), "=r"(v.z), "=r"(v.w) : "r"(a) : "memory");
  return v;
}
__device__ __forceinline__ void sts128(uint32_t a, uint4 v) {
  asm volatile("st.shared.v4.u32 [%0], {%1,%2,%3,%4};" ::"r"(a), "r"(v.x), "r"(v.y), "r"(v.z), "r"(v.w) : "memory");
}
__device__ __forceinline__ void stg128(void* p, uint4 v) {
  asm volatile("st.global.v4.u32 [%0], {%1,%2,%3,%4};" ::"l"(p), "r"(v.x), "r"(v.y), "r"(v.z), "r"(v.w) : "memory");
}
__device__ __forceinline__ void cp_async16(uint32_t dst, const void* src) {
  asm volatile("cp.async.cg.shared.global [%0], [%1], 16;" ::"r"(dst), "l"(src) : "memory");
}
__device__ __forceinline__ void cp_async_wait_all() { asm volatile("cp.async.wait_all;" ::: "memory"); }
__device__ __forceinline__ uint32_t pack_bf16(float lo, float hi) {
  uint32_t r;
  asm("cvt.rn.bf16x2.f32 %0, %1, %2;" : "=r"(r) : "f"(hi), "f"(lo));
  return r;
}
__device__ __forceinline__ uint32_t hmul2_bf16(uint32_t a, uint32_t b) {
  uint32_t r;
  asm("mul.rn.bf16x2 %0, %1, %2;" : "=r"(r) : "r"(a), "r"(b));
  return r;
}
__device__ __forceinline__ uint32_t hsub2_bf16(uint32_t a, uint32_t b) {
  uint32_t r;
  asm("sub.rn.bf16x2 %0, %1, %2;" : "=r"(r) : "r"(a), "r"(b));
  return r;
}
__device__ __forceinline__ uint32_t hadd2_bf16(uint32_t a, uint32_t b) {
  uint32_t r;
  asm("add.rn.bf16x2 %0, %1, %2;" : "=r"(r) : "r"(a), "r"(b));
  return r;
}
__device__ __forceinline__ uint32_t hfma2_bf16(uint32_t a, uint32_t b, uint32_t c) {
  uint32_t r;
  asm("fma.rn.bf16x2 %0, %1, %2, %3;" : "=r"(r) : "r"(a), "r"(b), "r"(c));
  return r;
}
__device__ __forceinline__ bool mbar_test(uint32_t b, uint32_t ph) {
  uint32_t done;
  asm volatile("{.reg .pred p; mbarrier.test_wait.parity.shared::cta.b64 p, [%1], %2; selp.u32 %0,1,0,p;}" : "=r"(done) : "r"(b), "r"(ph) : "memory");
  return __all_sync(0xffffffffu, done != 0);
}
__device__ __forceinline__ uint4 ldg128_cg(const void* p) {
  uint4 v;
  asm volatile("ld.global.cg.v4.u32 {%0,%1,%2,%3}, [%4];" : "=r"(v.x), "=r"(v.y), "=r"(v.z), "=r"(v.w) : "l"(p) : "memory");
  return v;
}
__device__ __forceinline__ float bf_lo(uint32_t w) { return __uint_as_float(w << 16); }
__device__ __forceinline__ float bf_hi(uint32_t w) { return __uint_as_float(w & 0xffff0000u); }
__device__ __forceinline__ float rbf(float x) { return __bfloat162float(__float2bfloat16_rn(x)); }
__device__ __forceinline__ float ex2f(float x) { float r; asm("ex2.approx.ftz.f32 %0, %1;" : "=f"(r) : "f"(x)); return r; }
__device__ __forceinline__ float rcpf(float x) { float r; asm("rcp.approx.ftz.f32 %0, %1;" : "=f"(r) : "f"(x)); return r; }
__device__ __forceinline__ float gelu_tanh(float x) {
  const float c1 = -2.0f * 0.7978845608028654f * 1.4426950408889634f;
  const float c2 = c1 * 0.044715f;
  const float e = ex2f(x * fmaf(c2, x * x, c1));
  return x * rcpf(1.0f + e);
}
__device__ __forceinline__ float silu_f(float x) {
  const float e = ex2f(-1.4426950408889634f * x);
  return x * rcpf(1.0f + e);
}

__device__ __forceinline__ void wgmma_n128_tb(float (&d)[64], uint32_t da, uint32_t db, int scale_d) {
  asm volatile(
    "{\n.reg .pred p;\n.reg .b64 da, db;\nsetp.ne.b32 p, %66, 0;\n"
    "mov.b64 da, {%64, 0x40000040};\nmov.b64 db, {%65, 0x40000040};\n"
    "wgmma.mma_async.sync.aligned.m64n128k16.f32.bf16.bf16 {%0, %1, %2, %3, %4, %5, %6, %7, %8, %9, %10, %11, %12, %13, %14, %15, %16, %17, %18, %19, %20, %21, %22, %23, %24, %25, %26, %27, %28, %29, %30, %31, %32, %33, %34, %35, %36, %37, %38, %39, %40, %41, %42, %43, %44, %45, %46, %47, %48, %49, %50, %51, %52, %53, %54, %55, %56, %57, %58, %59, %60, %61, %62, %63}, da, db, p, 1, 1, 0, 1;\n}\n"
    : "+f"(d[0]), "+f"(d[1]), "+f"(d[2]), "+f"(d[3]), "+f"(d[4]), "+f"(d[5]), "+f"(d[6]), "+f"(d[7]), "+f"(d[8]), "+f"(d[9]), "+f"(d[10]), "+f"(d[11]), "+f"(d[12]), "+f"(d[13]), "+f"(d[14]), "+f"(d[15]), "+f"(d[16]), "+f"(d[17]), "+f"(d[18]), "+f"(d[19]), "+f"(d[20]), "+f"(d[21]), "+f"(d[22]), "+f"(d[23]), "+f"(d[24]), "+f"(d[25]), "+f"(d[26]), "+f"(d[27]), "+f"(d[28]), "+f"(d[29]), "+f"(d[30]), "+f"(d[31]), "+f"(d[32]), "+f"(d[33]), "+f"(d[34]), "+f"(d[35]), "+f"(d[36]), "+f"(d[37]), "+f"(d[38]), "+f"(d[39]), "+f"(d[40]), "+f"(d[41]), "+f"(d[42]), "+f"(d[43]), "+f"(d[44]), "+f"(d[45]), "+f"(d[46]), "+f"(d[47]), "+f"(d[48]), "+f"(d[49]), "+f"(d[50]), "+f"(d[51]), "+f"(d[52]), "+f"(d[53]), "+f"(d[54]), "+f"(d[55]), "+f"(d[56]), "+f"(d[57]), "+f"(d[58]), "+f"(d[59]), "+f"(d[60]), "+f"(d[61]), "+f"(d[62]), "+f"(d[63])
    : "r"(da), "r"(db), "r"(scale_d));
}
__device__ __forceinline__ void wgmma_n128_tb_p(float (&d)[64], uint32_t da, uint32_t db, int scale_d, int enable) {
  asm volatile(
    "{\n.reg .pred p;\n.reg .b64 da, db;\nsetp.ne.b32 p, %66, 0;\n.reg .pred q;\nsetp.ne.b32 q, %67, 0;\n"
    "mov.b64 da, {%64, 0x40000040};\nmov.b64 db, {%65, 0x40000040};\n"
    "@q wgmma.mma_async.sync.aligned.m64n128k16.f32.bf16.bf16 {%0, %1, %2, %3, %4, %5, %6, %7, %8, %9, %10, %11, %12, %13, %14, %15, %16, %17, %18, %19, %20, %21, %22, %23, %24, %25, %26, %27, %28, %29, %30, %31, %32, %33, %34, %35, %36, %37, %38, %39, %40, %41, %42, %43, %44, %45, %46, %47, %48, %49, %50, %51, %52, %53, %54, %55, %56, %57, %58, %59, %60, %61, %62, %63}, da, db, p, 1, 1, 0, 1;\n}\n"
    : "+f"(d[0]), "+f"(d[1]), "+f"(d[2]), "+f"(d[3]), "+f"(d[4]), "+f"(d[5]), "+f"(d[6]), "+f"(d[7]), "+f"(d[8]), "+f"(d[9]), "+f"(d[10]), "+f"(d[11]), "+f"(d[12]), "+f"(d[13]), "+f"(d[14]), "+f"(d[15]), "+f"(d[16]), "+f"(d[17]), "+f"(d[18]), "+f"(d[19]), "+f"(d[20]), "+f"(d[21]), "+f"(d[22]), "+f"(d[23]), "+f"(d[24]), "+f"(d[25]), "+f"(d[26]), "+f"(d[27]), "+f"(d[28]), "+f"(d[29]), "+f"(d[30]), "+f"(d[31]), "+f"(d[32]), "+f"(d[33]), "+f"(d[34]), "+f"(d[35]), "+f"(d[36]), "+f"(d[37]), "+f"(d[38]), "+f"(d[39]), "+f"(d[40]), "+f"(d[41]), "+f"(d[42]), "+f"(d[43]), "+f"(d[44]), "+f"(d[45]), "+f"(d[46]), "+f"(d[47]), "+f"(d[48]), "+f"(d[49]), "+f"(d[50]), "+f"(d[51]), "+f"(d[52]), "+f"(d[53]), "+f"(d[54]), "+f"(d[55]), "+f"(d[56]), "+f"(d[57]), "+f"(d[58]), "+f"(d[59]), "+f"(d[60]), "+f"(d[61]), "+f"(d[62]), "+f"(d[63])
    : "r"(da), "r"(db), "r"(scale_d), "r"(enable));
}
__device__ __forceinline__ void wgmma_n112(float (&d)[56], uint32_t da, uint32_t db, int scale_d) {
  asm volatile(
    "{\n.reg .pred p;\n.reg .b64 da, db;\nsetp.ne.b32 p, %58, 0;\n"
    "mov.b64 da, {%56, 0x40000040};\nmov.b64 db, {%57, 0x40000040};\n"
    "wgmma.mma_async.sync.aligned.m64n112k16.f32.bf16.bf16 {%0, %1, %2, %3, %4, %5, %6, %7, %8, %9, %10, %11, %12, %13, %14, %15, %16, %17, %18, %19, %20, %21, %22, %23, %24, %25, %26, %27, %28, %29, %30, %31, %32, %33, %34, %35, %36, %37, %38, %39, %40, %41, %42, %43, %44, %45, %46, %47, %48, %49, %50, %51, %52, %53, %54, %55}, da, db, p, 1, 1, 0, 0;\n}\n"
    : "+f"(d[0]), "+f"(d[1]), "+f"(d[2]), "+f"(d[3]), "+f"(d[4]), "+f"(d[5]), "+f"(d[6]), "+f"(d[7]), "+f"(d[8]), "+f"(d[9]), "+f"(d[10]), "+f"(d[11]), "+f"(d[12]), "+f"(d[13]), "+f"(d[14]), "+f"(d[15]), "+f"(d[16]), "+f"(d[17]), "+f"(d[18]), "+f"(d[19]), "+f"(d[20]), "+f"(d[21]), "+f"(d[22]), "+f"(d[23]), "+f"(d[24]), "+f"(d[25]), "+f"(d[26]), "+f"(d[27]), "+f"(d[28]), "+f"(d[29]), "+f"(d[30]), "+f"(d[31]), "+f"(d[32]), "+f"(d[33]), "+f"(d[34]), "+f"(d[35]), "+f"(d[36]), "+f"(d[37]), "+f"(d[38]), "+f"(d[39]), "+f"(d[40]), "+f"(d[41]), "+f"(d[42]), "+f"(d[43]), "+f"(d[44]), "+f"(d[45]), "+f"(d[46]), "+f"(d[47]), "+f"(d[48]), "+f"(d[49]), "+f"(d[50]), "+f"(d[51]), "+f"(d[52]), "+f"(d[53]), "+f"(d[54]), "+f"(d[55])
    : "r"(da), "r"(db), "r"(scale_d));
}
__device__ __forceinline__ void wgmma_n224_tb(float (&d)[112], uint32_t da, uint32_t db, int scale_d) {
  asm volatile(
    "{\n.reg .pred p;\n.reg .b64 da, db;\nsetp.ne.b32 p, %114, 0;\n"
    "mov.b64 da, {%112, 0x40000040};\nmov.b64 db, {%113, 0x40000040};\n"
    "wgmma.mma_async.sync.aligned.m64n224k16.f32.bf16.bf16 {%0, %1, %2, %3, %4, %5, %6, %7, %8, %9, %10, %11, %12, %13, %14, %15, %16, %17, %18, %19, %20, %21, %22, %23, %24, %25, %26, %27, %28, %29, %30, %31, %32, %33, %34, %35, %36, %37, %38, %39, %40, %41, %42, %43, %44, %45, %46, %47, %48, %49, %50, %51, %52, %53, %54, %55, %56, %57, %58, %59, %60, %61, %62, %63, %64, %65, %66, %67, %68, %69, %70, %71, %72, %73, %74, %75, %76, %77, %78, %79, %80, %81, %82, %83, %84, %85, %86, %87, %88, %89, %90, %91, %92, %93, %94, %95, %96, %97, %98, %99, %100, %101, %102, %103, %104, %105, %106, %107, %108, %109, %110, %111}, da, db, p, 1, 1, 0, 1;\n}\n"
    : "+f"(d[0]), "+f"(d[1]), "+f"(d[2]), "+f"(d[3]), "+f"(d[4]), "+f"(d[5]), "+f"(d[6]), "+f"(d[7]), "+f"(d[8]), "+f"(d[9]), "+f"(d[10]), "+f"(d[11]), "+f"(d[12]), "+f"(d[13]), "+f"(d[14]), "+f"(d[15]), "+f"(d[16]), "+f"(d[17]), "+f"(d[18]), "+f"(d[19]), "+f"(d[20]), "+f"(d[21]), "+f"(d[22]), "+f"(d[23]), "+f"(d[24]), "+f"(d[25]), "+f"(d[26]), "+f"(d[27]), "+f"(d[28]), "+f"(d[29]), "+f"(d[30]), "+f"(d[31]), "+f"(d[32]), "+f"(d[33]), "+f"(d[34]), "+f"(d[35]), "+f"(d[36]), "+f"(d[37]), "+f"(d[38]), "+f"(d[39]), "+f"(d[40]), "+f"(d[41]), "+f"(d[42]), "+f"(d[43]), "+f"(d[44]), "+f"(d[45]), "+f"(d[46]), "+f"(d[47]), "+f"(d[48]), "+f"(d[49]), "+f"(d[50]), "+f"(d[51]), "+f"(d[52]), "+f"(d[53]), "+f"(d[54]), "+f"(d[55]), "+f"(d[56]), "+f"(d[57]), "+f"(d[58]), "+f"(d[59]), "+f"(d[60]), "+f"(d[61]), "+f"(d[62]), "+f"(d[63]), "+f"(d[64]), "+f"(d[65]), "+f"(d[66]), "+f"(d[67]), "+f"(d[68]), "+f"(d[69]), "+f"(d[70]), "+f"(d[71]), "+f"(d[72]), "+f"(d[73]), "+f"(d[74]), "+f"(d[75]), "+f"(d[76]), "+f"(d[77]), "+f"(d[78]), "+f"(d[79]), "+f"(d[80]), "+f"(d[81]), "+f"(d[82]), "+f"(d[83]), "+f"(d[84]), "+f"(d[85]), "+f"(d[86]), "+f"(d[87]), "+f"(d[88]), "+f"(d[89]), "+f"(d[90]), "+f"(d[91]), "+f"(d[92]), "+f"(d[93]), "+f"(d[94]), "+f"(d[95]), "+f"(d[96]), "+f"(d[97]), "+f"(d[98]), "+f"(d[99]), "+f"(d[100]), "+f"(d[101]), "+f"(d[102]), "+f"(d[103]), "+f"(d[104]), "+f"(d[105]), "+f"(d[106]), "+f"(d[107]), "+f"(d[108]), "+f"(d[109]), "+f"(d[110]), "+f"(d[111])
    : "r"(da), "r"(db), "r"(scale_d));
}

constexpr int K1_NS = 6;
constexpr int K1_A_BYTES = 7 * 16384;
constexpr int K1_B_OFF = K1_A_BYTES;
constexpr int K1_STG_OFF = K1_B_OFF + K1_NS * 16384;
constexpr int K1_BAR_OFF = K1_STG_OFF + 8 * 2048;
constexpr int K1_SMEM = K1_BAR_OFF + 256 + 1024;

struct K1Ctx {
  uint32_t sb, bar_full, rel0, rel1;
  uint32_t dA, dBk, dBn;
  bool lane0;
};
__device__ __forceinline__ void k1_release(const K1Ctx& c, int slot) {
  if (c.lane0) {
    asm volatile("mbarrier.arrive.shared::cluster.b64 _, [%0];" ::"r"(c.rel0 + 8 * slot) : "memory");
    asm volatile("mbarrier.arrive.shared::cluster.b64 _, [%0];" ::"r"(c.rel1 + 8 * slot) : "memory");
  }
}

__device__ __noinline__ void geglu_tile(uint32_t stg, __nv_bfloat16* gptr  , int lane) {
  const int row = lane >> 1;
  const uint32_t base = stg + row * 64;
  const int sw = (row >> 1) & 3;
  uint4 g[2], u[2];
#pragma unroll
  for (int i = 0; i < 2; i++) {
    const uint32_t a = base + ((((lane & 1) * 2 + i) ^ sw) * 16);
    g[i] = lds128(a); u[i] = lds128(a + 1024);
  }
#pragma unroll
  for (int i = 0; i < 2; i++) {
    uint4 o;
    o.x = hmul2_bf16(pack_bf16(gelu_tanh(bf_lo(g[i].x)), gelu_tanh(bf_hi(g[i].x))), u[i].x);
    o.y = hmul2_bf16(pack_bf16(gelu_tanh(bf_lo(g[i].y)), gelu_tanh(bf_hi(g[i].y))), u[i].y);
    o.z = hmul2_bf16(pack_bf16(gelu_tanh(bf_lo(g[i].z)), gelu_tanh(bf_hi(g[i].z))), u[i].z);
    o.w = hmul2_bf16(pack_bf16(gelu_tanh(bf_lo(g[i].w)), gelu_tanh(bf_hi(g[i].w))), u[i].w);
    stg128(gptr + i * 8, o);
  }
}

__device__ __forceinline__ void k1_unit_ab(const K1Ctx& c, int warp, int lane, int mt, int j) {
  const uint32_t stg = c.sb + K1_STG_OFF + warp * 2048;
  const int wq = warp & 3;
  const int st_row = (lane & 7) + 8 * ((lane >> 3) & 1);
  const int st_chunk = lane >> 4;
  float acc[2][56];
  int slot = 0; uint32_t ph = 0;
#pragma unroll 1
  for (int kb = 0; kb < 7; kb++) {
    const int pslot = (slot == 0) ? K1_NS - 1 : slot - 1;
    mbar_wait(c.bar_full + 8 * slot, ph, 3);
    if (kb == 6) named_arrive(2, 256);
    if (kb == 0 && (threadIdx.x & 127) == 0) DBG(0, 4);
    if ((threadIdx.x & 127) == 0) DBGC(1, 46 + kb);
    wg_fence();
    const uint32_t da = c.dA + kb * 1024;
    const uint32_t db = c.dBk + slot * 1024;
#pragma unroll
    for (int k = 0; k < 4; k++) {
      wgmma_n112(acc[0], da + k * 2, db + k * 2, (kb | k) != 0);
      wgmma_n112(acc[1], da + 512 + k * 2, db + k * 2, (kb | k) != 0);
    }
    wg_commit();
    if (kb > 0) { wg_wait<1>(); k1_release(c, pslot); }
    if (++slot == K1_NS) { slot = 0; ph ^= 1; }
  }
  wg_wait<0>();
  k1_release(c, 6 % K1_NS);
  if ((threadIdx.x & 127) == 0) DBG(0, 5);
  const uint32_t sgn = (j < 4) ? 0u : 0x80008000u;
  __nv_bfloat16* outp = g_ab + (size_t)((j < 4 ? 0 : 2048) + mt * 128 + wq * 16 + (lane >> 3)) * 448 + (j & 3) * 112 + (lane & 7) * 8;
  const uint32_t sa = stg + st_row * 128;
  const uint32_t la = stg + (lane >> 3) * 128;
#pragma unroll
  for (int h = 0; h < 2; h++) {
#pragma unroll
    for (int rnd = 0; rnd < 2; rnd++) {
#pragma unroll
      for (int g = 0; g < (rnd ? 6 : 8); g += 2) {
        const float* a = &acc[h][4 * (g + 8 * rnd)];
        stmatrix_x4(sa + (((g + st_chunk) ^ (st_row & 7)) * 16),
                    pack_bf16(a[0], a[1]) ^ sgn, pack_bf16(a[2], a[3]) ^ sgn, pack_bf16(a[4], a[5]) ^ sgn, pack_bf16(a[6], a[7]) ^ sgn);
      }
      __syncwarp();
      if (rnd == 0 || (lane & 7) < 6) {
#pragma unroll
        for (int t = 0; t < 4; t++) {
          const int r7 = (t * 4 + (lane >> 3)) & 7;
          stg128(outp + (h * 64 + t * 4) * 448 + rnd * 64, lds128(la + t * 512 + (((lane & 7) ^ r7) * 16)));
        }
      }
      __syncwarp();
    }
  }
}

__device__ __forceinline__ void k1_unit_gu(const K1Ctx& c, int warp, int lane, int mt, int unit, int fb, int hsel) {
  const uint32_t stg = c.sb + K1_STG_OFF + warp * 2048;
  const int wq = warp & 3;
  const int full = (unit < 4);
  float acc[2][64];
  const uint32_t dA0 = c.dA + (full ? 0 : hsel * 512);
  int slot = (unit * 7) % K1_NS; uint32_t ph = ((unit * 7) / K1_NS) & 1;
  named_bar(2 + ((unit - 1) & 1), 256);
  if (full) {
#pragma unroll 1
    for (int kb = 0; kb < 7; kb++) {
      const int pslot = (slot == 0) ? K1_NS - 1 : slot - 1;
      mbar_wait(c.bar_full + 8 * slot, ph, 4);
      if (kb == 6) named_arrive(2 + (unit & 1), 256);
      if (kb == 0 && (threadIdx.x & 127) == 0) DBG(0, 4 + 3 * unit);
      wg_fence();
      const uint32_t da = dA0 + kb * 1024;
      const uint32_t db = c.dBn + slot * 1024;
#pragma unroll
      for (int k = 0; k < 4; k++) {
        wgmma_n128_tb(acc[0], da + k * 2, db + k * 128, (kb | k) != 0);
        wgmma_n128_tb(acc[1], da + 512 + k * 2, db + k * 128, (kb | k) != 0);
      }
      wg_commit();
      if (kb > 0) { wg_wait<1>(); k1_release(c, pslot); }
      if (++slot == K1_NS) { slot = 0; ph ^= 1; }
    }
  } else {
#pragma unroll 1
    for (int kb = 0; kb < 7; kb++) {
      const int pslot = (slot == 0) ? K1_NS - 1 : slot - 1;
      mbar_wait(c.bar_full + 8 * slot, ph, 5);
      if (kb == 0 && (threadIdx.x & 127) == 0) DBG(0, 4 + 3 * unit);
      wg_fence();
      const uint32_t da = dA0 + kb * 1024;
      const uint32_t db = c.dBn + slot * 1024;
#pragma unroll
      for (int k = 0; k < 4; k++) wgmma_n128_tb(acc[0], da + k * 2, db + k * 128, (kb | k) != 0);
      wg_commit();
      if (kb > 0) { wg_wait<1>(); k1_release(c, pslot); }
      if (++slot == K1_NS) { slot = 0; ph ^= 1; }
    }
  }
  wg_wait<0>();
  k1_release(c, (slot == 0) ? K1_NS - 1 : slot - 1);
  if ((threadIdx.x & 127) == 0) DBG(0, 5 + 3 * unit);
  const int st_row = (lane & 7) + 8 * ((lane >> 3) & 1);
  const int st_chunk = lane >> 4;
  const uint32_t sa = stg + st_row * 64;
  const int sw = (st_row >> 1) & 3;
  __nv_bfloat16* outp = g_h + (size_t)(mt * 128 + (full ? 0 : hsel * 64) + wq * 16 + (lane >> 1)) * 1792 + fb * 64 + (lane & 1) * 16;
#pragma unroll
  for (int h = 0; h < 2; h++) {
    if (h == 1 && !full) break;
#pragma unroll
    for (int ch = 0; ch < 2; ch++) {
#pragma unroll
      for (int g = 0; g < 4; g += 2) {
        const float* a = &acc[h][4 * (4 * ch + g)];
        const float* u = a + 32;
        const uint32_t ad = sa + (((g + st_chunk) ^ sw) * 16);
        stmatrix_x4(ad, pack_bf16(a[0], a[1]), pack_bf16(a[2], a[3]), pack_bf16(a[4], a[5]), pack_bf16(a[6], a[7]));
        stmatrix_x4(ad + 1024, pack_bf16(u[0], u[1]), pack_bf16(u[2], u[3]), pack_bf16(u[4], u[5]), pack_bf16(u[6], u[7]));
      }
      __syncwarp();
      geglu_tile(stg, outp + (size_t)h * 64 * 1792 + ch * 32, lane);
      __syncwarp();
    }
  }
}

struct PfPtrs { const uint8_t* wr; const uint8_t* wi; const uint8_t* wg; const uint8_t* wu; const uint8_t* wd; const uint8_t* cr; const uint8_t* ci; };

__global__ void __cluster_dims__(2, 1, 1) __launch_bounds__(384, 1)
k1_kernel(const __grid_constant__ CUtensorMap tm_wr, const __grid_constant__ CUtensorMap tm_wi,
          const __grid_constant__ CUtensorMap tm_wg, const __grid_constant__ CUtensorMap tm_wu,
          const __nv_bfloat16* __restrict__ x, const PfPtrs pf) {
  extern __shared__ uint8_t smem_raw[];
  const uint32_t sb = (s2u(smem_raw) + 1023) & ~1023u;
  const int tid = threadIdx.x, warp = tid >> 5, lane = tid & 31;
  uint32_t rank;
  asm volatile("mov.u32 %0, %%cluster_ctarank;" : "=r"(rank));
  const int cid = blockIdx.x >> 1;
  const int p = cid >> 3, j = cid & 7;
  const int mt = 2 * p + (int)rank;
  const uint32_t bar_full = sb + K1_BAR_OFF;
  const uint32_t bar_empty = bar_full + 8 * K1_NS;
  const int fb_base = 7 * (j >> 1);
  const int fb0 = fb_base + ((j & 1) ? 4 : 0);
  const int fbh = fb_base + 3;
  const CUtensorMap* tw = (j < 4) ? &tm_wr : &tm_wi;
  const CUtensorMap* tgu = rank ? &tm_wu : &tm_wg;

  if (tid == 0) DBG(0, 0);
  if (tid == 256) {
    for (int i = 0; i < K1_NS; i++) { mbar_init(bar_full + 8 * i, 1); mbar_init(bar_empty + 8 * i, 8); }
    asm volatile("fence.mbarrier_init.release.cluster;" ::: "memory");
    prefetch_tmap(tw);
    prefetch_tmap(tgu);
    if (blockIdx.x < 64) g_flags[blockIdx.x] = 0;
  }
  __syncwarp();
  cluster_arrive_relaxed();
  pdl_launch();

  if (warp >= 8) {
    reg_dec<40>();
    cluster_wait();
    if (tid == 256) {
      int slot = 0; uint32_t ph = 0;
      int kb = 0, unit = 0;
#pragma unroll 1
      for (int s = 0; s < 35; s++) {
        if (s >= K1_NS) mbar_wait(bar_empty + 8 * slot, ph ^ 1, 2);
        DBG(0, 20 + s);
        const uint32_t dst = sb + K1_B_OFF + slot * 16384;
        if (unit == 0) {
          mbar_expect(bar_full + 8 * slot, 14336);
          tma2d_mc(dst + rank * 7168, tw, kb * 64, (j & 3) * 112 + rank * 56, bar_full + 8 * slot, 3);
        } else {
          const int fb = (unit == 4) ? fbh : (fb0 + unit - 1);
          mbar_expect(bar_full + 8 * slot, 16384);
          tma2d_mc(dst + rank * 8192, tgu, fb * 64, kb * 64, bar_full + 8 * slot, 3);
        }
        if (++kb == 7) { kb = 0; unit++; }
        if (++slot == K1_NS) { slot = 0; ph ^= 1; }
      }
    } else if (tid == 288) {
      const int b = blockIdx.x;
      l2_prefetch(pf.wg + b * 12544, 12544);
      l2_prefetch(pf.wu + b * 12544, 12544);
    }
  } else {
    reg_inc<232>();
    const int wg = warp >> 2;
    {
      const int c = lane & 7;
      const int r0 = warp * 16 + (lane >> 3);
      const uint4* src = reinterpret_cast<const uint4*>(x + (size_t)(mt * 128 + r0) * 448) + c;
      uint4 nx[7];
#pragma unroll
      for (int b = 0; b < 7; b++)
        asm volatile("ld.global.nc.v4.u32 {%0,%1,%2,%3}, [%4];" : "=r"(nx[b].x), "=r"(nx[b].y), "=r"(nx[b].z), "=r"(nx[b].w) : "l"(src + b * 8) : "memory");
#pragma unroll
      for (int pass = 1; pass < 4; pass++) asm volatile("prefetch.global.L2 [%0];" ::"l"(src + pass * 4 * 56 + c * 7 - c) : "memory");
#pragma unroll 1
      for (int pass = 0; pass < 4; pass++) {
        uint4 v[7];
#pragma unroll
        for (int b = 0; b < 7; b++) v[b] = nx[b];
        if (pass < 3) {
          const uint4* s2 = src + (pass + 1) * 4 * 56;
#pragma unroll
          for (int b = 0; b < 7; b++)
            asm volatile("ld.global.nc.v4.u32 {%0,%1,%2,%3}, [%4];" : "=r"(nx[b].x), "=r"(nx[b].y), "=r"(nx[b].z), "=r"(nx[b].w) : "l"(s2 + b * 8) : "memory");
        }
        float s0 = 0.f, s1 = 0.f, s2v = 0.f, s3 = 0.f;
#pragma unroll
        for (int b = 0; b < 7; b++) {
          s0 += bf_lo(v[b].x) + bf_hi(v[b].x); s1 += bf_lo(v[b].y) + bf_hi(v[b].y);
          s2v += bf_lo(v[b].z) + bf_hi(v[b].z); s3 += bf_lo(v[b].w) + bf_hi(v[b].w);
        }
        float m = (s0 + s1) + (s2v + s3);
        m += __shfl_xor_sync(0xffffffffu, m, 1);
        m += __shfl_xor_sync(0xffffffffu, m, 2);
        m += __shfl_xor_sync(0xffffffffu, m, 4);
        m *= (1.0f / 448.0f);
        float q0 = 0.f, q1 = 0.f, q2 = 0.f, q3 = 0.f;
#pragma unroll
        for (int b = 0; b < 7; b++) {
          float d;
          d = bf_lo(v[b].x) - m; q0 = fmaf(d, d, q0); d = bf_hi(v[b].x) - m; q1 = fmaf(d, d, q1);
          d = bf_lo(v[b].y) - m; q2 = fmaf(d, d, q2); d = bf_hi(v[b].y) - m; q3 = fmaf(d, d, q3);
          d = bf_lo(v[b].z) - m; q0 = fmaf(d, d, q0); d = bf_hi(v[b].z) - m; q1 = fmaf(d, d, q1);
          d = bf_lo(v[b].w) - m; q2 = fmaf(d, d, q2); d = bf_hi(v[b].w) - m; q3 = fmaf(d, d, q3);
        }
        float q = (q0 + q1) + (q2 + q3);
        q += __shfl_xor_sync(0xffffffffu, q, 1);
        q += __shfl_xor_sync(0xffffffffu, q, 2);
        q += __shfl_xor_sync(0xffffffffu, q, 4);
        const float var_b = rbf(q * (1.0f / 448.0f));
        const float den = rbf(sqrtf(rbf(var_b + 1e-5f)));
        const float ri = 1.0f / den;
        const float rih = rbf(ri);
        const uint32_t rhi2 = pack_bf16(rih, rih), rlo2 = pack_bf16(ri - rih, ri - rih);
        const uint32_t m2 = pack_bf16(m, m);
        const int r = r0 + pass * 4;
        const uint32_t a0 = sb + r * 128 + ((c ^ (r & 7)) * 16);
#pragma unroll
        for (int b = 0; b < 7; b++) {
          uint32_t w4[4] = {v[b].x, v[b].y, v[b].z, v[b].w};
#pragma unroll
          for (int qq = 0; qq < 4; qq++) {
            const uint32_t dw = hsub2_bf16(w4[qq], m2);
            w4[qq] = hfma2_bf16(dw, rhi2, hmul2_bf16(dw, rlo2));
          }
          sts128(a0 + b * 16384, make_uint4(w4[0], w4[1], w4[2], w4[3]));
        }
      }
    }
    if (lane == 0) DBG(0, 59 + (warp & 3));
    asm volatile("fence.proxy.async.shared::cta;" ::: "memory");
    named_bar(1, 256);
    cluster_wait();
    if (tid == 0) DBG(0, 3);

    K1Ctx c;
    c.sb = sb; c.bar_full = bar_full; c.lane0 = (lane == 0);
    asm volatile("mapa.shared::cluster.u32 %0, %1, %2;" : "=r"(c.rel0) : "r"(bar_empty), "r"(0));
    asm volatile("mapa.shared::cluster.u32 %0, %1, %2;" : "=r"(c.rel1) : "r"(bar_empty), "r"(1));
    c.dA = make_desc(sb, 16, 1024);
    c.dBk = make_desc(sb + K1_B_OFF, 16, 1024);
    c.dBn = make_desc(sb + K1_B_OFF, 8192, 1024);
    if (wg == 0) {
      k1_unit_ab(c, warp, lane, mt, j);
      if (tid == 0) DBG(0, 6);
    }
#pragma unroll 1
    for (int unit = 2 - wg; unit < 5; unit += 2) {
      k1_unit_gu(c, warp, lane, mt, unit, (unit == 4) ? fbh : fb0 + unit - 1, j & 1);
      if ((tid & 127) == 0) DBG(0, 6 + 3 * unit);
    }
  }
  __syncwarp();
  cluster_arrive_relaxed();
  cluster_wait();
}

constexpr int K2_NS = 4;
constexpr int K2_STAGE = 16384 + 32768;
constexpr int K2_BAR_OFF = K2_NS * K2_STAGE;
constexpr int K2_SMEM = K2_BAR_OFF + 256 + 1024;
constexpr int K2_PITCH = 464;

__device__ __forceinline__ void spin_flag(const unsigned int* flag, unsigned int target) {
  int it = 0;
  while (true) {
    unsigned int v;
    asm volatile("ld.acquire.gpu.global.u32 %0, [%1];" : "=r"(v) : "l"(flag) : "memory");
    if (v >= target) break;
    if (++it > SPIN_LIMIT) { TIMEOUT(20); break; }
  }
}

__global__ void __cluster_dims__(2, 1, 1) __launch_bounds__(384, 1)
k2_kernel(const __grid_constant__ CUtensorMap tm_cr, const __grid_constant__ CUtensorMap tm_ci, const __grid_constant__ CUtensorMap tm_h,
          const __grid_constant__ CUtensorMap tm_ab, const __grid_constant__ CUtensorMap tm_wd,
          const __nv_bfloat16* __restrict__ x, __nv_bfloat16* __restrict__ out) {
  extern __shared__ uint8_t smem_raw[];
  const uint32_t sb = (s2u(smem_raw) + 1023) & ~1023u;
  const int tid = threadIdx.x, warp = tid >> 5, lane = tid & 31;
  uint32_t rank;
  asm volatile("mov.u32 %0, %%cluster_ctarank;" : "=r"(rank));
  const int cid = blockIdx.x >> 1;
  const int q = cid & 3, n = (cid >> 2) & 1, p = cid >> 3;
  const int mt = 2 * p + (int)rank;
  const int tile = mt * 2 + n;
  const uint32_t bar_full = sb + K2_BAR_OFF;
  const uint32_t bar_empty = bar_full + 8 * K2_NS;
  const int g0 = (q == 0) ? 0 : (q == 1 ? 22 : (q == 2 ? 43 : 64));
  const int nkb = (q == 0) ? 22 : (q == 3 ? 28 : 21);

  if (tid == 0) DBG(1, 0);
  if (tid == 256) {
    for (int i = 0; i < K2_NS; i++) { mbar_init(bar_full + 8 * i, 1); mbar_init(bar_empty + 8 * i, 16); }
    asm volatile("fence.mbarrier_init.release.cluster;" ::: "memory");
    if (q == 3) { prefetch_tmap(&tm_h); prefetch_tmap(&tm_wd); }
    else { prefetch_tmap(&tm_cr); prefetch_tmap(&tm_ci); prefetch_tmap(&tm_ab); }
  }
  __syncwarp();
  cluster_arrive_relaxed();
  cluster_wait();

  if (warp >= 8) {
    reg_dec<40>();
    if (tid == 256) {
      const CUtensorMap* tb = (q < 3) ? &tm_ab : &tm_wd;
      const int kb0 = (q < 3) ? g0 : 0;
      int slot = 0; uint32_t ph = 0;
#pragma unroll 1
      for (int it = 0; it < nkb + K2_NS; it++) {
        const int s = (it < K2_NS) ? it : it - K2_NS;
        const bool pre = (it < K2_NS), post = (!pre && s < K2_NS);
        if (it == K2_NS) { pdl_wait(); DBG(1, 31); slot = 0; }
        if (!pre && !post) mbar_wait(bar_empty + 8 * slot, ph, 10);
        const uint32_t dst = sb + slot * K2_STAGE;
        const uint32_t fb = bar_full + 8 * slot;
        if (!post) mbar_expect(fb, K2_STAGE);
        const bool doA = pre ? (q < 3) : (post ? (q == 3) : true);
        const bool doB = pre ? (q == 3) : (post ? (q < 3) : true);
        if (doA) {
          const int g = g0 + s;
          const CUtensorMap* ta = (g < 32) ? &tm_cr : (g < 64 ? &tm_ci : &tm_h);
          tma2d(dst, ta, (g & 31) * 64 + ((g >= 96) ? 2048 : 0), mt * 128, fb);
        }
        if (doB) {
          tma3d_mc(dst + 16384 + (2 * rank) * 8192, tb, (2 * rank) * 64, n, (kb0 + s) * 64, fb, 3);
          tma3d_mc(dst + 16384 + (2 * rank + 1) * 8192, tb, (2 * rank + 1) * 64, n, (kb0 + s) * 64, fb, 3);
        }
        if (++slot == K2_NS) { slot = 0; if (!pre && !post) ph ^= 1; }
      }
    }
  } else {
    reg_inc<232>();
    const int wg = warp >> 2;
    float acc[112];
    uint32_t rel0, rel1;
    asm volatile("mapa.shared::cluster.u32 %0, %1, %2;" : "=r"(rel0) : "r"(bar_empty), "r"(0));
    asm volatile("mapa.shared::cluster.u32 %0, %1, %2;" : "=r"(rel1) : "r"(bar_empty), "r"(1));
    const uint32_t dA0 = make_desc(sb + wg * 8192, 16, 1024);
    const uint32_t dB0 = make_desc(sb + 16384, 8192, 1024);
    int slot = 0; uint32_t ph = 0;
#pragma unroll 1
    for (int s = 0; s < nkb; s++) {
      mbar_wait(bar_full + 8 * slot, ph, 11);
      if (tid == 0) DBG(1, 1 + s);
      if (tid == 0 && (s == 5 || s == 15)) DBGC(1, 53 + (s == 15));
      if (tid == 0 && (s == 23 || s == 27)) DBGC(1, 55 + (s == 27));
      wg_fence();
      const uint32_t da = dA0 + slot * (K2_STAGE / 16);
      const uint32_t db = dB0 + slot * (K2_STAGE / 16);
#pragma unroll
      for (int k = 0; k < 4; k++) wgmma_n224_tb(acc, da + k * 2, db + k * 128, (s | k) != 0);
      wg_commit();
      if (s > 0) {
        wg_wait<1>();
        const int ps = (slot == 0) ? K2_NS - 1 : slot - 1;
        if (lane == 0) {
          asm volatile("mbarrier.arrive.shared::cluster.b64 _, [%0];" ::"r"(rel0 + 8 * ps) : "memory");
          asm volatile("mbarrier.arrive.shared::cluster.b64 _, [%0];" ::"r"(rel1 + 8 * ps) : "memory");
        }
      }
      if (++slot == K2_NS) { slot = 0; ph ^= 1; }
    }
    wg_wait<0>();
    pdl_wait();
    if (tid == 0) DBG(1, 29);
    if (q < 3) {
      float4* part = g_part + (size_t)tile * (3 * 28 * 256) + tid;
#pragma unroll
      for (int g = 0; g < 28; g++) part[(q * 28 + g) * 256] = make_float4(acc[4 * g], acc[4 * g + 1], acc[4 * g + 2], acc[4 * g + 3]);
      __threadfence();
      named_bar(1, 256);
      if (tid == 0) { atomicAdd(&g_flags[tile], 1u); spin_flag(&g_flags[tile], 3u); }
      named_bar(1, 256);
      if (tid == 0) DBG(1, 30);
      const int G0 = q * 10, NG = (q == 2) ? 8 : 10;
      const float4* pp = part + G0 * 256;
      const uint32_t sl = sb + tid * 16;
#pragma unroll 1
      for (int g = 0; g < NG; g++) {
        cp_async16(sl + (3 * g) * 4096, pp + g * 256);
        cp_async16(sl + (3 * g + 1) * 4096, pp + (28 + g) * 256);
        cp_async16(sl + (3 * g + 2) * 4096, pp + (56 + g) * 256);
      }
      cp_async_wait_all();
      uint32_t* sp = reinterpret_cast<uint32_t*>(g_s + (size_t)(mt * 128 + warp * 16 + (lane >> 2)) * 448 + n * 224 + (lane & 3) * 2) + G0 * 4;
#pragma unroll 2
      for (int g = 0; g < NG; g++) {
        const uint4 a = lds128(sl + (3 * g) * 4096), b = lds128(sl + (3 * g + 1) * 4096), cc = lds128(sl + (3 * g + 2) * 4096);
        sp[g * 4] = pack_bf16(__uint_as_float(a.x) + __uint_as_float(b.x) + __uint_as_float(cc.x), __uint_as_float(a.y) + __uint_as_float(b.y) + __uint_as_float(cc.y));
        sp[g * 4 + 8 * 224] = pack_bf16(__uint_as_float(a.z) + __uint_as_float(b.z) + __uint_as_float(cc.z), __uint_as_float(a.w) + __uint_as_float(b.w) + __uint_as_float(cc.w));
      }
      __threadfence();
      named_bar(1, 256);
      if (tid == 0) atomicAdd(&g_flags[32 + tile], 1u);
    } else {
      named_bar(1, 256);
      const uint32_t stg = sb + warp * 16 * K2_PITCH;
      const int st_row = (lane & 7) + 8 * ((lane >> 3) & 1);
      const uint32_t sa = stg + st_row * K2_PITCH + (lane >> 4) * 16;
#pragma unroll
      for (int g = 0; g < 28; g += 2) {
        const float* a = &acc[4 * g];
        stmatrix_x4(sa + g * 16, pack_bf16(a[0], a[1]), pack_bf16(a[2], a[3]), pack_bf16(a[4], a[5]), pack_bf16(a[6], a[7]));
      }
      const int lc = (lane < 28) ? lane : 27;
      const size_t gbase = (size_t)(mt * 128 + warp * 16) * 448 + n * 224 + lc * 8;
      const uint32_t lp = stg + lc * 16;
      const uint32_t xs = sb + 65536 + warp * 16384 + lane * 16;
#pragma unroll 1
      for (int t = 0; t < 16; t++) cp_async16(xs + t * 512, x + gbase + t * 448);
      __syncwarp();
#pragma unroll 2
      for (int t = 0; t < 16; t++) {
        const uint4 fv = lds128(lp + t * K2_PITCH);
        uint4 o;
        o.x = pack_bf16(silu_f(bf_lo(fv.x)), silu_f(bf_hi(fv.x)));
        o.y = pack_bf16(silu_f(bf_lo(fv.y)), silu_f(bf_hi(fv.y)));
        o.z = pack_bf16(silu_f(bf_lo(fv.z)), silu_f(bf_hi(fv.z)));
        o.w = pack_bf16(silu_f(bf_lo(fv.w)), silu_f(bf_hi(fv.w)));
        if (lane < 28) sts128(lp + t * K2_PITCH, o);
      }
      if (lane == 0) spin_flag(&g_flags[32 + tile], 3u);
      __syncwarp();
      if (tid == 0) DBG(1, 30);
#pragma unroll 1
      for (int t = 0; t < 16; t++) cp_async16(xs + 8192 + t * 512, g_s + gbase + t * 448);
      cp_async_wait_all();
#pragma unroll 4
      for (int t = 0; t < 16; t++) {
        const uint4 gv = lds128(lp + t * K2_PITCH), xx = lds128(xs + t * 512), ss = lds128(xs + 8192 + t * 512);
        uint4 o;
        o.x = hadd2_bf16(xx.x, hmul2_bf16(ss.x, gv.x));
        o.y = hadd2_bf16(xx.y, hmul2_bf16(ss.y, gv.y));
        o.z = hadd2_bf16(xx.z, hmul2_bf16(ss.z, gv.z));
        o.w = hadd2_bf16(xx.w, hmul2_bf16(ss.w, gv.w));
        if (lane < 28) stg128(out + gbase + t * 448, o);
      }
    }
    if (tid == 0) DBG(1, 63);
  }
  __syncwarp();
  cluster_arrive_relaxed();
  cluster_wait();
}

typedef CUresult (*EncFn)(CUtensorMap*, CUtensorMapDataType, cuuint32_t, void*, const cuuint64_t*, const cuuint64_t*, const cuuint32_t*,
                          const cuuint32_t*, CUtensorMapInterleave, CUtensorMapSwizzle, CUtensorMapL2promotion, CUtensorMapFloatOOBfill);

void make2d(EncFn enc, CUtensorMap* tm, const void* ptr, uint64_t cols, uint64_t rows, uint32_t bc, uint32_t br) {
  cuuint64_t gd[2] = {cols, rows};
  cuuint64_t gs[1] = {cols * 2};
  cuuint32_t bd[2] = {bc, br};
  cuuint32_t es[2] = {1, 1};
  enc(tm, CU_TENSOR_MAP_DATA_TYPE_BFLOAT16, 2, const_cast<void*>(ptr), gd, gs, bd, es, CU_TENSOR_MAP_INTERLEAVE_NONE,
      CU_TENSOR_MAP_SWIZZLE_128B, CU_TENSOR_MAP_L2_PROMOTION_L2_128B, CU_TENSOR_MAP_FLOAT_OOB_FILL_NONE);
}
void make3d_half(EncFn enc, CUtensorMap* tm, const void* ptr, uint64_t rows) {
  cuuint64_t gd[3] = {224, 2, rows};
  cuuint64_t gs[2] = {448, 896};
  cuuint32_t bd[3] = {64, 1, 64};
  cuuint32_t es[3] = {1, 1, 1};
  enc(tm, CU_TENSOR_MAP_DATA_TYPE_BFLOAT16, 3, const_cast<void*>(ptr), gd, gs, bd, es, CU_TENSOR_MAP_INTERLEAVE_NONE,
      CU_TENSOR_MAP_SWIZZLE_128B, CU_TENSOR_MAP_L2_PROMOTION_L2_128B, CU_TENSOR_MAP_FLOAT_OOB_FILL_NONE);
}

struct Maps { CUtensorMap wr, wi, wg, wu, cr, ci, h, ab, wd; };

}

extern "C" void kernel_launch(void* const* d_in, const int* in_sizes, int n_in, void* d_out, int out_size) {
  (void)in_sizes; (void)n_in; (void)out_size;
  static Maps maps;
  static const void* cached[9] = {nullptr};
  static bool attr_done = false;
  bool same = true;
  for (int i = 0; i < 9; i++) same = same && (cached[i] == d_in[i]);
  if (!same) {
    void* fn = nullptr;
    cudaDriverEntryPointQueryResult qr;
    cudaGetDriverEntryPoint("cuTensorMapEncodeTiled", &fn, cudaEnableDefault, &qr);
    EncFn enc = (EncFn)fn;
    void *p_ab = nullptr, *p_h = nullptr;
    cudaGetSymbolAddress(&p_ab, g_ab);
    cudaGetSymbolAddress(&p_h, g_h);
    make2d(enc, &maps.cr, d_in[1], 2048, 2048, 64, 128);
    make2d(enc, &maps.ci, d_in[2], 2048, 2048, 64, 128);
    make2d(enc, &maps.wr, d_in[3], 448, 448, 64, 56);
    make2d(enc, &maps.wi, d_in[4], 448, 448, 64, 56);
    make2d(enc, &maps.wg, d_in[6], 1792, 448, 64, 64);
    make2d(enc, &maps.wu, d_in[7], 1792, 448, 64, 64);
    make3d_half(enc, &maps.wd, d_in[8], 1792);
    make2d(enc, &maps.h, p_h, 1792, 2048, 64, 128);
    make3d_half(enc, &maps.ab, p_ab, 4096);
    for (int i = 0; i < 9; i++) cached[i] = d_in[i];
  }
  if (!attr_done) {
    cudaFuncSetAttribute(k1_kernel, cudaFuncAttributeMaxDynamicSharedMemorySize, K1_SMEM);
    cudaFuncSetAttribute(k2_kernel, cudaFuncAttributeMaxDynamicSharedMemorySize, K2_SMEM);
    attr_done = true;
  }
  PfPtrs pf;
  pf.wr = (const uint8_t*)d_in[3]; pf.wi = (const uint8_t*)d_in[4]; pf.wg = (const uint8_t*)d_in[6]; pf.wu = (const uint8_t*)d_in[7];
  pf.wd = (const uint8_t*)d_in[8]; pf.cr = (const uint8_t*)d_in[1]; pf.ci = (const uint8_t*)d_in[2];
  k1_kernel<<<128, 384, K1_SMEM>>>(maps.wr, maps.wi, maps.wg, maps.wu, (const __nv_bfloat16*)d_in[0], pf);

  cudaLaunchConfig_t cfg = {};
  cfg.gridDim = dim3(128); cfg.blockDim = dim3(384); cfg.dynamicSmemBytes = K2_SMEM; cfg.stream = cudaStreamPerThread;
  cudaLaunchAttribute at[1];
  at[0].id = cudaLaunchAttributeProgrammaticStreamSerialization;
  at[0].val.programmaticStreamSerializationAllowed = 1;
  cfg.attrs = at; cfg.numAttrs = 1;
  cudaLaunchKernelEx(&cfg, k2_kernel, maps.cr, maps.ci, maps.h, maps.ab, maps.wd, (const __nv_bfloat16*)d_in[0], (__nv_bfloat16*)d_out);
}
```

```cpp
#include <cuda_runtime.h>
#include <cuda_bf16.h>
#include <cuda.h>
#include <stdint.h>

namespace {

__device__ __align__(1024) __nv_bfloat16 g_ab[4096 * 448];
__device__ __align__(1024) __nv_bfloat16 g_h[2048 * 1792];
__device__ uint2 g_part[32 * 3 * 28 * 256];
__device__ __align__(1024) __nv_bfloat16 g_s[2048 * 448];
__device__ unsigned int g_flags[64];

#define DBG(k, i) do {} while (0)
#define DBGC(k, i) do {} while (0)

#define TIMEOUT(code) __trap()
#define SPIN_LIMIT (1 << 22)
__device__ __forceinline__ uint32_t s2u(const void* p) { return (uint32_t)__cvta_generic_to_shared(p); }
__device__ __forceinline__ void mbar_init(uint32_t b, int c) { asm volatile("mbarrier.init.shared::cta.b64 [%0], %1;" ::"r"(b), "r"(c)); }
__device__ __forceinline__ void mbar_expect(uint32_t b, uint32_t bytes) {
  asm volatile("mbarrier.arrive.expect_tx.shared::cta.b64 _, [%0], %1;" ::"r"(b), "r"(bytes) : "memory");
}
__device__ __forceinline__ void mbar_wait(uint32_t b, uint32_t ph, int code = 1) {
  uint32_t done = 0;
  int it = 0;
  while (true) {
    asm volatile("{.reg .pred p; mbarrier.try_wait.parity.shared::cta.b64 p, [%1], %2; selp.u32 %0,1,0,p;}" : "=r"(done) : "r"(b), "r"(ph) : "memory");
    if (done) break;
    if (++it > SPIN_LIMIT) { TIMEOUT(code); break; }
  }
}
__device__ __forceinline__ void mbar_arrive_cluster(uint32_t b, uint32_t cta) {
  uint32_t r;
  asm volatile("mapa.shared::cluster.u32 %0, %1, %2;" : "=r"(r) : "r"(b), "r"(cta));
  asm volatile("mbarrier.arrive.shared::cluster.b64 _, [%0];" ::"r"(r) : "memory");
}
__device__ __forceinline__ void tma2d(uint32_t dst, const CUtensorMap* m, int c0, int c1, uint32_t bar) {
  asm volatile("cp.async.bulk.tensor.2d.shared::cluster.global.mbarrier::complete_tx::bytes [%0], [%1, {%3,%4}], [%2];" ::"r"(dst), "l"(m), "r"(bar), "r"(c0), "r"(c1) : "memory");
}
__device__ __forceinline__ void tma2d_mc(uint32_t dst, const CUtensorMap* m, int c0, int c1, uint32_t bar, uint16_t mask) {
  asm volatile("cp.async.bulk.tensor.2d.shared::cluster.global.mbarrier::complete_tx::bytes.multicast::cluster [%0], [%1, {%3,%4}], [%2], %5;" ::"r"(dst), "l"(m), "r"(bar), "r"(c0), "r"(c1), "h"(mask) : "memory");
}
__device__ __forceinline__ void tma3d_mc(uint32_t dst, const CUtensorMap* m, int c0, int c1, int c2, uint32_t bar, uint16_t mask) {
  asm volatile("cp.async.bulk.tensor.3d.shared::cluster.global.mbarrier::complete_tx::bytes.multicast::cluster [%0], [%1, {%3,%4,%5}], [%2], %6;" ::"r"(dst), "l"(m), "r"(bar), "r"(c0), "r"(c1), "r"(c2), "h"(mask) : "memory");
}
__device__ __forceinline__ void prefetch_tmap(const CUtensorMap* m) { asm volatile("prefetch.tensormap [%0];" ::"l"(m) : "memory"); }
__device__ __forceinline__ void l2_prefetch(const void* p, uint32_t bytes) {
  asm volatile("cp.async.bulk.prefetch.L2.global [%0], %1;" ::"l"(p), "r"(bytes) : "memory");
}
__device__ __forceinline__ void cluster_arrive_relaxed() { asm volatile("barrier.cluster.arrive.relaxed.aligned;" ::: "memory"); }
__device__ __forceinline__ void cluster_wait() { asm volatile("barrier.cluster.wait.aligned;" ::: "memory"); }
__device__ __forceinline__ void wg_fence() { __syncwarp(); asm volatile("wgmma.fence.sync.aligned;" ::: "memory"); }
__device__ __forceinline__ void wg_commit() { asm volatile("wgmma.commit_group.sync.aligned;" ::: "memory"); }
template <int N> __device__ __forceinline__ void wg_wait() { __syncwarp(); asm volatile("wgmma.wait_group.sync.aligned %0;" ::"n"(N) : "memory"); }
__device__ __forceinline__ void named_bar(int id, int n) { asm volatile("bar.sync %0, %1;" ::"r"(id), "r"(n) : "memory"); }
__device__ __forceinline__ void named_arrive(int id, int n) { asm volatile("bar.arrive %0, %1;" ::"r"(id), "r"(n) : "memory"); }
template <int N> __device__ __forceinline__ void reg_inc() { asm volatile("setmaxnreg.inc.sync.aligned.u32 %0;" ::"n"(N)); }
template <int N> __device__ __forceinline__ void reg_dec() { asm volatile("setmaxnreg.dec.sync.aligned.u32 %0;" ::"n"(N)); }
__device__ __forceinline__ void pdl_wait() { asm volatile("griddepcontrol.wait;" ::: "memory"); }
__device__ __forceinline__ void pdl_launch() { asm volatile("griddepcontrol.launch_dependents;" ::: "memory"); }

__device__ __forceinline__ uint32_t make_desc(uint32_t addr, uint32_t lbo, uint32_t  ) {
  return ((addr & 0x3FFFF) >> 4) | ((lbo >> 4) << 16);
}
__device__ __forceinline__ void stmatrix_x4(uint32_t addr, uint32_t r0, uint32_t r1, uint32_t r2, uint32_t r3) {
  asm volatile("stmatrix.sync.aligned.m8n8.x4.shared.b16 [%0], {%1,%2,%3,%4};" ::"r"(addr), "r"(r0), "r"(r1), "r"(r2), "r"(r3) : "memory");
}
__device__ __forceinline__ uint4 lds128(uint32_t a) {
  uint4 v;
  asm volatile("ld.shared.v4.u32 {%0,%1,%2,%3}, [%4];" : "=r"(v.x), "=r"(v.y), "=r"(v.z), "=r"(v.w) : "r"(a) : "memory");
  return v;
}
__device__ __forceinline__ void sts128(uint32_t a, uint4 v) {
  asm volatile("st.shared.v4.u32 [%0], {%1,%2,%3,%4};" ::"r"(a), "r"(v.x), "r"(v.y), "r"(v.z), "r"(v.w) : "memory");
}
__device__ __forceinline__ void stg128(void* p, uint4 v) {
  asm volatile("st.global.v4.u32 [%0], {%1,%2,%3,%4};" ::"l"(p), "r"(v.x), "r"(v.y), "r"(v.z), "r"(v.w) : "memory");
}
__device__ __forceinline__ void cp_async16(uint32_t dst, const void* src) {
  asm volatile("cp.async.cg.shared.global [%0], [%1], 16;" ::"r"(dst), "l"(src) : "memory");
}
__device__ __forceinline__ void cp_async8(uint32_t dst, const void* src) {
  asm volatile("cp.async.ca.shared.global [%0], [%1], 8;" ::"r"(dst), "l"(src) : "memory");
}
__device__ __forceinline__ uint2 lds64(uint32_t a) {
  uint2 v;
  asm volatile("ld.shared.v2.u32 {%0,%1}, [%2];" : "=r"(v.x), "=r"(v.y) : "r"(a) : "memory");
  return v;
}
__device__ __forceinline__ void cp_async_wait_all() { asm volatile("cp.async.wait_all;" ::: "memory"); }
__device__ __forceinline__ uint32_t pack_bf16(float lo, float hi) {
  uint32_t r;
  asm("cvt.rn.bf16x2.f32 %0, %1, %2;" : "=r"(r) : "f"(hi), "f"(lo));
  return r;
}
__device__ __forceinline__ uint32_t hmul2_bf16(uint32_t a, uint32_t b) {
  uint32_t r;
  asm("mul.rn.bf16x2 %0, %1, %2;" : "=r"(r) : "r"(a), "r"(b));
  return r;
}
__device__ __forceinline__ uint32_t hsub2_bf16(uint32_t a, uint32_t b) {
  uint32_t r;
  asm("sub.rn.bf16x2 %0, %1, %2;" : "=r"(r) : "r"(a), "r"(b));
  return r;
}
__device__ __forceinline__ uint32_t hadd2_bf16(uint32_t a, uint32_t b) {
  uint32_t r;
  asm("add.rn.bf16x2 %0, %1, %2;" : "=r"(r) : "r"(a), "r"(b));
  return r;
}
__device__ __forceinline__ uint32_t hfma2_bf16(uint32_t a, uint32_t b, uint32_t c) {
  uint32_t r;
  asm("fma.rn.bf16x2 %0, %1, %2, %3;" : "=r"(r) : "r"(a), "r"(b), "r"(c));
  return r;
}
__device__ __forceinline__ bool mbar_test(uint32_t b, uint32_t ph) {
  uint32_t done;
  asm volatile("{.reg .pred p; mbarrier.test_wait.parity.shared::cta.b64 p, [%1], %2; selp.u32 %0,1,0,p;}" : "=r"(done) : "r"(b), "r"(ph) : "memory");
  return __all_sync(0xffffffffu, done != 0);
}
__device__ __forceinline__ uint4 ldg128_cg(const void* p) {
  uint4 v;
  asm volatile("ld.global.cg.v4.u32 {%0,%1,%2,%3}, [%4];" : "=r"(v.x), "=r"(v.y), "=r"(v.z), "=r"(v.w) : "l"(p) : "memory");
  return v;
}
__device__ __forceinline__ float bf_lo(uint32_t w) { return __uint_as_float(w << 16); }
__device__ __forceinline__ float bf_hi(uint32_t w) { return __uint_as_float(w & 0xffff0000u); }
__device__ __forceinline__ float rbf(float x) { return __bfloat162float(__float2bfloat16_rn(x)); }
__device__ __forceinline__ float ex2f(float x) { float r; asm("ex2.approx.ftz.f32 %0, %1;" : "=f"(r) : "f"(x)); return r; }
__device__ __forceinline__ float rcpf(float x) { float r; asm("rcp.approx.ftz.f32 %0, %1;" : "=f"(r) : "f"(x)); return r; }
__device__ __forceinline__ float gelu_tanh(float x) {
  const float c1 = -2.0f * 0.7978845608028654f * 1.4426950408889634f;
  const float c2 = c1 * 0.044715f;
  const float e = ex2f(x * fmaf(c2, x * x, c1));
  return x * rcpf(1.0f + e);
}
__device__ __forceinline__ float silu_f(float x) {
  const float e = ex2f(-1.4426950408889634f * x);
  return x * rcpf(1.0f + e);
}

__device__ __forceinline__ void wgmma_n128_tb(float (&d)[64], uint32_t da, uint32_t db, int scale_d) {
  asm volatile(
    "{\n.reg .pred p;\n.reg .b64 da, db;\nsetp.ne.b32 p, %66, 0;\n"
    "mov.b64 da, {%64, 0x40000040};\nmov.b64 db, {%65, 0x40000040};\n"
    "wgmma.mma_async.sync.aligned.m64n128k16.f32.bf16.bf16 {%0, %1, %2, %3, %4, %5, %6, %7, %8, %9, %10, %11, %12, %13, %14, %15, %16, %17, %18, %19, %20, %21, %22, %23, %24, %25, %26, %27, %28, %29, %30, %31, %32, %33, %34, %35, %36, %37, %38, %39, %40, %41, %42, %43, %44, %45, %46, %47, %48, %49, %50, %51, %52, %53, %54, %55, %56, %57, %58, %59, %60, %61, %62, %63}, da, db, p, 1, 1, 0, 1;\n}\n"
    : "+f"(d[0]), "+f"(d[1]), "+f"(d[2]), "+f"(d[3]), "+f"(d[4]), "+f"(d[5]), "+f"(d[6]), "+f"(d[7]), "+f"(d[8]), "+f"(d[9]), "+f"(d[10]), "+f"(d[11]), "+f"(d[12]), "+f"(d[13]), "+f"(d[14]), "+f"(d[15]), "+f"(d[16]), "+f"(d[17]), "+f"(d[18]), "+f"(d[19]), "+f"(d[20]), "+f"(d[21]), "+f"(d[22]), "+f"(d[23]), "+f"(d[24]), "+f"(d[25]), "+f"(d[26]), "+f"(d[27]), "+f"(d[28]), "+f"(d[29]), "+f"(d[30]), "+f"(d[31]), "+f"(d[32]), "+f"(d[33]), "+f"(d[34]), "+f"(d[35]), "+f"(d[36]), "+f"(d[37]), "+f"(d[38]), "+f"(d[39]), "+f"(d[40]), "+f"(d[41]), "+f"(d[42]), "+f"(d[43]), "+f"(d[44]), "+f"(d[45]), "+f"(d[46]), "+f"(d[47]), "+f"(d[48]), "+f"(d[49]), "+f"(d[50]), "+f"(d[51]), "+f"(d[52]), "+f"(d[53]), "+f"(d[54]), "+f"(d[55]), "+f"(d[56]), "+f"(d[57]), "+f"(d[58]), "+f"(d[59]), "+f"(d[60]), "+f"(d[61]), "+f"(d[62]), "+f"(d[63])
    : "r"(da), "r"(db), "r"(scale_d));
}
__device__ __forceinline__ void wgmma_n128_tb_p(float (&d)[64], uint32_t da, uint32_t db, int scale_d, int enable) {
  asm volatile(
    "{\n.reg .pred p;\n.reg .b64 da, db;\nsetp.ne.b32 p, %66, 0;\n.reg .pred q;\nsetp.ne.b32 q, %67, 0;\n"
    "mov.b64 da, {%64, 0x40000040};\nmov.b64 db, {%65, 0x40000040};\n"
    "@q wgmma.mma_async.sync.aligned.m64n128k16.f32.bf16.bf16 {%0, %1, %2, %3, %4, %5, %6, %7, %8, %9, %10, %11, %12, %13, %14, %15, %16, %17, %18, %19, %20, %21, %22, %23, %24, %25, %26, %27, %28, %29, %30, %31, %32, %33, %34, %35, %36, %37, %38, %39, %40, %41, %42, %43, %44, %45, %46, %47, %48, %49, %50, %51, %52, %53, %54, %55, %56, %57, %58, %59, %60, %61, %62, %63}, da, db, p, 1, 1, 0, 1;\n}\n"
    : "+f"(d[0]), "+f"(d[1]), "+f"(d[2]), "+f"(d[3]), "+f"(d[4]), "+f"(d[5]), "+f"(d[6]), "+f"(d[7]), "+f"(d[8]), "+f"(d[9]), "+f"(d[10]), "+f"(d[11]), "+f"(d[12]), "+f"(d[13]), "+f"(d[14]), "+f"(d[15]), "+f"(d[16]), "+f"(d[17]), "+f"(d[18]), "+f"(d[19]), "+f"(d[20]), "+f"(d[21]), "+f"(d[22]), "+f"(d[23]), "+f"(d[24]), "+f"(d[25]), "+f"(d[26]), "+f"(d[27]), "+f"(d[28]), "+f"(d[29]), "+f"(d[30]), "+f"(d[31]), "+f"(d[32]), "+f"(d[33]), "+f"(d[34]), "+f"(d[35]), "+f"(d[36]), "+f"(d[37]), "+f"(d[38]), "+f"(d[39]), "+f"(d[40]), "+f"(d[41]), "+f"(d[42]), "+f"(d[43]), "+f"(d[44]), "+f"(d[45]), "+f"(d[46]), "+f"(d[47]), "+f"(d[48]), "+f"(d[49]), "+f"(d[50]), "+f"(d[51]), "+f"(d[52]), "+f"(d[53]), "+f"(d[54]), "+f"(d[55]), "+f"(d[56]), "+f"(d[57]), "+f"(d[58]), "+f"(d[59]), "+f"(d[60]), "+f"(d[61]), "+f"(d[62]), "+f"(d[63])
    : "r"(da), "r"(db), "r"(scale_d), "r"(enable));
}
__device__ __forceinline__ void wgmma_n112(float (&d)[56], uint32_t da, uint32_t db, int scale_d) {
  asm volatile(
    "{\n.reg .pred p;\n.reg .b64 da, db;\nsetp.ne.b32 p, %58, 0;\n"
    "mov.b64 da, {%56, 0x40000040};\nmov.b64 db, {%57, 0x40000040};\n"
    "wgmma.mma_async.sync.aligned.m64n112k16.f32.bf16.bf16 {%0, %1, %2, %3, %4, %5, %6, %7, %8, %9, %10, %11, %12, %13, %14, %15, %16, %17, %18, %19, %20, %21, %22, %23, %24, %25, %26, %27, %28, %29, %30, %31, %32, %33, %34, %35, %36, %37, %38, %39, %40, %41, %42, %43, %44, %45, %46, %47, %48, %49, %50, %51, %52, %53, %54, %55}, da, db, p, 1, 1, 0, 0;\n}\n"
    : "+f"(d[0]), "+f"(d[1]), "+f"(d[2]), "+f"(d[3]), "+f"(d[4]), "+f"(d[5]), "+f"(d[6]), "+f"(d[7]), "+f"(d[8]), "+f"(d[9]), "+f"(d[10]), "+f"(d[11]), "+f"(d[12]), "+f"(d[13]), "+f"(d[14]), "+f"(d[15]), "+f"(d[16]), "+f"(d[17]), "+f"(d[18]), "+f"(d[19]), "+f"(d[20]), "+f"(d[21]), "+f"(d[22]), "+f"(d[23]), "+f"(d[24]), "+f"(d[25]), "+f"(d[26]), "+f"(d[27]), "+f"(d[28]), "+f"(d[29]), "+f"(d[30]), "+f"(d[31]), "+f"(d[32]), "+f"(d[33]), "+f"(d[34]), "+f"(d[35]), "+f"(d[36]), "+f"(d[37]), "+f"(d[38]), "+f"(d[39]), "+f"(d[40]), "+f"(d[41]), "+f"(d[42]), "+f"(d[43]), "+f"(d[44]), "+f"(d[45]), "+f"(d[46]), "+f"(d[47]), "+f"(d[48]), "+f"(d[49]), "+f"(d[50]), "+f"(d[51]), "+f"(d[52]), "+f"(d[53]), "+f"(d[54]), "+f"(d[55])
    : "r"(da), "r"(db), "r"(scale_d));
}
__device__ __forceinline__ void wgmma_n224_tb(float (&d)[112], uint32_t da, uint32_t db, int scale_d) {
  asm volatile(
    "{\n.reg .pred p;\n.reg .b64 da, db;\nsetp.ne.b32 p, %114, 0;\n"
    "mov.b64 da, {%112, 0x40000040};\nmov.b64 db, {%113, 0x40000040};\n"
    "wgmma.mma_async.sync.aligned.m64n224k16.f32.bf16.bf16 {%0, %1, %2, %3, %4, %5, %6, %7, %8, %9, %10, %11, %12, %13, %14, %15, %16, %17, %18, %19, %20, %21, %22, %23, %24, %25, %26, %27, %28, %29, %30, %31, %32, %33, %34, %35, %36, %37, %38, %39, %40, %41, %42, %43, %44, %45, %46, %47, %48, %49, %50, %51, %52, %53, %54, %55, %56, %57, %58, %59, %60, %61, %62, %63, %64, %65, %66, %67, %68, %69, %70, %71, %72, %73, %74, %75, %76, %77, %78, %79, %80, %81, %82, %83, %84, %85, %86, %87, %88, %89, %90, %91, %92, %93, %94, %95, %96, %97, %98, %99, %100, %101, %102, %103, %104, %105, %106, %107, %108, %109, %110, %111}, da, db, p, 1, 1, 0, 1;\n}\n"
    : "+f"(d[0]), "+f"(d[1]), "+f"(d[2]), "+f"(d[3]), "+f"(d[4]), "+f"(d[5]), "+f"(d[6]), "+f"(d[7]), "+f"(d[8]), "+f"(d[9]), "+f"(d[10]), "+f"(d[11]), "+f"(d[12]), "+f"(d[13]), "+f"(d[14]), "+f"(d[15]), "+f"(d[16]), "+f"(d[17]), "+f"(d[18]), "+f"(d[19]), "+f"(d[20]), "+f"(d[21]), "+f"(d[22]), "+f"(d[23]), "+f"(d[24]), "+f"(d[25]), "+f"(d[26]), "+f"(d[27]), "+f"(d[28]), "+f"(d[29]), "+f"(d[30]), "+f"(d[31]), "+f"(d[32]), "+f"(d[33]), "+f"(d[34]), "+f"(d[35]), "+f"(d[36]), "+f"(d[37]), "+f"(d[38]), "+f"(d[39]), "+f"(d[40]), "+f"(d[41]), "+f"(d[42]), "+f"(d[43]), "+f"(d[44]), "+f"(d[45]), "+f"(d[46]), "+f"(d[47]), "+f"(d[48]), "+f"(d[49]), "+f"(d[50]), "+f"(d[51]), "+f"(d[52]), "+f"(d[53]), "+f"(d[54]), "+f"(d[55]), "+f"(d[56]), "+f"(d[57]), "+f"(d[58]), "+f"(d[59]), "+f"(d[60]), "+f"(d[61]), "+f"(d[62]), "+f"(d[63]), "+f"(d[64]), "+f"(d[65]), "+f"(d[66]), "+f"(d[67]), "+f"(d[68]), "+f"(d[69]), "+f"(d[70]), "+f"(d[71]), "+f"(d[72]), "+f"(d[73]), "+f"(d[74]), "+f"(d[75]), "+f"(d[76]), "+f"(d[77]), "+f"(d[78]), "+f"(d[79]), "+f"(d[80]), "+f"(d[81]), "+f"(d[82]), "+f"(d[83]), "+f"(d[84]), "+f"(d[85]), "+f"(d[86]), "+f"(d[87]), "+f"(d[88]), "+f"(d[89]), "+f"(d[90]), "+f"(d[91]), "+f"(d[92]), "+f"(d[93]), "+f"(d[94]), "+f"(d[95]), "+f"(d[96]), "+f"(d[97]), "+f"(d[98]), "+f"(d[99]), "+f"(d[100]), "+f"(d[101]), "+f"(d[102]), "+f"(d[103]), "+f"(d[104]), "+f"(d[105]), "+f"(d[106]), "+f"(d[107]), "+f"(d[108]), "+f"(d[109]), "+f"(d[110]), "+f"(d[111])
    : "r"(da), "r"(db), "r"(scale_d));
}

constexpr int K1_NS = 6;
constexpr int K1_A_BYTES = 7 * 16384;
constexpr int K1_B_OFF = K1_A_BYTES;
constexpr int K1_STG_OFF = K1_B_OFF + K1_NS * 16384;
constexpr int K1_BAR_OFF = K1_STG_OFF + 8 * 2048;
constexpr int K1_SMEM = K1_BAR_OFF + 256 + 1024;

struct K1Ctx {
  uint32_t sb, bar_full, rel0, rel1;
  uint32_t dA, dBk, dBn;
  bool lane0;
};
__device__ __forceinline__ void k1_release(const K1Ctx& c, int slot) {
  if (c.lane0) {
    asm volatile("mbarrier.arrive.shared::cluster.b64 _, [%0];" ::"r"(c.rel0 + 8 * slot) : "memory");
    asm volatile("mbarrier.arrive.shared::cluster.b64 _, [%0];" ::"r"(c.rel1 + 8 * slot) : "memory");
  }
}

__device__ __noinline__ void geglu_tile(uint32_t stg, __nv_bfloat16* gptr  , int lane) {
  const int row = lane >> 1;
  const uint32_t base = stg + row * 64;
  const int sw = (row >> 1) & 3;
  uint4 g[2], u[2];
#pragma unroll
  for (int i = 0; i < 2; i++) {
    const uint32_t a = base + ((((lane & 1) * 2 + i) ^ sw) * 16);
    g[i] = lds128(a); u[i] = lds128(a + 1024);
  }
#pragma unroll
  for (int i = 0; i < 2; i++) {
    uint4 o;
    o.x = hmul2_bf16(pack_bf16(gelu_tanh(bf_lo(g[i].x)), gelu_tanh(bf_hi(g[i].x))), u[i].x);
    o.y = hmul2_bf16(pack_bf16(gelu_tanh(bf_lo(g[i].y)), gelu_tanh(bf_hi(g[i].y))), u[i].y);
    o.z = hmul2_bf16(pack_bf16(gelu_tanh(bf_lo(g[i].z)), gelu_tanh(bf_hi(g[i].z))), u[i].z);
    o.w = hmul2_bf16(pack_bf16(gelu_tanh(bf_lo(g[i].w)), gelu_tanh(bf_hi(g[i].w))), u[i].w);
    stg128(gptr + i * 8, o);
  }
}

__device__ __forceinline__ void k1_unit_ab(const K1Ctx& c, int warp, int lane, int mt, int j) {
  const uint32_t stg = c.sb + K1_STG_OFF + warp * 2048;
  const int wq = warp & 3;
  const int st_row = (lane & 7) + 8 * ((lane >> 3) & 1);
  const int st_chunk = lane >> 4;
  float acc[2][56];
  int slot = 0; uint32_t ph = 0;
#pragma unroll 1
  for (int kb = 0; kb < 7; kb++) {
    const int pslot = (slot == 0) ? K1_NS - 1 : slot - 1;
    mbar_wait(c.bar_full + 8 * slot, ph, 3);
    if (kb == 6) named_arrive(2, 256);
    if (kb == 0 && (threadIdx.x & 127) == 0) DBG(0, 4);
    if ((threadIdx.x & 127) == 0) DBGC(1, 46 + kb);
    wg_fence();
    const uint32_t da = c.dA + kb * 1024;
    const uint32_t db = c.dBk + slot * 1024;
#pragma unroll
    for (int k = 0; k < 4; k++) {
      wgmma_n112(acc[0], da + k * 2, db + k * 2, (kb | k) != 0);
      wgmma_n112(acc[1], da + 512 + k * 2, db + k * 2, (kb | k) != 0);
    }
    wg_commit();
    if (kb > 0) { wg_wait<1>(); k1_release(c, pslot); }
    if (++slot == K1_NS) { slot = 0; ph ^= 1; }
  }
  wg_wait<0>();
  k1_release(c, 6 % K1_NS);
  if ((threadIdx.x & 127) == 0) DBG(0, 5);
  const uint32_t sgn = (j < 4) ? 0u : 0x80008000u;
  __nv_bfloat16* outp = g_ab + (size_t)((j < 4 ? 0 : 2048) + mt * 128 + wq * 16 + (lane >> 3)) * 448 + (j & 3) * 112 + (lane & 7) * 8;
  const uint32_t sa = stg + st_row * 128;
  const uint32_t la = stg + (lane >> 3) * 128;
#pragma unroll
  for (int h = 0; h < 2; h++) {
#pragma unroll
    for (int rnd = 0; rnd < 2; rnd++) {
#pragma unroll
      for (int g = 0; g < (rnd ? 6 : 8); g += 2) {
        const float* a = &acc[h][4 * (g + 8 * rnd)];
        stmatrix_x4(sa + (((g + st_chunk) ^ (st_row & 7)) * 16),
                    pack_bf16(a[0], a[1]) ^ sgn, pack_bf16(a[2], a[3]) ^ sgn, pack_bf16(a[4], a[5]) ^ sgn, pack_bf16(a[6], a[7]) ^ sgn);
      }
      __syncwarp();
      if (rnd == 0 || (lane & 7) < 6) {
#pragma unroll
        for (int t = 0; t < 4; t++) {
          const int r7 = (t * 4 + (lane >> 3)) & 7;
          stg128(outp + (h * 64 + t * 4) * 448 + rnd * 64, lds128(la + t * 512 + (((lane & 7) ^ r7) * 16)));
        }
      }
      __syncwarp();
    }
  }
}

__device__ __forceinline__ void k1_unit_gu(const K1Ctx& c, int warp, int lane, int mt, int unit, int fb, int hsel) {
  const uint32_t stg = c.sb + K1_STG_OFF + warp * 2048;
  const int wq = warp & 3;
  const int full = (unit < 4);
  float acc[2][64];
  const uint32_t dA0 = c.dA + (full ? 0 : hsel * 512);
  int slot = (unit * 7) % K1_NS; uint32_t ph = ((unit * 7) / K1_NS) & 1;
  named_bar(2 + ((unit - 1) & 1), 256);
  if (full) {
#pragma unroll 1
    for (int kb = 0; kb < 7; kb++) {
      const int pslot = (slot == 0) ? K1_NS - 1 : slot - 1;
      mbar_wait(c.bar_full + 8 * slot, ph, 4);
      if (kb == 6) named_arrive(2 + (unit & 1), 256);
      if (kb == 0 && (threadIdx.x & 127) == 0) DBG(0, 4 + 3 * unit);
      wg_fence();
      const uint32_t da = dA0 + kb * 1024;
      const uint32_t db = c.dBn + slot * 1024;
#pragma unroll
      for (int k = 0; k < 4; k++) {
        wgmma_n128_tb(acc[0], da + k * 2, db + k * 128, (kb | k) != 0);
        wgmma_n128_tb(acc[1], da + 512 + k * 2, db + k * 128, (kb | k) != 0);
      }
      wg_commit();
      if (kb > 0) { wg_wait<1>(); k1_release(c, pslot); }
      if (++slot == K1_NS) { slot = 0; ph ^= 1; }
    }
  } else {
#pragma unroll 1
    for (int kb = 0; kb < 7; kb++) {
      const int pslot = (slot == 0) ? K1_NS - 1 : slot - 1;
      mbar_wait(c.bar_full + 8 * slot, ph, 5);
      if (kb == 0 && (threadIdx.x & 127) == 0) DBG(0, 4 + 3 * unit);
      wg_fence();
      const uint32_t da = dA0 + kb * 1024;
      const uint32_t db = c.dBn + slot * 1024;
#pragma unroll
      for (int k = 0; k < 4; k++) wgmma_n128_tb(acc[0], da + k * 2, db + k * 128, (kb | k) != 0);
      wg_commit();
      if (kb > 0) { wg_wait<1>(); k1_release(c, pslot); }
      if (++slot == K1_NS) { slot = 0; ph ^= 1; }
    }
  }
  wg_wait<0>();
  k1_release(c, (slot == 0) ? K1_NS - 1 : slot - 1);
  if ((threadIdx.x & 127) == 0) DBG(0, 5 + 3 * unit);
  const int st_row = (lane & 7) + 8 * ((lane >> 3) & 1);
  const int st_chunk = lane >> 4;
  const uint32_t sa = stg + st_row * 64;
  const int sw = (st_row >> 1) & 3;
  __nv_bfloat16* outp = g_h + (size_t)(mt * 128 + (full ? 0 : hsel * 64) + wq * 16 + (lane >> 1)) * 1792 + fb * 64 + (lane & 1) * 16;
#pragma unroll
  for (int h = 0; h < 2; h++) {
    if (h == 1 && !full) break;
#pragma unroll
    for (int ch = 0; ch < 2; ch++) {
#pragma unroll
      for (int g = 0; g < 4; g += 2) {
        const float* a = &acc[h][4 * (4 * ch + g)];
        const float* u = a + 32;
        const uint32_t ad = sa + (((g + st_chunk) ^ sw) * 16);
        stmatrix_x4(ad, pack_bf16(a[0], a[1]), pack_bf16(a[2], a[3]), pack_bf16(a[4], a[5]), pack_bf16(a[6], a[7]));
        stmatrix_x4(ad + 1024, pack_bf16(u[0], u[1]), pack_bf16(u[2], u[3]), pack_bf16(u[4], u[5]), pack_bf16(u[6], u[7]));
      }
      __syncwarp();
      geglu_tile(stg, outp + (size_t)h * 64 * 1792 + ch * 32, lane);
      __syncwarp();
    }
  }
}

struct PfPtrs { const uint8_t* wr; const uint8_t* wi; const uint8_t* wg; const uint8_t* wu; const uint8_t* wd; const uint8_t* cr; const uint8_t* ci; };

__global__ void __cluster_dims__(2, 1, 1) __launch_bounds__(384, 1)
k1_kernel(const __grid_constant__ CUtensorMap tm_wr, const __grid_constant__ CUtensorMap tm_wi,
          const __grid_constant__ CUtensorMap tm_wg, const __grid_constant__ CUtensorMap tm_wu,
          const __nv_bfloat16* __restrict__ x, const PfPtrs pf) {
  extern __shared__ uint8_t smem_raw[];
  const uint32_t sb = (s2u(smem_raw) + 1023) & ~1023u;
  const int tid = threadIdx.x, warp = tid >> 5, lane = tid & 31;
  uint32_t rank;
  asm volatile("mov.u32 %0, %%cluster_ctarank;" : "=r"(rank));
  const int cid = blockIdx.x >> 1;
  const int p = cid >> 3, j = cid & 7;
  const int mt = 2 * p + (int)rank;
  const uint32_t bar_full = sb + K1_BAR_OFF;
  const uint32_t bar_empty = bar_full + 8 * K1_NS;
  const int fb_base = 7 * (j >> 1);
  const int fb0 = fb_base + ((j & 1) ? 4 : 0);
  const int fbh = fb_base + 3;
  const CUtensorMap* tw = (j < 4) ? &tm_wr : &tm_wi;
  const CUtensorMap* tgu = rank ? &tm_wu : &tm_wg;

  if (tid == 0) DBG(0, 0);
  if (tid == 256) {
    for (int i = 0; i < K1_NS; i++) { mbar_init(bar_full + 8 * i, 1); mbar_init(bar_empty + 8 * i, 8); }
    asm volatile("fence.mbarrier_init.release.cluster;" ::: "memory");
    prefetch_tmap(tw);
    prefetch_tmap(tgu);
    if (blockIdx.x < 64) g_flags[blockIdx.x] = 0;
  }
  __syncwarp();
  cluster_arrive_relaxed();
  pdl_launch();

  if (warp >= 8) {
    reg_dec<40>();
    cluster_wait();
    if (tid == 256) {
      int slot = 0; uint32_t ph = 0;
      int kb = 0, unit = 0;
#pragma unroll 1
      for (int s = 0; s < 35; s++) {
        if (s >= K1_NS) mbar_wait(bar_empty + 8 * slot, ph ^ 1, 2);
        DBG(0, 20 + s);
        const uint32_t dst = sb + K1_B_OFF + slot * 16384;
        if (unit == 0) {
          mbar_expect(bar_full + 8 * slot, 14336);
          tma2d_mc(dst + rank * 7168, tw, kb * 64, (j & 3) * 112 + rank * 56, bar_full + 8 * slot, 3);
        } else {
          const int fb = (unit == 4) ? fbh : (fb0 + unit - 1);
          mbar_expect(bar_full + 8 * slot, 16384);
          tma2d_mc(dst + rank * 8192, tgu, fb * 64, kb * 64, bar_full + 8 * slot, 3);
        }
        if (++kb == 7) { kb = 0; unit++; }
        if (++slot == K1_NS) { slot = 0; ph ^= 1; }
      }
    } else if (tid == 288) {
      const int b = blockIdx.x;
      l2_prefetch(pf.wg + b * 12544, 12544);
      l2_prefetch(pf.wu + b * 12544, 12544);
    }
  } else {
    reg_inc<232>();
    const int wg = warp >> 2;
    {
      const int c = lane & 7;
      const int r0 = warp * 16 + (lane >> 3);
      const uint4* src = reinterpret_cast<const uint4*>(x + (size_t)(mt * 128 + r0) * 448) + c;
      uint4 nx[7];
#pragma unroll
      for (int b = 0; b < 7; b++)
        asm volatile("ld.global.nc.v4.u32 {%0,%1,%2,%3}, [%4];" : "=r"(nx[b].x), "=r"(nx[b].y), "=r"(nx[b].z), "=r"(nx[b].w) : "l"(src + b * 8) : "memory");
#pragma unroll
      for (int pass = 1; pass < 4; pass++) asm volatile("prefetch.global.L2 [%0];" ::"l"(src + pass * 4 * 56 + c * 7 - c) : "memory");
#pragma unroll 1
      for (int pass = 0; pass < 4; pass++) {
        uint4 v[7];
#pragma unroll
        for (int b = 0; b < 7; b++) v[b] = nx[b];
        if (pass < 3) {
          const uint4* s2 = src + (pass + 1) * 4 * 56;
#pragma unroll
          for (int b = 0; b < 7; b++)
            asm volatile("ld.global.nc.v4.u32 {%0,%1,%2,%3}, [%4];" : "=r"(nx[b].x), "=r"(nx[b].y), "=r"(nx[b].z), "=r"(nx[b].w) : "l"(s2 + b * 8) : "memory");
        }
        float s0 = 0.f, s1 = 0.f, s2v = 0.f, s3 = 0.f;
#pragma unroll
        for (int b = 0; b < 7; b++) {
          s0 += bf_lo(v[b].x) + bf_hi(v[b].x); s1 += bf_lo(v[b].y) + bf_hi(v[b].y);
          s2v += bf_lo(v[b].z) + bf_hi(v[b].z); s3 += bf_lo(v[b].w) + bf_hi(v[b].w);
        }
        float m = (s0 + s1) + (s2v + s3);
        m += __shfl_xor_sync(0xffffffffu, m, 1);
        m += __shfl_xor_sync(0xffffffffu, m, 2);
        m += __shfl_xor_sync(0xffffffffu, m, 4);
        m *= (1.0f / 448.0f);
        float q0 = 0.f, q1 = 0.f, q2 = 0.f, q3 = 0.f;
#pragma unroll
        for (int b = 0; b < 7; b++) {
          float d;
          d = bf_lo(v[b].x) - m; q0 = fmaf(d, d, q0); d = bf_hi(v[b].x) - m; q1 = fmaf(d, d, q1);
          d = bf_lo(v[b].y) - m; q2 = fmaf(d, d, q2); d = bf_hi(v[b].y) - m; q3 = fmaf(d, d, q3);
          d = bf_lo(v[b].z) - m; q0 = fmaf(d, d, q0); d = bf_hi(v[b].z) - m; q1 = fmaf(d, d, q1);
          d = bf_lo(v[b].w) - m; q2 = fmaf(d, d, q2); d = bf_hi(v[b].w) - m; q3 = fmaf(d, d, q3);
        }
        float q = (q0 + q1) + (q2 + q3);
        q += __shfl_xor_sync(0xffffffffu, q, 1);
        q += __shfl_xor_sync(0xffffffffu, q, 2);
        q += __shfl_xor_sync(0xffffffffu, q, 4);
        const float var_b = rbf(q * (1.0f / 448.0f));
        const float den = rbf(sqrtf(rbf(var_b + 1e-5f)));
        const float ri = 1.0f / den;
        const float rih = rbf(ri);
        const uint32_t rhi2 = pack_bf16(rih, rih), rlo2 = pack_bf16(ri - rih, ri - rih);
        const uint32_t m2 = pack_bf16(m, m);
        const int r = r0 + pass * 4;
        const uint32_t a0 = sb + r * 128 + ((c ^ (r & 7)) * 16);
#pragma unroll
        for (int b = 0; b < 7; b++) {
          uint32_t w4[4] = {v[b].x, v[b].y, v[b].z, v[b].w};
#pragma unroll
          for (int qq = 0; qq < 4; qq++) {
            const uint32_t dw = hsub2_bf16(w4[qq], m2);
            w4[qq] = hfma2_bf16(dw, rhi2, hmul2_bf16(dw, rlo2));
          }
          sts128(a0 + b * 16384, make_uint4(w4[0], w4[1], w4[2], w4[3]));
        }
      }
    }
    if (lane == 0) DBG(0, 59 + (warp & 3));
    asm volatile("fence.proxy.async.shared::cta;" ::: "memory");
    named_bar(1, 256);
    cluster_wait();
    if (tid == 0) DBG(0, 3);

    K1Ctx c;
    c.sb = sb; c.bar_full = bar_full; c.lane0 = (lane == 0);
    asm volatile("mapa.shared::cluster.u32 %0, %1, %2;" : "=r"(c.rel0) : "r"(bar_empty), "r"(0));
    asm volatile("mapa.shared::cluster.u32 %0, %1, %2;" : "=r"(c.rel1) : "r"(bar_empty), "r"(1));
    c.dA = make_desc(sb, 16, 1024);
    c.dBk = make_desc(sb + K1_B_OFF, 16, 1024);
    c.dBn = make_desc(sb + K1_B_OFF, 8192, 1024);
    if (wg == 0) {
      k1_unit_ab(c, warp, lane, mt, j);
      if (tid == 0) DBG(0, 6);
    }
#pragma unroll 1
    for (int unit = 2 - wg; unit < 5; unit += 2) {
      k1_unit_gu(c, warp, lane, mt, unit, (unit == 4) ? fbh : fb0 + unit - 1, j & 1);
      if ((tid & 127) == 0) DBG(0, 6 + 3 * unit);
    }
  }
  __syncwarp();
  cluster_arrive_relaxed();
  cluster_wait();
}

constexpr int K2_NS = 4;
constexpr int K2_STAGE = 16384 + 32768;
constexpr int K2_BAR_OFF = K2_NS * K2_STAGE;
constexpr int K2_SMEM = K2_BAR_OFF + 256 + 1024;
constexpr int K2_PITCH = 464;

__device__ __forceinline__ void spin_flag(const unsigned int* flag, unsigned int target) {
  int it = 0;
  while (true) {
    unsigned int v;
    asm volatile("ld.acquire.gpu.global.u32 %0, [%1];" : "=r"(v) : "l"(flag) : "memory");
    if (v >= target) break;
    if (++it > SPIN_LIMIT) { TIMEOUT(20); break; }
  }
}

__global__ void __cluster_dims__(2, 1, 1) __launch_bounds__(384, 1)
k2_kernel(const __grid_constant__ CUtensorMap tm_cr, const __grid_constant__ CUtensorMap tm_ci, const __grid_constant__ CUtensorMap tm_h,
          const __grid_constant__ CUtensorMap tm_ab, const __grid_constant__ CUtensorMap tm_wd,
          const __nv_bfloat16* __restrict__ x, __nv_bfloat16* __restrict__ out) {
  extern __shared__ uint8_t smem_raw[];
  const uint32_t sb = (s2u(smem_raw) + 1023) & ~1023u;
  const int tid = threadIdx.x, warp = tid >> 5, lane = tid & 31;
  uint32_t rank;
  asm volatile("mov.u32 %0, %%cluster_ctarank;" : "=r"(rank));
  const int cid = blockIdx.x >> 1;
  const int q = cid & 3, n = (cid >> 2) & 1, p = cid >> 3;
  const int mt = 2 * p + (int)rank;
  const int tile = mt * 2 + n;
  const uint32_t bar_full = sb + K2_BAR_OFF;
  const uint32_t bar_empty = bar_full + 8 * K2_NS;
  const int g0 = (q == 0) ? 0 : (q == 1 ? 22 : (q == 2 ? 43 : 64));
  const int nkb = (q == 0) ? 22 : (q == 3 ? 28 : 21);

  if (tid == 0) DBG(1, 0);
  if (tid == 256) {
    for (int i = 0; i < K2_NS; i++) { mbar_init(bar_full + 8 * i, 1); mbar_init(bar_empty + 8 * i, 16); }
    asm volatile("fence.mbarrier_init.release.cluster;" ::: "memory");
    if (q == 3) { prefetch_tmap(&tm_h); prefetch_tmap(&tm_wd); }
    else { prefetch_tmap(&tm_cr); prefetch_tmap(&tm_ci); prefetch_tmap(&tm_ab); }
  }
  __syncwarp();
  cluster_arrive_relaxed();
  cluster_wait();

  if (warp >= 8) {
    reg_dec<40>();
    if (tid == 256) {
      const CUtensorMap* tb = (q < 3) ? &tm_ab : &tm_wd;
      const int kb0 = (q < 3) ? g0 : 0;
      int slot = 0; uint32_t ph = 0;
#pragma unroll 1
      for (int it = 0; it < nkb + K2_NS; it++) {
        const int s = (it < K2_NS) ? it : it - K2_NS;
        const bool pre = (it < K2_NS), post = (!pre && s < K2_NS);
        if (it == K2_NS) { pdl_wait(); DBG(1, 31); slot = 0; }
        if (!pre && !post) mbar_wait(bar_empty + 8 * slot, ph, 10);
        const uint32_t dst = sb + slot * K2_STAGE;
        const uint32_t fb = bar_full + 8 * slot;
        if (!post) mbar_expect(fb, K2_STAGE);
        const bool doA = pre ? (q < 3) : (post ? (q == 3) : true);
        const bool doB = pre ? (q == 3) : (post ? (q < 3) : true);
        if (doA) {
          const int g = g0 + s;
          const CUtensorMap* ta = (g < 32) ? &tm_cr : (g < 64 ? &tm_ci : &tm_h);
          tma2d(dst, ta, (g & 31) * 64 + ((g >= 96) ? 2048 : 0), mt * 128, fb);
        }
        if (doB) {
          tma3d_mc(dst + 16384 + (2 * rank) * 8192, tb, (2 * rank) * 64, n, (kb0 + s) * 64, fb, 3);
          tma3d_mc(dst + 16384 + (2 * rank + 1) * 8192, tb, (2 * rank + 1) * 64, n, (kb0 + s) * 64, fb, 3);
        }
        if (++slot == K2_NS) { slot = 0; if (!pre && !post) ph ^= 1; }
      }
    }
  } else {
    reg_inc<232>();
    const int wg = warp >> 2;
    float acc[112];
    uint32_t rel0, rel1;
    asm volatile("mapa.shared::cluster.u32 %0, %1, %2;" : "=r"(rel0) : "r"(bar_empty), "r"(0));
    asm volatile("mapa.shared::cluster.u32 %0, %1, %2;" : "=r"(rel1) : "r"(bar_empty), "r"(1));
    const uint32_t dA0 = make_desc(sb + wg * 8192, 16, 1024);
    const uint32_t dB0 = make_desc(sb + 16384, 8192, 1024);
    int slot = 0; uint32_t ph = 0;
#pragma unroll 1
    for (int s = 0; s < nkb; s++) {
      mbar_wait(bar_full + 8 * slot, ph, 11);
      if (tid == 0) DBG(1, 1 + s);
      if (tid == 0 && (s == 5 || s == 15)) DBGC(1, 53 + (s == 15));
      if (tid == 0 && (s == 23 || s == 27)) DBGC(1, 55 + (s == 27));
      wg_fence();
      const uint32_t da = dA0 + slot * (K2_STAGE / 16);
      const uint32_t db = dB0 + slot * (K2_STAGE / 16);
#pragma unroll
      for (int k = 0; k < 4; k++) wgmma_n224_tb(acc, da + k * 2, db + k * 128, (s | k) != 0);
      wg_commit();
      if (s > 0) {
        wg_wait<1>();
        const int ps = (slot == 0) ? K2_NS - 1 : slot - 1;
        if (lane == 0) {
          asm volatile("mbarrier.arrive.shared::cluster.b64 _, [%0];" ::"r"(rel0 + 8 * ps) : "memory");
          asm volatile("mbarrier.arrive.shared::cluster.b64 _, [%0];" ::"r"(rel1 + 8 * ps) : "memory");
        }
      }
      if (++slot == K2_NS) { slot = 0; ph ^= 1; }
    }
    wg_wait<0>();
    pdl_wait();
    if (tid == 0) DBG(1, 29);
    if (q < 3) {
      const int G0 = q * 10, NG = (q == 2) ? 8 : 10;
      uint2* part = g_part + (size_t)tile * (3 * 28 * 256) + tid;
      const uint32_t sl = sb + tid * 16;
      named_bar(1, 256);
#pragma unroll
      for (int g = 0; g < 28; g++) {
        if ((unsigned)(g - G0) < (unsigned)NG)
          sts128(sl + (g - G0) * 4096, make_uint4(__float_as_uint(acc[4 * g]), __float_as_uint(acc[4 * g + 1]), __float_as_uint(acc[4 * g + 2]), __float_as_uint(acc[4 * g + 3])));
        else
          part[(q * 28 + g) * 256] = make_uint2(pack_bf16(acc[4 * g], acc[4 * g + 1]), pack_bf16(acc[4 * g + 2], acc[4 * g + 3]));
      }
      __threadfence();
      named_bar(1, 256);
      if (tid == 0) { atomicAdd(&g_flags[tile], 1u); spin_flag(&g_flags[tile], 3u); }
      named_bar(1, 256);
      if (tid == 0) DBG(1, 30);
      const uint2* pa = part + (((q + 1) % 3) * 28 + G0) * 256;
      const uint2* pb = part + (((q + 2) % 3) * 28 + G0) * 256;
      const uint32_t s2 = sb + 49152 + tid * 16;
#pragma unroll 1
      for (int g = 0; g < NG; g++) {
        cp_async8(s2 + g * 4096, pa + g * 256);
        cp_async8(s2 + g * 4096 + 8, pb + g * 256);
      }
      cp_async_wait_all();
      uint32_t* sp = reinterpret_cast<uint32_t*>(g_s + (size_t)(mt * 128 + warp * 16 + (lane >> 2)) * 448 + n * 224 + (lane & 3) * 2) + G0 * 4;
#pragma unroll 2
      for (int g = 0; g < NG; g++) {
        const uint4 a = lds128(sl + g * 4096), b = lds128(s2 + g * 4096);
        sp[g * 4] = pack_bf16(__uint_as_float(a.x) + bf_lo(b.x) + bf_lo(b.z), __uint_as_float(a.y) + bf_hi(b.x) + bf_hi(b.z));
        sp[g * 4 + 8 * 224] = pack_bf16(__uint_as_float(a.z) + bf_lo(b.y) + bf_lo(b.w), __uint_as_float(a.w) + bf_hi(b.y) + bf_hi(b.w));
      }
      __threadfence();
      named_bar(1, 256);
      if (tid == 0) atomicAdd(&g_flags[32 + tile], 1u);
    } else {
      named_bar(1, 256);
      const uint32_t stg = sb + warp * 16 * K2_PITCH;
      const int st_row = (lane & 7) + 8 * ((lane >> 3) & 1);
      const uint32_t sa = stg + st_row * K2_PITCH + (lane >> 4) * 16;
#pragma unroll
      for (int g = 0; g < 28; g += 2) {
        const float* a = &acc[4 * g];
        stmatrix_x4(sa + g * 16, pack_bf16(a[0], a[1]), pack_bf16(a[2], a[3]), pack_bf16(a[4], a[5]), pack_bf16(a[6], a[7]));
      }
      const int lc = (lane < 28) ? lane : 27;
      const size_t gbase = (size_t)(mt * 128 + warp * 16) * 448 + n * 224 + lc * 8;
      const uint32_t lp = stg + lc * 16;
      const uint32_t xs = sb + 65536 + warp * 16384 + lane * 16;
#pragma unroll 1
      for (int t = 0; t < 16; t++) cp_async16(xs + t * 512, x + gbase + t * 448);
      __syncwarp();
#pragma unroll 2
      for (int t = 0; t < 16; t++) {
        const uint4 fv = lds128(lp + t * K2_PITCH);
        uint4 o;
        o.x = pack_bf16(silu_f(bf_lo(fv.x)), silu_f(bf_hi(fv.x)));
        o.y = pack_bf16(silu_f(bf_lo(fv.y)), silu_f(bf_hi(fv.y)));
        o.z = pack_bf16(silu_f(bf_lo(fv.z)), silu_f(bf_hi(fv.z)));
        o.w = pack_bf16(silu_f(bf_lo(fv.w)), silu_f(bf_hi(fv.w)));
        if (lane < 28) sts128(lp + t * K2_PITCH, o);
      }
      if (lane == 0) spin_flag(&g_flags[32 + tile], 3u);
      __syncwarp();
      if (tid == 0) DBG(1, 30);
#pragma unroll 1
      for (int t = 0; t < 16; t++) cp_async16(xs + 8192 + t * 512, g_s + gbase + t * 448);
      cp_async_wait_all();
#pragma unroll 4
      for (int t = 0; t < 16; t++) {
        const uint4 gv = lds128(lp + t * K2_PITCH), xx = lds128(xs + t * 512), ss = lds128(xs + 8192 + t * 512);
        uint4 o;
        o.x = hadd2_bf16(xx.x, hmul2_bf16(ss.x, gv.x));
        o.y = hadd2_bf16(xx.y, hmul2_bf16(ss.y, gv.y));
        o.z = hadd2_bf16(xx.z, hmul2_bf16(ss.z, gv.z));
        o.w = hadd2_bf16(xx.w, hmul2_bf16(ss.w, gv.w));
        if (lane < 28) stg128(out + gbase + t * 448, o);
      }
    }
    if (tid == 0) DBG(1, 63);
  }
  __syncwarp();
  cluster_arrive_relaxed();
  cluster_wait();
}

typedef CUresult (*EncFn)(CUtensorMap*, CUtensorMapDataType, cuuint32_t, void*, const cuuint64_t*, const cuuint64_t*, const cuuint32_t*,
                          const cuuint32_t*, CUtensorMapInterleave, CUtensorMapSwizzle, CUtensorMapL2promotion, CUtensorMapFloatOOBfill);

void make2d(EncFn enc, CUtensorMap* tm, const void* ptr, uint64_t cols, uint64_t rows, uint32_t bc, uint32_t br) {
  cuuint64_t gd[2] = {cols, rows};
  cuuint64_t gs[1] = {cols * 2};
  cuuint32_t bd[2] = {bc, br};
  cuuint32_t es[2] = {1, 1};
  enc(tm, CU_TENSOR_MAP_DATA_TYPE_BFLOAT16, 2, const_cast<void*>(ptr), gd, gs, bd, es, CU_TENSOR_MAP_INTERLEAVE_NONE,
      CU_TENSOR_MAP_SWIZZLE_128B, CU_TENSOR_MAP_L2_PROMOTION_L2_128B, CU_TENSOR_MAP_FLOAT_OOB_FILL_NONE);
}
void make3d_half(EncFn enc, CUtensorMap* tm, const void* ptr, uint64_t rows) {
  cuuint64_t gd[3] = {224, 2, rows};
  cuuint64_t gs[2] = {448, 896};
  cuuint32_t bd[3] = {64, 1, 64};
  cuuint32_t es[3] = {1, 1, 1};
  enc(tm, CU_TENSOR_MAP_DATA_TYPE_BFLOAT16, 3, const_cast<void*>(ptr), gd, gs, bd, es, CU_TENSOR_MAP_INTERLEAVE_NONE,
      CU_TENSOR_MAP_SWIZZLE_128B, CU_TENSOR_MAP_L2_PROMOTION_L2_128B, CU_TENSOR_MAP_FLOAT_OOB_FILL_NONE);
}

struct Maps { CUtensorMap wr, wi, wg, wu, cr, ci, h, ab, wd; };

}

extern "C" void kernel_launch(void* const* d_in, const int* in_sizes, int n_in, void* d_out, int out_size) {
  (void)in_sizes; (void)n_in; (void)out_size;
  static Maps maps;
  static const void* cached[9] = {nullptr};
  static bool attr_done = false;
  bool same = true;
  for (int i = 0; i < 9; i++) same = same && (cached[i] == d_in[i]);
  if (!same) {
    void* fn = nullptr;
    cudaDriverEntryPointQueryResult qr;
    cudaGetDriverEntryPoint("cuTensorMapEncodeTiled", &fn, cudaEnableDefault, &qr);
    EncFn enc = (EncFn)fn;
    void *p_ab = nullptr, *p_h = nullptr;
    cudaGetSymbolAddress(&p_ab, g_ab);
    cudaGetSymbolAddress(&p_h, g_h);
    make2d(enc, &maps.cr, d_in[1], 2048, 2048, 64, 128);
    make2d(enc, &maps.ci, d_in[2], 2048, 2048, 64, 128);
    make2d(enc, &maps.wr, d_in[3], 448, 448, 64, 56);
    make2d(enc, &maps.wi, d_in[4], 448, 448, 64, 56);
    make2d(enc, &maps.wg, d_in[6], 1792, 448, 64, 64);
    make2d(enc, &maps.wu, d_in[7], 1792, 448, 64, 64);
    make3d_half(enc, &maps.wd, d_in[8], 1792);
    make2d(enc, &maps.h, p_h, 1792, 2048, 64, 128);
    make3d_half(enc, &maps.ab, p_ab, 4096);
    for (int i = 0; i < 9; i++) cached[i] = d_in[i];
  }
  if (!attr_done) {
    cudaFuncSetAttribute(k1_kernel, cudaFuncAttributeMaxDynamicSharedMemorySize, K1_SMEM);
    cudaFuncSetAttribute(k2_kernel, cudaFuncAttributeMaxDynamicSharedMemorySize, K2_SMEM);
    attr_done = true;
  }
  PfPtrs pf;
  pf.wr = (const uint8_t*)d_in[3]; pf.wi = (const uint8_t*)d_in[4]; pf.wg = (const uint8_t*)d_in[6]; pf.wu = (const uint8_t*)d_in[7];
  pf.wd = (const uint8_t*)d_in[8]; pf.cr = (const uint8_t*)d_in[1]; pf.ci = (const uint8_t*)d_in[2];
  k1_kernel<<<128, 384, K1_SMEM>>>(maps.wr, maps.wi, maps.wg, maps.wu, (const __nv_bfloat16*)d_in[0], pf);

  cudaLaunchConfig_t cfg = {};
  cfg.gridDim = dim3(128); cfg.blockDim = dim3(384); cfg.dynamicSmemBytes = K2_SMEM; cfg.stream = cudaStreamPerThread;
  cudaLaunchAttribute at[1];
  at[0].id = cudaLaunchAttributeProgrammaticStreamSerialization;
  at[0].val.programmaticStreamSerializationAllowed = 1;
  cfg.attrs = at; cfg.numAttrs = 1;
  cudaLaunchKernelEx(&cfg, k2_kernel, maps.cr, maps.ci, maps.h, maps.ab, maps.wd, (const __nv_bfloat16*)d_in[0], (__nv_bfloat16*)d_out);
}
```

```cpp
#include <cuda_runtime.h>
#include <cuda_bf16.h>
#include <cuda.h>
#include <stdint.h>

namespace {

__device__ __align__(1024) __nv_bfloat16 g_ab[4096 * 448];
__device__ __align__(1024) __nv_bfloat16 g_h[2048 * 1792];
__device__ uint2 g_part[32 * 3 * 28 * 256];
__device__ __align__(1024) __nv_bfloat16 g_s[2048 * 448];
__device__ unsigned int g_epoch;
__device__ unsigned int g_ab_cnt;
__device__ unsigned int g_h_cnt[16];
__device__ unsigned int g_flags[64];

#define DBG(k, i) do {} while (0)
#define DBGC(k, i) do {} while (0)

#define TIMEOUT(code) __trap()
#define SPIN_LIMIT (1 << 22)
__device__ __forceinline__ uint32_t s2u(const void* p) { return (uint32_t)__cvta_generic_to_shared(p); }
__device__ __forceinline__ void mbar_init(uint32_t b, int c) { asm volatile("mbarrier.init.shared::cta.b64 [%0], %1;" ::"r"(b), "r"(c)); }
__device__ __forceinline__ void mbar_expect(uint32_t b, uint32_t bytes) {
  asm volatile("mbarrier.arrive.expect_tx.shared::cta.b64 _, [%0], %1;" ::"r"(b), "r"(bytes) : "memory");
}
__device__ __forceinline__ void mbar_wait(uint32_t b, uint32_t ph, int code = 1) {
  uint32_t done = 0;
  int it = 0;
  while (true) {
    asm volatile("{.reg .pred p; mbarrier.try_wait.parity.shared::cta.b64 p, [%1], %2; selp.u32 %0,1,0,p;}" : "=r"(done) : "r"(b), "r"(ph) : "memory");
    if (done) break;
    if (++it > SPIN_LIMIT) { TIMEOUT(code); break; }
  }
}
__device__ __forceinline__ void mbar_arrive_cluster(uint32_t b, uint32_t cta) {
  uint32_t r;
  asm volatile("mapa.shared::cluster.u32 %0, %1, %2;" : "=r"(r) : "r"(b), "r"(cta));
  asm volatile("mbarrier.arrive.shared::cluster.b64 _, [%0];" ::"r"(r) : "memory");
}
__device__ __forceinline__ void tma2d(uint32_t dst, const CUtensorMap* m, int c0, int c1, uint32_t bar) {
  asm volatile("cp.async.bulk.tensor.2d.shared::cluster.global.mbarrier::complete_tx::bytes [%0], [%1, {%3,%4}], [%2];" ::"r"(dst), "l"(m), "r"(bar), "r"(c0), "r"(c1) : "memory");
}
__device__ __forceinline__ void tma2d_mc(uint32_t dst, const CUtensorMap* m, int c0, int c1, uint32_t bar, uint16_t mask) {
  asm volatile("cp.async.bulk.tensor.2d.shared::cluster.global.mbarrier::complete_tx::bytes.multicast::cluster [%0], [%1, {%3,%4}], [%2], %5;" ::"r"(dst), "l"(m), "r"(bar), "r"(c0), "r"(c1), "h"(mask) : "memory");
}
__device__ __forceinline__ void tma3d_mc(uint32_t dst, const CUtensorMap* m, int c0, int c1, int c2, uint32_t bar, uint16_t mask) {
  asm volatile("cp.async.bulk.tensor.3d.shared::cluster.global.mbarrier::complete_tx::bytes.multicast::cluster [%0], [%1, {%3,%4,%5}], [%2], %6;" ::"r"(dst), "l"(m), "r"(bar), "r"(c0), "r"(c1), "r"(c2), "h"(mask) : "memory");
}
__device__ __forceinline__ void prefetch_tmap(const CUtensorMap* m) { asm volatile("prefetch.tensormap [%0];" ::"l"(m) : "memory"); }
__device__ __forceinline__ void l2_prefetch(const void* p, uint32_t bytes) {
  asm volatile("cp.async.bulk.prefetch.L2.global [%0], %1;" ::"l"(p), "r"(bytes) : "memory");
}
__device__ __forceinline__ void cluster_arrive_relaxed() { asm volatile("barrier.cluster.arrive.relaxed.aligned;" ::: "memory"); }
__device__ __forceinline__ void cluster_wait() { asm volatile("barrier.cluster.wait.aligned;" ::: "memory"); }
__device__ __forceinline__ void wg_fence() { __syncwarp(); asm volatile("wgmma.fence.sync.aligned;" ::: "memory"); }
__device__ __forceinline__ void wg_commit() { asm volatile("wgmma.commit_group.sync.aligned;" ::: "memory"); }
template <int N> __device__ __forceinline__ void wg_wait() { __syncwarp(); asm volatile("wgmma.wait_group.sync.aligned %0;" ::"n"(N) : "memory"); }
__device__ __forceinline__ void named_bar(int id, int n) { asm volatile("bar.sync %0, %1;" ::"r"(id), "r"(n) : "memory"); }
__device__ __forceinline__ void named_arrive(int id, int n) { asm volatile("bar.arrive %0, %1;" ::"r"(id), "r"(n) : "memory"); }
template <int N> __device__ __forceinline__ void reg_inc() { asm volatile("setmaxnreg.inc.sync.aligned.u32 %0;" ::"n"(N)); }
template <int N> __device__ __forceinline__ void reg_dec() { asm volatile("setmaxnreg.dec.sync.aligned.u32 %0;" ::"n"(N)); }
__device__ __forceinline__ void pdl_wait() { asm volatile("griddepcontrol.wait;" ::: "memory"); }
__device__ __forceinline__ void pdl_launch() { asm volatile("griddepcontrol.launch_dependents;" ::: "memory"); }

__device__ __forceinline__ uint32_t make_desc(uint32_t addr, uint32_t lbo, uint32_t  ) {
  return ((addr & 0x3FFFF) >> 4) | ((lbo >> 4) << 16);
}
__device__ __forceinline__ void stmatrix_x4(uint32_t addr, uint32_t r0, uint32_t r1, uint32_t r2, uint32_t r3) {
  asm volatile("stmatrix.sync.aligned.m8n8.x4.shared.b16 [%0], {%1,%2,%3,%4};" ::"r"(addr), "r"(r0), "r"(r1), "r"(r2), "r"(r3) : "memory");
}
__device__ __forceinline__ uint4 lds128(uint32_t a) {
  uint4 v;
  asm volatile("ld.shared.v4.u32 {%0,%1,%2,%3}, [%4];" : "=r"(v.x), "=r"(v.y), "=r"(v.z), "=r"(v.w) : "r"(a) : "memory");
  return v;
}
__device__ __forceinline__ void sts128(uint32_t a, uint4 v) {
  asm volatile("st.shared.v4.u32 [%0], {%1,%2,%3,%4};" ::"r"(a), "r"(v.x), "r"(v.y), "r"(v.z), "r"(v.w) : "memory");
}
__device__ __forceinline__ void stg128(void* p, uint4 v) {
  asm volatile("st.global.v4.u32 [%0], {%1,%2,%3,%4};" ::"l"(p), "r"(v.x), "r"(v.y), "r"(v.z), "r"(v.w) : "memory");
}
__device__ __forceinline__ void cp_async16(uint32_t dst, const void* src) {
  asm volatile("cp.async.cg.shared.global [%0], [%1], 16;" ::"r"(dst), "l"(src) : "memory");
}
__device__ __forceinline__ void cp_async8(uint32_t dst, const void* src) {
  asm volatile("cp.async.ca.shared.global [%0], [%1], 8;" ::"r"(dst), "l"(src) : "memory");
}
__device__ __forceinline__ uint2 lds64(uint32_t a) {
  uint2 v;
  asm volatile("ld.shared.v2.u32 {%0,%1}, [%2];" : "=r"(v.x), "=r"(v.y) : "r"(a) : "memory");
  return v;
}
__device__ __forceinline__ void cp_async_wait_all() { asm volatile("cp.async.wait_all;" ::: "memory"); }
__device__ __forceinline__ uint32_t pack_bf16(float lo, float hi) {
  uint32_t r;
  asm("cvt.rn.bf16x2.f32 %0, %1, %2;" : "=r"(r) : "f"(hi), "f"(lo));
  return r;
}
__device__ __forceinline__ uint32_t hmul2_bf16(uint32_t a, uint32_t b) {
  uint32_t r;
  asm("mul.rn.bf16x2 %0, %1, %2;" : "=r"(r) : "r"(a), "r"(b));
  return r;
}
__device__ __forceinline__ uint32_t hsub2_bf16(uint32_t a, uint32_t b) {
  uint32_t r;
  asm("sub.rn.bf16x2 %0, %1, %2;" : "=r"(r) : "r"(a), "r"(b));
  return r;
}
__device__ __forceinline__ uint32_t hadd2_bf16(uint32_t a, uint32_t b) {
  uint32_t r;
  asm("add.rn.bf16x2 %0, %1, %2;" : "=r"(r) : "r"(a), "r"(b));
  return r;
}
__device__ __forceinline__ uint32_t hfma2_bf16(uint32_t a, uint32_t b, uint32_t c) {
  uint32_t r;
  asm("fma.rn.bf16x2 %0, %1, %2, %3;" : "=r"(r) : "r"(a), "r"(b), "r"(c));
  return r;
}
__device__ __forceinline__ bool mbar_test(uint32_t b, uint32_t ph) {
  uint32_t done;
  asm volatile("{.reg .pred p; mbarrier.test_wait.parity.shared::cta.b64 p, [%1], %2; selp.u32 %0,1,0,p;}" : "=r"(done) : "r"(b), "r"(ph) : "memory");
  return __all_sync(0xffffffffu, done != 0);
}
__device__ __forceinline__ uint4 ldg128_cg(const void* p) {
  uint4 v;
  asm volatile("ld.global.cg.v4.u32 {%0,%1,%2,%3}, [%4];" : "=r"(v.x), "=r"(v.y), "=r"(v.z), "=r"(v.w) : "l"(p) : "memory");
  return v;
}
__device__ __forceinline__ float bf_lo(uint32_t w) { return __uint_as_float(w << 16); }
__device__ __forceinline__ float bf_hi(uint32_t w) { return __uint_as_float(w & 0xffff0000u); }
__device__ __forceinline__ float rbf(float x) { return __bfloat162float(__float2bfloat16_rn(x)); }
__device__ __forceinline__ float ex2f(float x) { float r; asm("ex2.approx.ftz.f32 %0, %1;" : "=f"(r) : "f"(x)); return r; }
__device__ __forceinline__ float rcpf(float x) { float r; asm("rcp.approx.ftz.f32 %0, %1;" : "=f"(r) : "f"(x)); return r; }
__device__ __forceinline__ float gelu_tanh(float x) {
  const float c1 = -2.0f * 0.7978845608028654f * 1.4426950408889634f;
  const float c2 = c1 * 0.044715f;
  const float e = ex2f(x * fmaf(c2, x * x, c1));
  return x * rcpf(1.0f + e);
}
__device__ __forceinline__ float silu_f(float x) {
  const float e = ex2f(-1.4426950408889634f * x);
  return x * rcpf(1.0f + e);
}

__device__ __forceinline__ void wgmma_n128_tb(float (&d)[64], uint32_t da, uint32_t db, int scale_d) {
  asm volatile(
    "{\n.reg .pred p;\n.reg .b64 da, db;\nsetp.ne.b32 p, %66, 0;\n"
    "mov.b64 da, {%64, 0x40000040};\nmov.b64 db, {%65, 0x40000040};\n"
    "wgmma.mma_async.sync.aligned.m64n128k16.f32.bf16.bf16 {%0, %1, %2, %3, %4, %5, %6, %7, %8, %9, %10, %11, %12, %13, %14, %15, %16, %17, %18, %19, %20, %21, %22, %23, %24, %25, %26, %27, %28, %29, %30, %31, %32, %33, %34, %35, %36, %37, %38, %39, %40, %41, %42, %43, %44, %45, %46, %47, %48, %49, %50, %51, %52, %53, %54, %55, %56, %57, %58, %59, %60, %61, %62, %63}, da, db, p, 1, 1, 0, 1;\n}\n"
    : "+f"(d[0]), "+f"(d[1]), "+f"(d[2]), "+f"(d[3]), "+f"(d[4]), "+f"(d[5]), "+f"(d[6]), "+f"(d[7]), "+f"(d[8]), "+f"(d[9]), "+f"(d[10]), "+f"(d[11]), "+f"(d[12]), "+f"(d[13]), "+f"(d[14]), "+f"(d[15]), "+f"(d[16]), "+f"(d[17]), "+f"(d[18]), "+f"(d[19]), "+f"(d[20]), "+f"(d[21]), "+f"(d[22]), "+f"(d[23]), "+f"(d[24]), "+f"(d[25]), "+f"(d[26]), "+f"(d[27]), "+f"(d[28]), "+f"(d[29]), "+f"(d[30]), "+f"(d[31]), "+f"(d[32]), "+f"(d[33]), "+f"(d[34]), "+f"(d[35]), "+f"(d[36]), "+f"(d[37]), "+f"(d[38]), "+f"(d[39]), "+f"(d[40]), "+f"(d[41]), "+f"(d[42]), "+f"(d[43]), "+f"(d[44]), "+f"(d[45]), "+f"(d[46]), "+f"(d[47]), "+f"(d[48]), "+f"(d[49]), "+f"(d[50]), "+f"(d[51]), "+f"(d[52]), "+f"(d[53]), "+f"(d[54]), "+f"(d[55]), "+f"(d[56]), "+f"(d[57]), "+f"(d[58]), "+f"(d[59]), "+f"(d[60]), "+f"(d[61]), "+f"(d[62]), "+f"(d[63])
    : "r"(da), "r"(db), "r"(scale_d));
}
__device__ __forceinline__ void wgmma_n128_tb_p(float (&d)[64], uint32_t da, uint32_t db, int scale_d, int enable) {
  asm volatile(
    "{\n.reg .pred p;\n.reg .b64 da, db;\nsetp.ne.b32 p, %66, 0;\n.reg .pred q;\nsetp.ne.b32 q, %67, 0;\n"
    "mov.b64 da, {%64, 0x40000040};\nmov.b64 db, {%65, 0x40000040};\n"
    "@q wgmma.mma_async.sync.aligned.m64n128k16.f32.bf16.bf16 {%0, %1, %2, %3, %4, %5, %6, %7, %8, %9, %10, %11, %12, %13, %14, %15, %16, %17, %18, %19, %20, %21, %22, %23, %24, %25, %26, %27, %28, %29, %30, %31, %32, %33, %34, %35, %36, %37, %38, %39, %40, %41, %42, %43, %44, %45, %46, %47, %48, %49, %50, %51, %52, %53, %54, %55, %56, %57, %58, %59, %60, %61, %62, %63}, da, db, p, 1, 1, 0, 1;\n}\n"
    : "+f"(d[0]), "+f"(d[1]), "+f"(d[2]), "+f"(d[3]), "+f"(d[4]), "+f"(d[5]), "+f"(d[6]), "+f"(d[7]), "+f"(d[8]), "+f"(d[9]), "+f"(d[10]), "+f"(d[11]), "+f"(d[12]), "+f"(d[13]), "+f"(d[14]), "+f"(d[15]), "+f"(d[16]), "+f"(d[17]), "+f"(d[18]), "+f"(d[19]), "+f"(d[20]), "+f"(d[21]), "+f"(d[22]), "+f"(d[23]), "+f"(d[24]), "+f"(d[25]), "+f"(d[26]), "+f"(d[27]), "+f"(d[28]), "+f"(d[29]), "+f"(d[30]), "+f"(d[31]), "+f"(d[32]), "+f"(d[33]), "+f"(d[34]), "+f"(d[35]), "+f"(d[36]), "+f"(d[37]), "+f"(d[38]), "+f"(d[39]), "+f"(d[40]), "+f"(d[41]), "+f"(d[42]), "+f"(d[43]), "+f"(d[44]), "+f"(d[45]), "+f"(d[46]), "+f"(d[47]), "+f"(d[48]), "+f"(d[49]), "+f"(d[50]), "+f"(d[51]), "+f"(d[52]), "+f"(d[53]), "+f"(d[54]), "+f"(d[55]), "+f"(d[56]), "+f"(d[57]), "+f"(d[58]), "+f"(d[59]), "+f"(d[60]), "+f"(d[61]), "+f"(d[62]), "+f"(d[63])
    : "r"(da), "r"(db), "r"(scale_d), "r"(enable));
}
__device__ __forceinline__ void wgmma_n112(float (&d)[56], uint32_t da, uint32_t db, int scale_d) {
  asm volatile(
    "{\n.reg .pred p;\n.reg .b64 da, db;\nsetp.ne.b32 p, %58, 0;\n"
    "mov.b64 da, {%56, 0x40000040};\nmov.b64 db, {%57, 0x40000040};\n"
    "wgmma.mma_async.sync.aligned.m64n112k16.f32.bf16.bf16 {%0, %1, %2, %3, %4, %5, %6, %7, %8, %9, %10, %11, %12, %13, %14, %15, %16, %17, %18, %19, %20, %21, %22, %23, %24, %25, %26, %27, %28, %29, %30, %31, %32, %33, %34, %35, %36, %37, %38, %39, %40, %41, %42, %43, %44, %45, %46, %47, %48, %49, %50, %51, %52, %53, %54, %55}, da, db, p, 1, 1, 0, 0;\n}\n"
    : "+f"(d[0]), "+f"(d[1]), "+f"(d[2]), "+f"(d[3]), "+f"(d[4]), "+f"(d[5]), "+f"(d[6]), "+f"(d[7]), "+f"(d[8]), "+f"(d[9]), "+f"(d[10]), "+f"(d[11]), "+f"(d[12]), "+f"(d[13]), "+f"(d[14]), "+f"(d[15]), "+f"(d[16]), "+f"(d[17]), "+f"(d[18]), "+f"(d[19]), "+f"(d[20]), "+f"(d[21]), "+f"(d[22]), "+f"(d[23]), "+f"(d[24]), "+f"(d[25]), "+f"(d[26]), "+f"(d[27]), "+f"(d[28]), "+f"(d[29]), "+f"(d[30]), "+f"(d[31]), "+f"(d[32]), "+f"(d[33]), "+f"(d[34]), "+f"(d[35]), "+f"(d[36]), "+f"(d[37]), "+f"(d[38]), "+f"(d[39]), "+f"(d[40]), "+f"(d[41]), "+f"(d[42]), "+f"(d[43]), "+f"(d[44]), "+f"(d[45]), "+f"(d[46]), "+f"(d[47]), "+f"(d[48]), "+f"(d[49]), "+f"(d[50]), "+f"(d[51]), "+f"(d[52]), "+f"(d[53]), "+f"(d[54]), "+f"(d[55])
    : "r"(da), "r"(db), "r"(scale_d));
}
__device__ __forceinline__ void wgmma_n224_tb(float (&d)[112], uint32_t da, uint32_t db, int scale_d) {
  asm volatile(
    "{\n.reg .pred p;\n.reg .b64 da, db;\nsetp.ne.b32 p, %114, 0;\n"
    "mov.b64 da, {%112, 0x40000040};\nmov.b64 db, {%113, 0x40000040};\n"
    "wgmma.mma_async.sync.aligned.m64n224k16.f32.bf16.bf16 {%0, %1, %2, %3, %4, %5, %6, %7, %8, %9, %10, %11, %12, %13, %14, %15, %16, %17, %18, %19, %20, %21, %22, %23, %24, %25, %26, %27, %28, %29, %30, %31, %32, %33, %34, %35, %36, %37, %38, %39, %40, %41, %42, %43, %44, %45, %46, %47, %48, %49, %50, %51, %52, %53, %54, %55, %56, %57, %58, %59, %60, %61, %62, %63, %64, %65, %66, %67, %68, %69, %70, %71, %72, %73, %74, %75, %76, %77, %78, %79, %80, %81, %82, %83, %84, %85, %86, %87, %88, %89, %90, %91, %92, %93, %94, %95, %96, %97, %98, %99, %100, %101, %102, %103, %104, %105, %106, %107, %108, %109, %110, %111}, da, db, p, 1, 1, 0, 1;\n}\n"
    : "+f"(d[0]), "+f"(d[1]), "+f"(d[2]), "+f"(d[3]), "+f"(d[4]), "+f"(d[5]), "+f"(d[6]), "+f"(d[7]), "+f"(d[8]), "+f"(d[9]), "+f"(d[10]), "+f"(d[11]), "+f"(d[12]), "+f"(d[13]), "+f"(d[14]), "+f"(d[15]), "+f"(d[16]), "+f"(d[17]), "+f"(d[18]), "+f"(d[19]), "+f"(d[20]), "+f"(d[21]), "+f"(d[22]), "+f"(d[23]), "+f"(d[24]), "+f"(d[25]), "+f"(d[26]), "+f"(d[27]), "+f"(d[28]), "+f"(d[29]), "+f"(d[30]), "+f"(d[31]), "+f"(d[32]), "+f"(d[33]), "+f"(d[34]), "+f"(d[35]), "+f"(d[36]), "+f"(d[37]), "+f"(d[38]), "+f"(d[39]), "+f"(d[40]), "+f"(d[41]), "+f"(d[42]), "+f"(d[43]), "+f"(d[44]), "+f"(d[45]), "+f"(d[46]), "+f"(d[47]), "+f"(d[48]), "+f"(d[49]), "+f"(d[50]), "+f"(d[51]), "+f"(d[52]), "+f"(d[53]), "+f"(d[54]), "+f"(d[55]), "+f"(d[56]), "+f"(d[57]), "+f"(d[58]), "+f"(d[59]), "+f"(d[60]), "+f"(d[61]), "+f"(d[62]), "+f"(d[63]), "+f"(d[64]), "+f"(d[65]), "+f"(d[66]), "+f"(d[67]), "+f"(d[68]), "+f"(d[69]), "+f"(d[70]), "+f"(d[71]), "+f"(d[72]), "+f"(d[73]), "+f"(d[74]), "+f"(d[75]), "+f"(d[76]), "+f"(d[77]), "+f"(d[78]), "+f"(d[79]), "+f"(d[80]), "+f"(d[81]), "+f"(d[82]), "+f"(d[83]), "+f"(d[84]), "+f"(d[85]), "+f"(d[86]), "+f"(d[87]), "+f"(d[88]), "+f"(d[89]), "+f"(d[90]), "+f"(d[91]), "+f"(d[92]), "+f"(d[93]), "+f"(d[94]), "+f"(d[95]), "+f"(d[96]), "+f"(d[97]), "+f"(d[98]), "+f"(d[99]), "+f"(d[100]), "+f"(d[101]), "+f"(d[102]), "+f"(d[103]), "+f"(d[104]), "+f"(d[105]), "+f"(d[106]), "+f"(d[107]), "+f"(d[108]), "+f"(d[109]), "+f"(d[110]), "+f"(d[111])
    : "r"(da), "r"(db), "r"(scale_d));
}

constexpr int K1_NS = 6;
constexpr int K1_A_BYTES = 7 * 16384;
constexpr int K1_B_OFF = K1_A_BYTES;
constexpr int K1_STG_OFF = K1_B_OFF + K1_NS * 16384;
constexpr int K1_BAR_OFF = K1_STG_OFF + 8 * 2048;
constexpr int K1_SMEM = K1_BAR_OFF + 256 + 1024;

struct K1Ctx {
  uint32_t sb, bar_full, rel0, rel1, rel2a, rel2b;
  uint32_t dA, dBk, dBn;
  bool lane0;
};
__device__ __forceinline__ void k1_release(const K1Ctx& c, int slot) {
  if (c.lane0) {
    asm volatile("mbarrier.arrive.shared::cluster.b64 _, [%0];" ::"r"(c.rel0 + 8 * slot) : "memory");
    asm volatile("mbarrier.arrive.shared::cluster.b64 _, [%0];" ::"r"(c.rel1 + 8 * slot) : "memory");
  }
}

__device__ __noinline__ void geglu_tile(uint32_t stg, __nv_bfloat16* gptr  , int lane) {
  const int row = lane >> 1;
  const uint32_t base = stg + row * 64;
  const int sw = (row >> 1) & 3;
  uint4 g[2], u[2];
#pragma unroll
  for (int i = 0; i < 2; i++) {
    const uint32_t a = base + ((((lane & 1) * 2 + i) ^ sw) * 16);
    g[i] = lds128(a); u[i] = lds128(a + 1024);
  }
#pragma unroll
  for (int i = 0; i < 2; i++) {
    uint4 o;
    o.x = hmul2_bf16(pack_bf16(gelu_tanh(bf_lo(g[i].x)), gelu_tanh(bf_hi(g[i].x))), u[i].x);
    o.y = hmul2_bf16(pack_bf16(gelu_tanh(bf_lo(g[i].y)), gelu_tanh(bf_hi(g[i].y))), u[i].y);
    o.z = hmul2_bf16(pack_bf16(gelu_tanh(bf_lo(g[i].z)), gelu_tanh(bf_hi(g[i].z))), u[i].z);
    o.w = hmul2_bf16(pack_bf16(gelu_tanh(bf_lo(g[i].w)), gelu_tanh(bf_hi(g[i].w))), u[i].w);
    stg128(gptr + i * 8, o);
  }
}

__device__ __forceinline__ void k1_unit_ab(const K1Ctx& c, int warp, int lane, int mt, int j) {
  const uint32_t stg = c.sb + K1_STG_OFF + warp * 2048;
  const int wq = warp & 3;
  const int st_row = (lane & 7) + 8 * ((lane >> 3) & 1);
  const int st_chunk = lane >> 4;
  float acc[2][56];
  int slot = 0; uint32_t ph = 0;
#pragma unroll 1
  for (int kb = 0; kb < 7; kb++) {
    const int pslot = (slot == 0) ? K1_NS - 1 : slot - 1;
    mbar_wait(c.bar_full + 8 * slot, ph, 3);
    if (kb == 6) named_arrive(2, 256);
    if (kb == 0 && (threadIdx.x & 127) == 0) DBG(0, 4);
    if ((threadIdx.x & 127) == 0) DBGC(1, 46 + kb);
    wg_fence();
    const uint32_t da = c.dA + kb * 1024;
    const uint32_t db = c.dBk + slot * 1024;
#pragma unroll
    for (int k = 0; k < 4; k++) {
      wgmma_n112(acc[0], da + k * 2, db + k * 2, (kb | k) != 0);
      wgmma_n112(acc[1], da + 512 + k * 2, db + k * 2, (kb | k) != 0);
    }
    wg_commit();
    if (kb > 0) { wg_wait<1>(); k1_release(c, pslot); }
    if (++slot == K1_NS) { slot = 0; ph ^= 1; }
  }
  wg_wait<0>();
  k1_release(c, 6 % K1_NS);
  if ((threadIdx.x & 127) == 0) DBG(0, 5);
  const uint32_t sgn = (j < 4) ? 0u : 0x80008000u;
  __nv_bfloat16* outp = g_ab + (size_t)((j < 4 ? 0 : 2048) + mt * 128 + wq * 16 + (lane >> 3)) * 448 + (j & 3) * 112 + (lane & 7) * 8;
  const uint32_t sa = stg + st_row * 128;
  const uint32_t la = stg + (lane >> 3) * 128;
#pragma unroll
  for (int h = 0; h < 2; h++) {
#pragma unroll
    for (int rnd = 0; rnd < 2; rnd++) {
#pragma unroll
      for (int g = 0; g < (rnd ? 6 : 8); g += 2) {
        const float* a = &acc[h][4 * (g + 8 * rnd)];
        stmatrix_x4(sa + (((g + st_chunk) ^ (st_row & 7)) * 16),
                    pack_bf16(a[0], a[1]) ^ sgn, pack_bf16(a[2], a[3]) ^ sgn, pack_bf16(a[4], a[5]) ^ sgn, pack_bf16(a[6], a[7]) ^ sgn);
      }
      __syncwarp();
      if (rnd == 0 || (lane & 7) < 6) {
#pragma unroll
        for (int t = 0; t < 4; t++) {
          const int r7 = (t * 4 + (lane >> 3)) & 7;
          stg128(outp + (h * 64 + t * 4) * 448 + rnd * 64, lds128(la + t * 512 + (((lane & 7) ^ r7) * 16)));
        }
      }
      __syncwarp();
    }
  }
}

__device__ __forceinline__ void k1_unit_gu(const K1Ctx& c, int warp, int lane, int mt, int unit, int fb, int hsel) {
  const uint32_t stg = c.sb + K1_STG_OFF + warp * 2048;
  const int wq = warp & 3;
  const int full = (unit < 4);
  float acc[2][64];
  const uint32_t dA0 = c.dA + (full ? 0 : hsel * 512);
  int slot = (unit * 7) % K1_NS; uint32_t ph = ((unit * 7) / K1_NS) & 1;
  named_bar(2 + ((unit - 1) & 1), 256);
  if (full) {
#pragma unroll 1
    for (int kb = 0; kb < 7; kb++) {
      const int pslot = (slot == 0) ? K1_NS - 1 : slot - 1;
      mbar_wait(c.bar_full + 8 * slot, ph, 4);
      if (kb == 6) named_arrive(2 + (unit & 1), 256);
      if (kb == 0 && (threadIdx.x & 127) == 0) DBG(0, 4 + 3 * unit);
      wg_fence();
      const uint32_t da = dA0 + kb * 1024;
      const uint32_t db = c.dBn + slot * 1024;
#pragma unroll
      for (int k = 0; k < 4; k++) {
        wgmma_n128_tb(acc[0], da + k * 2, db + k * 128, (kb | k) != 0);
        wgmma_n128_tb(acc[1], da + 512 + k * 2, db + k * 128, (kb | k) != 0);
      }
      wg_commit();
      if (kb > 0) { wg_wait<1>(); k1_release(c, pslot); }
      if (++slot == K1_NS) { slot = 0; ph ^= 1; }
    }
  } else {
#pragma unroll 1
    for (int kb = 0; kb < 7; kb++) {
      const int pslot = (slot == 0) ? K1_NS - 1 : slot - 1;
      mbar_wait(c.bar_full + 8 * slot, ph, 5);
      if (kb == 0 && (threadIdx.x & 127) == 0) DBG(0, 4 + 3 * unit);
      wg_fence();
      const uint32_t da = dA0 + kb * 1024;
      const uint32_t db = c.dBn + slot * 1024;
#pragma unroll
      for (int k = 0; k < 4; k++) wgmma_n128_tb(acc[0], da + k * 2, db + k * 128, (kb | k) != 0);
      wg_commit();
      if (kb > 0) { wg_wait<1>(); k1_release(c, pslot); }
      if (++slot == K1_NS) { slot = 0; ph ^= 1; }
    }
  }
  wg_wait<0>();
  k1_release(c, (slot == 0) ? K1_NS - 1 : slot - 1);
  if (unit >= 3 && lane < 4) {
    asm volatile("mbarrier.arrive.shared::cluster.b64 _, [%0];" ::"r"(c.rel2a + 8 * lane) : "memory");
    asm volatile("mbarrier.arrive.shared::cluster.b64 _, [%0];" ::"r"(c.rel2b + 8 * lane) : "memory");
  }
  if ((threadIdx.x & 127) == 0) DBG(0, 5 + 3 * unit);
  const int st_row = (lane & 7) + 8 * ((lane >> 3) & 1);
  const int st_chunk = lane >> 4;
  const uint32_t sa = stg + st_row * 64;
  const int sw = (st_row >> 1) & 3;
  __nv_bfloat16* outp = g_h + (size_t)(mt * 128 + (full ? 0 : hsel * 64) + wq * 16 + (lane >> 1)) * 1792 + fb * 64 + (lane & 1) * 16;
#pragma unroll
  for (int h = 0; h < 2; h++) {
    if (h == 1 && !full) break;
#pragma unroll
    for (int ch = 0; ch < 2; ch++) {
#pragma unroll
      for (int g = 0; g < 4; g += 2) {
        const float* a = &acc[h][4 * (4 * ch + g)];
        const float* u = a + 32;
        const uint32_t ad = sa + (((g + st_chunk) ^ sw) * 16);
        stmatrix_x4(ad, pack_bf16(a[0], a[1]), pack_bf16(a[2], a[3]), pack_bf16(a[4], a[5]), pack_bf16(a[6], a[7]));
        stmatrix_x4(ad + 1024, pack_bf16(u[0], u[1]), pack_bf16(u[2], u[3]), pack_bf16(u[4], u[5]), pack_bf16(u[6], u[7]));
      }
      __syncwarp();
      geglu_tile(stg, outp + (size_t)h * 64 * 1792 + ch * 32, lane);
      __syncwarp();
    }
  }
}

constexpr int K2_NS = 4;
constexpr int K2_STAGE = 16384 + 32768;
constexpr int K2_PITCH = 464;

__device__ __forceinline__ void spin_flag(const unsigned int* flag, unsigned int target) {
  int it = 0;
  while (true) {
    unsigned int v;
    asm volatile("ld.acquire.gpu.global.u32 %0, [%1];" : "=r"(v) : "l"(flag) : "memory");
    if ((int)(v - target) >= 0) break;
    if (++it > SPIN_LIMIT) { TIMEOUT(20); break; }
  }
}

struct PfPtrs { const uint8_t* wg; const uint8_t* wu; };

__device__ __forceinline__ void fence_proxy_async_all() { asm volatile("fence.proxy.async;" ::: "memory"); }

__global__ void __cluster_dims__(2, 1, 1) __launch_bounds__(384, 1)
fused_kernel(const __grid_constant__ CUtensorMap tm_wr, const __grid_constant__ CUtensorMap tm_wi,
             const __grid_constant__ CUtensorMap tm_wg, const __grid_constant__ CUtensorMap tm_wu,
             const __grid_constant__ CUtensorMap tm_cr, const __grid_constant__ CUtensorMap tm_ci, const __grid_constant__ CUtensorMap tm_h,
             const __grid_constant__ CUtensorMap tm_ab, const __grid_constant__ CUtensorMap tm_wd,
             const __nv_bfloat16* __restrict__ x, __nv_bfloat16* __restrict__ out, const PfPtrs pf) {
  extern __shared__ uint8_t smem_raw[];
  const uint32_t sb = (s2u(smem_raw) + 1023) & ~1023u;
  const int tid = threadIdx.x, warp = tid >> 5, lane = tid & 31;
  uint32_t rank;
  asm volatile("mov.u32 %0, %%cluster_ctarank;" : "=r"(rank));
  const int cid = blockIdx.x >> 1;
  const int p = cid >> 3, j = cid & 7;
  const int mt = 2 * p + (int)rank;
  const uint32_t bar_full = sb + K1_BAR_OFF;
  const uint32_t bar_empty = bar_full + 8 * K1_NS;
  const uint32_t bar_full2 = bar_empty + 8 * K1_NS;
  const uint32_t bar_empty2 = bar_full2 + 8 * K2_NS;
  const int fb_base = 7 * (j >> 1);
  const int fb0 = fb_base + ((j & 1) ? 4 : 0);
  const int fbh = fb_base + 3;
  const int q = j & 3, n = j >> 2;
  const int tile = mt * 2 + n;
  const int g0 = (q == 0) ? 0 : (q == 1 ? 22 : (q == 2 ? 43 : 64));
  const int nkb = (q == 0) ? 22 : (q == 3 ? 28 : 21);
  const unsigned int epoch = *reinterpret_cast<volatile unsigned int*>(&g_epoch);

  if (tid == 0) DBG(0, 0);
  if (tid == 256) {
    for (int i = 0; i < K1_NS; i++) { mbar_init(bar_full + 8 * i, 1); mbar_init(bar_empty + 8 * i, 8); }
    for (int i = 0; i < K2_NS; i++) { mbar_init(bar_full2 + 8 * i, 1); mbar_init(bar_empty2 + 8 * i, 16); }
    asm volatile("fence.mbarrier_init.release.cluster;" ::: "memory");
    prefetch_tmap((j < 4) ? &tm_wr : &tm_wi);
    prefetch_tmap(rank ? &tm_wu : &tm_wg);
  }
  __syncwarp();
  cluster_arrive_relaxed();

  if (warp >= 8) {
    reg_dec<40>();
    cluster_wait();
    if (tid == 256) {
      {
        const CUtensorMap* tw = (j < 4) ? &tm_wr : &tm_wi;
        const CUtensorMap* tgu = rank ? &tm_wu : &tm_wg;
        int slot = 0; uint32_t ph = 0;
        int kb = 0, unit = 0;
#pragma unroll 1
        for (int s = 0; s < 35; s++) {
          if (s >= K1_NS) mbar_wait(bar_empty + 8 * slot, ph ^ 1, 2);
          const uint32_t dst = sb + K1_B_OFF + slot * 16384;
          if (unit == 0) {
            mbar_expect(bar_full + 8 * slot, 14336);
            tma2d_mc(dst + rank * 7168, tw, kb * 64, (j & 3) * 112 + rank * 56, bar_full + 8 * slot, 3);
          } else {
            const int fb = (unit == 4) ? fbh : (fb0 + unit - 1);
            mbar_expect(bar_full + 8 * slot, 16384);
            tma2d_mc(dst + rank * 8192, tgu, fb * 64, kb * 64, bar_full + 8 * slot, 3);
          }
          if (++kb == 7) { kb = 0; unit++; }
          if (++slot == K1_NS) { slot = 0; ph ^= 1; }
        }
      }
      {
        const CUtensorMap* tb = (q < 3) ? &tm_ab : &tm_wd;
        prefetch_tmap(tb); prefetch_tmap((q < 3) ? ((g0 < 32) ? &tm_cr : &tm_ci) : &tm_h);
        const int kb0 = (q < 3) ? g0 : 0;
        if (q < 3) spin_flag(&g_ab_cnt, 128u * (epoch + 1)); else spin_flag(&g_h_cnt[mt], 16u * (epoch + 1));
        fence_proxy_async_all();
        DBG(1, 31);
        int slot = 0; uint32_t ph = 0;
#pragma unroll 1
        for (int s = 0; s < nkb; s++) {
          mbar_wait(bar_empty2 + 8 * slot, ph, 10);
          const uint32_t dst = sb + slot * K2_STAGE;
          const uint32_t fb = bar_full2 + 8 * slot;
          mbar_expect(fb, K2_STAGE);
          const int g = g0 + s;
          const CUtensorMap* ta = (g < 32) ? &tm_cr : (g < 64 ? &tm_ci : &tm_h);
          tma2d(dst, ta, (g & 31) * 64, mt * 128, fb);
          tma3d_mc(dst + 16384 + (2 * rank) * 8192, tb, (2 * rank) * 64, n, (kb0 + s) * 64, fb, 3);
          tma3d_mc(dst + 16384 + (2 * rank + 1) * 8192, tb, (2 * rank + 1) * 64, n, (kb0 + s) * 64, fb, 3);
          if (++slot == K2_NS) { slot = 0; ph ^= 1; }
        }
      }
    } else if (tid == 288) {
      const int b = blockIdx.x;
      l2_prefetch(pf.wg + b * 12544, 12544);
      l2_prefetch(pf.wu + b * 12544, 12544);
    }
  } else {
    reg_inc<232>();
    const int wg = warp >> 2;
    {
      const int c = lane & 7;
      const int r0 = warp * 16 + (lane >> 3);
      const uint4* src = reinterpret_cast<const uint4*>(x + (size_t)(mt * 128 + r0) * 448) + c;
      uint4 nx[7];
#pragma unroll
      for (int b = 0; b < 7; b++)
        asm volatile("ld.global.nc.v4.u32 {%0,%1,%2,%3}, [%4];" : "=r"(nx[b].x), "=r"(nx[b].y), "=r"(nx[b].z), "=r"(nx[b].w) : "l"(src + b * 8) : "memory");
#pragma unroll
      for (int pass = 1; pass < 4; pass++) asm volatile("prefetch.global.L2 [%0];" ::"l"(src + pass * 4 * 56 + c * 7 - c) : "memory");
#pragma unroll 1
      for (int pass = 0; pass < 4; pass++) {
        uint4 v[7];
#pragma unroll
        for (int b = 0; b < 7; b++) v[b] = nx[b];
        if (pass < 3) {
          const uint4* s2 = src + (pass + 1) * 4 * 56;
#pragma unroll
          for (int b = 0; b < 7; b++)
            asm volatile("ld.global.nc.v4.u32 {%0,%1,%2,%3}, [%4];" : "=r"(nx[b].x), "=r"(nx[b].y), "=r"(nx[b].z), "=r"(nx[b].w) : "l"(s2 + b * 8) : "memory");
        }
        float s0 = 0.f, s1 = 0.f, s2v = 0.f, s3 = 0.f;
#pragma unroll
        for (int b = 0; b < 7; b++) {
          s0 += bf_lo(v[b].x) + bf_hi(v[b].x); s1 += bf_lo(v[b].y) + bf_hi(v[b].y);
          s2v += bf_lo(v[b].z) + bf_hi(v[b].z); s3 += bf_lo(v[b].w) + bf_hi(v[b].w);
        }
        float m = (s0 + s1) + (s2v + s3);
        m += __shfl_xor_sync(0xffffffffu, m, 1);
        m += __shfl_xor_sync(0xffffffffu, m, 2);
        m += __shfl_xor_sync(0xffffffffu, m, 4);
        m *= (1.0f / 448.0f);
        float q0 = 0.f, q1 = 0.f, q2 = 0.f, q3 = 0.f;
#pragma unroll
        for (int b = 0; b < 7; b++) {
          float d;
          d = bf_lo(v[b].x) - m; q0 = fmaf(d, d, q0); d = bf_hi(v[b].x) - m; q1 = fmaf(d, d, q1);
          d = bf_lo(v[b].y) - m; q2 = fmaf(d, d, q2); d = bf_hi(v[b].y) - m; q3 = fmaf(d, d, q3);
          d = bf_lo(v[b].z) - m; q0 = fmaf(d, d, q0); d = bf_hi(v[b].z) - m; q1 = fmaf(d, d, q1);
          d = bf_lo(v[b].w) - m; q2 = fmaf(d, d, q2); d = bf_hi(v[b].w) - m; q3 = fmaf(d, d, q3);
        }
        float q = (q0 + q1) + (q2 + q3);
        q += __shfl_xor_sync(0xffffffffu, q, 1);
        q += __shfl_xor_sync(0xffffffffu, q, 2);
        q += __shfl_xor_sync(0xffffffffu, q, 4);
        const float var_b = rbf(q * (1.0f / 448.0f));
        const float den = rbf(sqrtf(rbf(var_b + 1e-5f)));
        const float ri = 1.0f / den;
        const float rih = rbf(ri);
        const uint32_t rhi2 = pack_bf16(rih, rih), rlo2 = pack_bf16(ri - rih, ri - rih);
        const uint32_t m2 = pack_bf16(m, m);
        const int r = r0 + pass * 4;
        const uint32_t a0 = sb + r * 128 + ((c ^ (r & 7)) * 16);
#pragma unroll
        for (int b = 0; b < 7; b++) {
          uint32_t w4[4] = {v[b].x, v[b].y, v[b].z, v[b].w};
#pragma unroll
          for (int qq = 0; qq < 4; qq++) {
            const uint32_t dw = hsub2_bf16(w4[qq], m2);
            w4[qq] = hfma2_bf16(dw, rhi2, hmul2_bf16(dw, rlo2));
          }
          sts128(a0 + b * 16384, make_uint4(w4[0], w4[1], w4[2], w4[3]));
        }
      }
    }
    asm volatile("fence.proxy.async.shared::cta;" ::: "memory");
    named_bar(1, 256);
    cluster_wait();
    if (tid == 0) DBG(0, 3);

    uint32_t rel0, rel1;
    asm volatile("mapa.shared::cluster.u32 %0, %1, %2;" : "=r"(rel0) : "r"(bar_empty2), "r"(0));
    asm volatile("mapa.shared::cluster.u32 %0, %1, %2;" : "=r"(rel1) : "r"(bar_empty2), "r"(1));
    {
      K1Ctx c;
      c.sb = sb; c.bar_full = bar_full; c.lane0 = (lane == 0);
      c.rel0 = rel0 - 8 * (K1_NS + K2_NS); c.rel1 = rel1 - 8 * (K1_NS + K2_NS);
      c.rel2a = rel0; c.rel2b = rel1;
      c.dA = make_desc(sb, 16, 1024);
      c.dBk = make_desc(sb + K1_B_OFF, 16, 1024);
      c.dBn = make_desc(sb + K1_B_OFF, 8192, 1024);
      if (wg == 0) {
        k1_unit_ab(c, warp, lane, mt, j);
        __threadfence();
        fence_proxy_async_all();
        named_bar(4, 128);
        if (tid == 0) {
          const unsigned int old = atomicAdd(&g_ab_cnt, 1u);
          if (old == 128u * (epoch + 1) - 1u) *reinterpret_cast<volatile unsigned int*>(&g_epoch) = epoch + 1;
          DBG(0, 6);
        }
      }
#pragma unroll 1
      for (int unit = 2 - wg; unit < 5; unit += 2) {
        k1_unit_gu(c, warp, lane, mt, unit, (unit == 4) ? fbh : fb0 + unit - 1, j & 1);
        if ((tid & 127) == 0) DBG(0, 6 + 3 * unit);
      }
      __threadfence();
      fence_proxy_async_all();
      named_bar(4 + wg, 128);
      if ((tid & 127) == 0) atomicAdd(&g_h_cnt[mt], 1u);
    }

    float acc[112];
    const uint32_t dA0 = make_desc(sb + wg * 8192, 16, 1024);
    const uint32_t dB0 = make_desc(sb + 16384, 8192, 1024);
    int slot = 0; uint32_t ph = 0;
#pragma unroll 1
    for (int s = 0; s < nkb; s++) {
      mbar_wait(bar_full2 + 8 * slot, ph, 11);
      if (tid == 0) DBG(1, 1 + s);
      wg_fence();
      const uint32_t da = dA0 + slot * (K2_STAGE / 16);
      const uint32_t db = dB0 + slot * (K2_STAGE / 16);
#pragma unroll
      for (int k = 0; k < 4; k++) wgmma_n224_tb(acc, da + k * 2, db + k * 128, (s | k) != 0);
      wg_commit();
      if (s > 0) {
        wg_wait<1>();
        const int ps = (slot == 0) ? K2_NS - 1 : slot - 1;
        if (lane == 0) {
          asm volatile("mbarrier.arrive.shared::cluster.b64 _, [%0];" ::"r"(rel0 + 8 * ps) : "memory");
          asm volatile("mbarrier.arrive.shared::cluster.b64 _, [%0];" ::"r"(rel1 + 8 * ps) : "memory");
        }
      }
      if (++slot == K2_NS) { slot = 0; ph ^= 1; }
    }
    wg_wait<0>();
    if (tid == 0) DBG(1, 29);
    if (q < 3) {
      const int G0 = q * 10, NG = (q == 2) ? 8 : 10;
      uint2* part = g_part + (size_t)tile * (3 * 28 * 256) + tid;
      const uint32_t sl = sb + tid * 16;
      named_bar(1, 256);
#pragma unroll
      for (int g = 0; g < 28; g++) {
        if ((unsigned)(g - G0) < (unsigned)NG)
          sts128(sl + (g - G0) * 4096, make_uint4(__float_as_uint(acc[4 * g]), __float_as_uint(acc[4 * g + 1]), __float_as_uint(acc[4 * g + 2]), __float_as_uint(acc[4 * g + 3])));
        else
          part[(q * 28 + g) * 256] = make_uint2(pack_bf16(acc[4 * g], acc[4 * g + 1]), pack_bf16(acc[4 * g + 2], acc[4 * g + 3]));
      }
      __threadfence();
      named_bar(1, 256);
      if (tid == 0) { atomicAdd(&g_flags[tile], 1u); spin_flag(&g_flags[tile], 3u * (epoch + 1)); }
      named_bar(1, 256);
      if (tid == 0) DBG(1, 30);
      const uint2* pa = part + (((q + 1) % 3) * 28 + G0) * 256;
      const uint2* pb = part + (((q + 2) % 3) * 28 + G0) * 256;
      const uint32_t s2 = sb + 49152 + tid * 16;
#pragma unroll 1
      for (int g = 0; g < NG; g++) {
        cp_async8(s2 + g * 4096, pa + g * 256);
        cp_async8(s2 + g * 4096 + 8, pb + g * 256);
      }
      cp_async_wait_all();
      uint32_t* sp = reinterpret_cast<uint32_t*>(g_s + (size_t)(mt * 128 + warp * 16 + (lane >> 2)) * 448 + n * 224 + (lane & 3) * 2) + G0 * 4;
#pragma unroll 2
      for (int g = 0; g < NG; g++) {
        const uint4 a = lds128(sl + g * 4096), b = lds128(s2 + g * 4096);
        sp[g * 4] = pack_bf16(__uint_as_float(a.x) + bf_lo(b.x) + bf_lo(b.z), __uint_as_float(a.y) + bf_hi(b.x) + bf_hi(b.z));
        sp[g * 4 + 8 * 224] = pack_bf16(__uint_as_float(a.z) + bf_lo(b.y) + bf_lo(b.w), __uint_as_float(a.w) + bf_hi(b.y) + bf_hi(b.w));
      }
      __threadfence();
      named_bar(1, 256);
      if (tid == 0) atomicAdd(&g_flags[32 + tile], 1u);
    } else {
      named_bar(1, 256);
      const uint32_t stg = sb + warp * 16 * K2_PITCH;
      const int st_row = (lane & 7) + 8 * ((lane >> 3) & 1);
      const uint32_t sa = stg + st_row * K2_PITCH + (lane >> 4) * 16;
#pragma unroll
      for (int g = 0; g < 28; g += 2) {
        const float* a = &acc[4 * g];
        stmatrix_x4(sa + g * 16, pack_bf16(a[0], a[1]), pack_bf16(a[2], a[3]), pack_bf16(a[4], a[5]), pack_bf16(a[6], a[7]));
      }
      const int lc = (lane < 28) ? lane : 27;
      const size_t gbase = (size_t)(mt * 128 + warp * 16) * 448 + n * 224 + lc * 8;
      const uint32_t lp = stg + lc * 16;
      const uint32_t xs = sb + 65536 + warp * 16384 + lane * 16;
#pragma unroll 1
      for (int t = 0; t < 16; t++) cp_async16(xs + t * 512, x + gbase + t * 448);
      __syncwarp();
#pragma unroll 2
      for (int t = 0; t < 16; t++) {
        const uint4 fv = lds128(lp + t * K2_PITCH);
        uint4 o;
        o.x = pack_bf16(silu_f(bf_lo(fv.x)), silu_f(bf_hi(fv.x)));
        o.y = pack_bf16(silu_f(bf_lo(fv.y)), silu_f(bf_hi(fv.y)));
        o.z = pack_bf16(silu_f(bf_lo(fv.z)), silu_f(bf_hi(fv.z)));
        o.w = pack_bf16(silu_f(bf_lo(fv.w)), silu_f(bf_hi(fv.w)));
        if (lane < 28) sts128(lp + t * K2_PITCH, o);
      }
      if (lane == 0) spin_flag(&g_flags[32 + tile], 3u * (epoch + 1));
      __syncwarp();
      if (tid == 0) DBG(1, 30);
#pragma unroll 1
      for (int t = 0; t < 16; t++) cp_async16(xs + 8192 + t * 512, g_s + gbase + t * 448);
      cp_async_wait_all();
#pragma unroll 4
      for (int t = 0; t < 16; t++) {
        const uint4 gv = lds128(lp + t * K2_PITCH), xx = lds128(xs + t * 512), ss = lds128(xs + 8192 + t * 512);
        uint4 o;
        o.x = hadd2_bf16(xx.x, hmul2_bf16(ss.x, gv.x));
        o.y = hadd2_bf16(xx.y, hmul2_bf16(ss.y, gv.y));
        o.z = hadd2_bf16(xx.z, hmul2_bf16(ss.z, gv.z));
        o.w = hadd2_bf16(xx.w, hmul2_bf16(ss.w, gv.w));
        if (lane < 28) stg128(out + gbase + t * 448, o);
      }
    }
    if (tid == 0) DBG(1, 63);
  }
  __syncwarp();
  cluster_arrive_relaxed();
  cluster_wait();
}

typedef CUresult (*EncFn)(CUtensorMap*, CUtensorMapDataType, cuuint32_t, void*, const cuuint64_t*, const cuuint64_t*, const cuuint32_t*,
                          const cuuint32_t*, CUtensorMapInterleave, CUtensorMapSwizzle, CUtensorMapL2promotion, CUtensorMapFloatOOBfill);

void make2d(EncFn enc, CUtensorMap* tm, const void* ptr, uint64_t cols, uint64_t rows, uint32_t bc, uint32_t br) {
  cuuint64_t gd[2] = {cols, rows};
  cuuint64_t gs[1] = {cols * 2};
  cuuint32_t bd[2] = {bc, br};
  cuuint32_t es[2] = {1, 1};
  enc(tm, CU_TENSOR_MAP_DATA_TYPE_BFLOAT16, 2, const_cast<void*>(ptr), gd, gs, bd, es, CU_TENSOR_MAP_INTERLEAVE_NONE,
      CU_TENSOR_MAP_SWIZZLE_128B, CU_TENSOR_MAP_L2_PROMOTION_L2_128B, CU_TENSOR_MAP_FLOAT_OOB_FILL_NONE);
}
void make3d_half(EncFn enc, CUtensorMap* tm, const void* ptr, uint64_t rows) {
  cuuint64_t gd[3] = {224, 2, rows};
  cuuint64_t gs[2] = {448, 896};
  cuuint32_t bd[3] = {64, 1, 64};
  cuuint32_t es[3] = {1, 1, 1};
  enc(tm, CU_TENSOR_MAP_DATA_TYPE_BFLOAT16, 3, const_cast<void*>(ptr), gd, gs, bd, es, CU_TENSOR_MAP_INTERLEAVE_NONE,
      CU_TENSOR_MAP_SWIZZLE_128B, CU_TENSOR_MAP_L2_PROMOTION_L2_128B, CU_TENSOR_MAP_FLOAT_OOB_FILL_NONE);
}

struct Maps { CUtensorMap wr, wi, wg, wu, cr, ci, h, ab, wd; };

}

extern "C" void kernel_launch(void* const* d_in, const int* in_sizes, int n_in, void* d_out, int out_size) {
  (void)in_sizes; (void)n_in; (void)out_size;
  static Maps maps;
  static const void* cached[9] = {nullptr};
  static bool attr_done = false;
  bool same = true;
  for (int i = 0; i < 9; i++) same = same && (cached[i] == d_in[i]);
  if (!same) {
    void* fn = nullptr;
    cudaDriverEntryPointQueryResult qr;
    cudaGetDriverEntryPoint("cuTensorMapEncodeTiled", &fn, cudaEnableDefault, &qr);
    EncFn enc = (EncFn)fn;
    void *p_ab = nullptr, *p_h = nullptr;
    cudaGetSymbolAddress(&p_ab, g_ab);
    cudaGetSymbolAddress(&p_h, g_h);
    make2d(enc, &maps.cr, d_in[1], 2048, 2048, 64, 128);
    make2d(enc, &maps.ci, d_in[2], 2048, 2048, 64, 128);
    make2d(enc, &maps.wr, d_in[3], 448, 448, 64, 56);
    make2d(enc, &maps.wi, d_in[4], 448, 448, 64, 56);
    make2d(enc, &maps.wg, d_in[6], 1792, 448, 64, 64);
    make2d(enc, &maps.wu, d_in[7], 1792, 448, 64, 64);
    make3d_half(enc, &maps.wd, d_in[8], 1792);
    make2d(enc, &maps.h, p_h, 1792, 2048, 64, 128);
    make3d_half(enc, &maps.ab, p_ab, 4096);
    for (int i = 0; i < 9; i++) cached[i] = d_in[i];
  }
  if (!attr_done) {
    cudaFuncSetAttribute(fused_kernel, cudaFuncAttributeMaxDynamicSharedMemorySize, K1_SMEM);
    attr_done = true;
  }
  PfPtrs pf;
  pf.wg = (const uint8_t*)d_in[6]; pf.wu = (const uint8_t*)d_in[7];
  fused_kernel<<<128, 384, K1_SMEM>>>(maps.wr, maps.wi, maps.wg, maps.wu, maps.cr, maps.ci, maps.h, maps.ab, maps.wd,
                                      (const __nv_bfloat16*)d_in[0], (__nv_bfloat16*)d_out, pf);
}
```

```cpp
#include <cuda_runtime.h>
#include <cuda_bf16.h>
#include <cuda.h>
#include <stdint.h>

namespace {

__device__ __align__(1024) __nv_bfloat16 g_ab[4096 * 448];
__device__ __align__(1024) __nv_bfloat16 g_h[2048 * 1792];
__device__ uint2 g_part[32 * 3 * 28 * 256];
__device__ __align__(1024) __nv_bfloat16 g_s[2048 * 448];
__device__ unsigned int g_flags[64];

#define DBG(k, i) do {} while (0)
#define DBGC(k, i) do {} while (0)

#define TIMEOUT(code) __trap()
#define SPIN_LIMIT (1 << 22)
__device__ __forceinline__ uint32_t s2u(const void* p) { return (uint32_t)__cvta_generic_to_shared(p); }
__device__ __forceinline__ void mbar_init(uint32_t b, int c) { asm volatile("mbarrier.init.shared::cta.b64 [%0], %1;" ::"r"(b), "r"(c)); }
__device__ __forceinline__ void mbar_expect(uint32_t b, uint32_t bytes) {
  asm volatile("mbarrier.arrive.expect_tx.shared::cta.b64 _, [%0], %1;" ::"r"(b), "r"(bytes) : "memory");
}
__device__ __forceinline__ void mbar_wait(uint32_t b, uint32_t ph, int code = 1) {
  uint32_t done = 0;
  int it = 0;
  while (true) {
    asm volatile("{.reg .pred p; mbarrier.try_wait.parity.shared::cta.b64 p, [%1], %2; selp.u32 %0,1,0,p;}" : "=r"(done) : "r"(b), "r"(ph) : "memory");
    if (done) break;
    if (++it > SPIN_LIMIT) { TIMEOUT(code); break; }
  }
}
__device__ __forceinline__ void mbar_arrive_cluster(uint32_t b, uint32_t cta) {
  uint32_t r;
  asm volatile("mapa.shared::cluster.u32 %0, %1, %2;" : "=r"(r) : "r"(b), "r"(cta));
  asm volatile("mbarrier.arrive.shared::cluster.b64 _, [%0];" ::"r"(r) : "memory");
}
__device__ __forceinline__ void tma2d(uint32_t dst, const CUtensorMap* m, int c0, int c1, uint32_t bar) {
  asm volatile("cp.async.bulk.tensor.2d.shared::cluster.global.mbarrier::complete_tx::bytes [%0], [%1, {%3,%4}], [%2];" ::"r"(dst), "l"(m), "r"(bar), "r"(c0), "r"(c1) : "memory");
}
__device__ __forceinline__ void tma2d_mc(uint32_t dst, const CUtensorMap* m, int c0, int c1, uint32_t bar, uint16_t mask) {
  asm volatile("cp.async.bulk.tensor.2d.shared::cluster.global.mbarrier::complete_tx::bytes.multicast::cluster [%0], [%1, {%3,%4}], [%2], %5;" ::"r"(dst), "l"(m), "r"(bar), "r"(c0), "r"(c1), "h"(mask) : "memory");
}
__device__ __forceinline__ void tma3d_mc(uint32_t dst, const CUtensorMap* m, int c0, int c1, int c2, uint32_t bar, uint16_t mask) {
  asm volatile("cp.async.bulk.tensor.3d.shared::cluster.global.mbarrier::complete_tx::bytes.multicast::cluster [%0], [%1, {%3,%4,%5}], [%2], %6;" ::"r"(dst), "l"(m), "r"(bar), "r"(c0), "r"(c1), "r"(c2), "h"(mask) : "memory");
}
__device__ __forceinline__ void tma2d_store(const CUtensorMap* m, uint32_t src, int c0, int c1) {
  asm volatile("cp.async.bulk.tensor.2d.global.shared::cta.bulk_group [%0, {%2,%3}], [%1];" ::"l"(m), "r"(src), "r"(c0), "r"(c1) : "memory");
}
__device__ __forceinline__ void bulk_commit() { asm volatile("cp.async.bulk.commit_group;" ::: "memory"); }
__device__ __forceinline__ void bulk_wait_read0() { asm volatile("cp.async.bulk.wait_group.read 0;" ::: "memory"); }
__device__ __forceinline__ void bulk_wait0() { asm volatile("cp.async.bulk.wait_group 0;" ::: "memory"); }
__device__ __forceinline__ void fence_async_smem() { asm volatile("fence.proxy.async.shared::cta;" ::: "memory"); }
__device__ __forceinline__ void prefetch_tmap(const CUtensorMap* m) { asm volatile("prefetch.tensormap [%0];" ::"l"(m) : "memory"); }
__device__ __forceinline__ void l2_prefetch(const void* p, uint32_t bytes) {
  asm volatile("cp.async.bulk.prefetch.L2.global [%0], %1;" ::"l"(p), "r"(bytes) : "memory");
}
__device__ __forceinline__ void cluster_arrive_relaxed() { asm volatile("barrier.cluster.arrive.relaxed.aligned;" ::: "memory"); }
__device__ __forceinline__ void cluster_wait() { asm volatile("barrier.cluster.wait.aligned;" ::: "memory"); }
__device__ __forceinline__ void wg_fence() { __syncwarp(); asm volatile("wgmma.fence.sync.aligned;" ::: "memory"); }
__device__ __forceinline__ void wg_commit() { asm volatile("wgmma.commit_group.sync.aligned;" ::: "memory"); }
template <int N> __device__ __forceinline__ void wg_wait() { __syncwarp(); asm volatile("wgmma.wait_group.sync.aligned %0;" ::"n"(N) : "memory"); }
__device__ __forceinline__ void named_bar(int id, int n) { asm volatile("bar.sync %0, %1;" ::"r"(id), "r"(n) : "memory"); }
__device__ __forceinline__ void named_arrive(int id, int n) { asm volatile("bar.arrive %0, %1;" ::"r"(id), "r"(n) : "memory"); }
template <int N> __device__ __forceinline__ void reg_inc() { asm volatile("setmaxnreg.inc.sync.aligned.u32 %0;" ::"n"(N)); }
template <int N> __device__ __forceinline__ void reg_dec() { asm volatile("setmaxnreg.dec.sync.aligned.u32 %0;" ::"n"(N)); }
__device__ __forceinline__ void pdl_wait() { asm volatile("griddepcontrol.wait;" ::: "memory"); }
__device__ __forceinline__ void pdl_launch() { asm volatile("griddepcontrol.launch_dependents;" ::: "memory"); }

__device__ __forceinline__ uint32_t make_desc(uint32_t addr, uint32_t lbo, uint32_t  ) {
  return ((addr & 0x3FFFF) >> 4) | ((lbo >> 4) << 16);
}
__device__ __forceinline__ void stmatrix_x4(uint32_t addr, uint32_t r0, uint32_t r1, uint32_t r2, uint32_t r3) {
  asm volatile("stmatrix.sync.aligned.m8n8.x4.shared.b16 [%0], {%1,%2,%3,%4};" ::"r"(addr), "r"(r0), "r"(r1), "r"(r2), "r"(r3) : "memory");
}
__device__ __forceinline__ uint4 lds128(uint32_t a) {
  uint4 v;
  asm volatile("ld.shared.v4.u32 {%0,%1,%2,%3}, [%4];" : "=r"(v.x), "=r"(v.y), "=r"(v.z), "=r"(v.w) : "r"(a) : "memory");
  return v;
}
__device__ __forceinline__ void sts128(uint32_t a, uint4 v) {
  asm volatile("st.shared.v4.u32 [%0], {%1,%2,%3,%4};" ::"r"(a), "r"(v.x), "r"(v.y), "r"(v.z), "r"(v.w) : "memory");
}
__device__ __forceinline__ void stg128(void* p, uint4 v) {
  asm volatile("st.global.v4.u32 [%0], {%1,%2,%3,%4};" ::"l"(p), "r"(v.x), "r"(v.y), "r"(v.z), "r"(v.w) : "memory");
}
__device__ __forceinline__ void cp_async16(uint32_t dst, const void* src) {
  asm volatile("cp.async.cg.shared.global [%0], [%1], 16;" ::"r"(dst), "l"(src) : "memory");
}
__device__ __forceinline__ void cp_async8(uint32_t dst, const void* src) {
  asm volatile("cp.async.ca.shared.global [%0], [%1], 8;" ::"r"(dst), "l"(src) : "memory");
}
__device__ __forceinline__ uint2 lds64(uint32_t a) {
  uint2 v;
  asm volatile("ld.shared.v2.u32 {%0,%1}, [%2];" : "=r"(v.x), "=r"(v.y) : "r"(a) : "memory");
  return v;
}
__device__ __forceinline__ void cp_async_wait_all() { asm volatile("cp.async.wait_all;" ::: "memory"); }
__device__ __forceinline__ uint32_t pack_bf16(float lo, float hi) {
  uint32_t r;
  asm("cvt.rn.bf16x2.f32 %0, %1, %2;" : "=r"(r) : "f"(hi), "f"(lo));
  return r;
}
__device__ __forceinline__ uint32_t hmul2_bf16(uint32_t a, uint32_t b) {
  uint32_t r;
  asm("mul.rn.bf16x2 %0, %1, %2;" : "=r"(r) : "r"(a), "r"(b));
  return r;
}
__device__ __forceinline__ uint32_t hsub2_bf16(uint32_t a, uint32_t b) {
  uint32_t r;
  asm("sub.rn.bf16x2 %0, %1, %2;" : "=r"(r) : "r"(a), "r"(b));
  return r;
}
__device__ __forceinline__ uint32_t hadd2_bf16(uint32_t a, uint32_t b) {
  uint32_t r;
  asm("add.rn.bf16x2 %0, %1, %2;" : "=r"(r) : "r"(a), "r"(b));
  return r;
}
__device__ __forceinline__ uint32_t hfma2_bf16(uint32_t a, uint32_t b, uint32_t c) {
  uint32_t r;
  asm("fma.rn.bf16x2 %0, %1, %2, %3;" : "=r"(r) : "r"(a), "r"(b), "r"(c));
  return r;
}
__device__ __forceinline__ bool mbar_test(uint32_t b, uint32_t ph) {
  uint32_t done;
  asm volatile("{.reg .pred p; mbarrier.test_wait.parity.shared::cta.b64 p, [%1], %2; selp.u32 %0,1,0,p;}" : "=r"(done) : "r"(b), "r"(ph) : "memory");
  return __all_sync(0xffffffffu, done != 0);
}
__device__ __forceinline__ uint4 ldg128_cg(const void* p) {
  uint4 v;
  asm volatile("ld.global.cg.v4.u32 {%0,%1,%2,%3}, [%4];" : "=r"(v.x), "=r"(v.y), "=r"(v.z), "=r"(v.w) : "l"(p) : "memory");
  return v;
}
__device__ __forceinline__ float bf_lo(uint32_t w) { return __uint_as_float(w << 16); }
__device__ __forceinline__ float bf_hi(uint32_t w) { return __uint_as_float(w & 0xffff0000u); }
__device__ __forceinline__ float rbf(float x) { return __bfloat162float(__float2bfloat16_rn(x)); }
__device__ __forceinline__ float ex2f(float x) { float r; asm("ex2.approx.ftz.f32 %0, %1;" : "=f"(r) : "f"(x)); return r; }
__device__ __forceinline__ float rcpf(float x) { float r; asm("rcp.approx.ftz.f32 %0, %1;" : "=f"(r) : "f"(x)); return r; }
__device__ __forceinline__ float tanhf_hw(float x) { float r; asm("tanh.approx.f32 %0, %1;" : "=f"(r) : "f"(x)); return r; }
__device__ __forceinline__ float gelu_tanh(float x) {
  const float c1 = 0.7978845608028654f;
  const float c2 = c1 * 0.044715f;
  const float t = tanhf_hw(x * fmaf(c2, x * x, c1));
  const float hx = 0.5f * x;
  return fmaf(hx, t, hx);
}
__device__ __forceinline__ float silu_f(float x) {
  const float e = ex2f(-1.4426950408889634f * x);
  return x * rcpf(1.0f + e);
}

__device__ __forceinline__ void wgmma_n128_tb(float (&d)[64], uint32_t da, uint32_t db, int scale_d) {
  asm volatile(
    "{\n.reg .pred p;\n.reg .b64 da, db;\nsetp.ne.b32 p, %66, 0;\n"
    "mov.b64 da, {%64, 0x40000040};\nmov.b64 db, {%65, 0x40000040};\n"
    "wgmma.mma_async.sync.aligned.m64n128k16.f32.bf16.bf16 {%0, %1, %2, %3, %4, %5, %6, %7, %8, %9, %10, %11, %12, %13, %14, %15, %16, %17, %18, %19, %20, %21, %22, %23, %24, %25, %26, %27, %28, %29, %30, %31, %32, %33, %34, %35, %36, %37, %38, %39, %40, %41, %42, %43, %44, %45, %46, %47, %48, %49, %50, %51, %52, %53, %54, %55, %56, %57, %58, %59, %60, %61, %62, %63}, da, db, p, 1, 1, 0, 1;\n}\n"
    : "+f"(d[0]), "+f"(d[1]), "+f"(d[2]), "+f"(d[3]), "+f"(d[4]), "+f"(d[5]), "+f"(d[6]), "+f"(d[7]), "+f"(d[8]), "+f"(d[9]), "+f"(d[10]), "+f"(d[11]), "+f"(d[12]), "+f"(d[13]), "+f"(d[14]), "+f"(d[15]), "+f"(d[16]), "+f"(d[17]), "+f"(d[18]), "+f"(d[19]), "+f"(d[20]), "+f"(d[21]), "+f"(d[22]), "+f"(d[23]), "+f"(d[24]), "+f"(d[25]), "+f"(d[26]), "+f"(d[27]), "+f"(d[28]), "+f"(d[29]), "+f"(d[30]), "+f"(d[31]), "+f"(d[32]), "+f"(d[33]), "+f"(d[34]), "+f"(d[35]), "+f"(d[36]), "+f"(d[37]), "+f"(d[38]), "+f"(d[39]), "+f"(d[40]), "+f"(d[41]), "+f"(d[42]), "+f"(d[43]), "+f"(d[44]), "+f"(d[45]), "+f"(d[46]), "+f"(d[47]), "+f"(d[48]), "+f"(d[49]), "+f"(d[50]), "+f"(d[51]), "+f"(d[52]), "+f"(d[53]), "+f"(d[54]), "+f"(d[55]), "+f"(d[56]), "+f"(d[57]), "+f"(d[58]), "+f"(d[59]), "+f"(d[60]), "+f"(d[61]), "+f"(d[62]), "+f"(d[63])
    : "r"(da), "r"(db), "r"(scale_d));
}
__device__ __forceinline__ void wgmma_n128_tb_p(float (&d)[64], uint32_t da, uint32_t db, int scale_d, int enable) {
  asm volatile(
    "{\n.reg .pred p;\n.reg .b64 da, db;\nsetp.ne.b32 p, %66, 0;\n.reg .pred q;\nsetp.ne.b32 q, %67, 0;\n"
    "mov.b64 da, {%64, 0x40000040};\nmov.b64 db, {%65, 0x40000040};\n"
    "@q wgmma.mma_async.sync.aligned.m64n128k16.f32.bf16.bf16 {%0, %1, %2, %3, %4, %5, %6, %7, %8, %9, %10, %11, %12, %13, %14, %15, %16, %17, %18, %19, %20, %21, %22, %23, %24, %25, %26, %27, %28, %29, %30, %31, %32, %33, %34, %35, %36, %37, %38, %39, %40, %41, %42, %43, %44, %45, %46, %47, %48, %49, %50, %51, %52, %53, %54, %55, %56, %57, %58, %59, %60, %61, %62, %63}, da, db, p, 1, 1, 0, 1;\n}\n"
    : "+f"(d[0]), "+f"(d[1]), "+f"(d[2]), "+f"(d[3]), "+f"(d[4]), "+f"(d[5]), "+f"(d[6]), "+f"(d[7]), "+f"(d[8]), "+f"(d[9]), "+f"(d[10]), "+f"(d[11]), "+f"(d[12]), "+f"(d[13]), "+f"(d[14]), "+f"(d[15]), "+f"(d[16]), "+f"(d[17]), "+f"(d[18]), "+f"(d[19]), "+f"(d[20]), "+f"(d[21]), "+f"(d[22]), "+f"(d[23]), "+f"(d[24]), "+f"(d[25]), "+f"(d[26]), "+f"(d[27]), "+f"(d[28]), "+f"(d[29]), "+f"(d[30]), "+f"(d[31]), "+f"(d[32]), "+f"(d[33]), "+f"(d[34]), "+f"(d[35]), "+f"(d[36]), "+f"(d[37]), "+f"(d[38]), "+f"(d[39]), "+f"(d[40]), "+f"(d[41]), "+f"(d[42]), "+f"(d[43]), "+f"(d[44]), "+f"(d[45]), "+f"(d[46]), "+f"(d[47]), "+f"(d[48]), "+f"(d[49]), "+f"(d[50]), "+f"(d[51]), "+f"(d[52]), "+f"(d[53]), "+f"(d[54]), "+f"(d[55]), "+f"(d[56]), "+f"(d[57]), "+f"(d[58]), "+f"(d[59]), "+f"(d[60]), "+f"(d[61]), "+f"(d[62]), "+f"(d[63])
    : "r"(da), "r"(db), "r"(scale_d), "r"(enable));
}
__device__ __forceinline__ void wgmma_n112(float (&d)[56], uint32_t da, uint32_t db, int scale_d) {
  asm volatile(
    "{\n.reg .pred p;\n.reg .b64 da, db;\nsetp.ne.b32 p, %58, 0;\n"
    "mov.b64 da, {%56, 0x40000040};\nmov.b64 db, {%57, 0x40000040};\n"
    "wgmma.mma_async.sync.aligned.m64n112k16.f32.bf16.bf16 {%0, %1, %2, %3, %4, %5, %6, %7, %8, %9, %10, %11, %12, %13, %14, %15, %16, %17, %18, %19, %20, %21, %22, %23, %24, %25, %26, %27, %28, %29, %30, %31, %32, %33, %34, %35, %36, %37, %38, %39, %40, %41, %42, %43, %44, %45, %46, %47, %48, %49, %50, %51, %52, %53, %54, %55}, da, db, p, 1, 1, 0, 0;\n}\n"
    : "+f"(d[0]), "+f"(d[1]), "+f"(d[2]), "+f"(d[3]), "+f"(d[4]), "+f"(d[5]), "+f"(d[6]), "+f"(d[7]), "+f"(d[8]), "+f"(d[9]), "+f"(d[10]), "+f"(d[11]), "+f"(d[12]), "+f"(d[13]), "+f"(d[14]), "+f"(d[15]), "+f"(d[16]), "+f"(d[17]), "+f"(d[18]), "+f"(d[19]), "+f"(d[20]), "+f"(d[21]), "+f"(d[22]), "+f"(d[23]), "+f"(d[24]), "+f"(d[25]), "+f"(d[26]), "+f"(d[27]), "+f"(d[28]), "+f"(d[29]), "+f"(d[30]), "+f"(d[31]), "+f"(d[32]), "+f"(d[33]), "+f"(d[34]), "+f"(d[35]), "+f"(d[36]), "+f"(d[37]), "+f"(d[38]), "+f"(d[39]), "+f"(d[40]), "+f"(d[41]), "+f"(d[42]), "+f"(d[43]), "+f"(d[44]), "+f"(d[45]), "+f"(d[46]), "+f"(d[47]), "+f"(d[48]), "+f"(d[49]), "+f"(d[50]), "+f"(d[51]), "+f"(d[52]), "+f"(d[53]), "+f"(d[54]), "+f"(d[55])
    : "r"(da), "r"(db), "r"(scale_d));
}
__device__ __forceinline__ void wgmma_n224_tb(float (&d)[112], uint32_t da, uint32_t db, int scale_d) {
  asm volatile(
    "{\n.reg .pred p;\n.reg .b64 da, db;\nsetp.ne.b32 p, %114, 0;\n"
    "mov.b64 da, {%112, 0x40000040};\nmov.b64 db, {%113, 0x40000040};\n"
    "wgmma.mma_async.sync.aligned.m64n224k16.f32.bf16.bf16 {%0, %1, %2, %3, %4, %5, %6, %7, %8, %9, %10, %11, %12, %13, %14, %15, %16, %17, %18, %19, %20, %21, %22, %23, %24, %25, %26, %27, %28, %29, %30, %31, %32, %33, %34, %35, %36, %37, %38, %39, %40, %41, %42, %43, %44, %45, %46, %47, %48, %49, %50, %51, %52, %53, %54, %55, %56, %57, %58, %59, %60, %61, %62, %63, %64, %65, %66, %67, %68, %69, %70, %71, %72, %73, %74, %75, %76, %77, %78, %79, %80, %81, %82, %83, %84, %85, %86, %87, %88, %89, %90, %91, %92, %93, %94, %95, %96, %97, %98, %99, %100, %101, %102, %103, %104, %105, %106, %107, %108, %109, %110, %111}, da, db, p, 1, 1, 0, 1;\n}\n"
    : "+f"(d[0]), "+f"(d[1]), "+f"(d[2]), "+f"(d[3]), "+f"(d[4]), "+f"(d[5]), "+f"(d[6]), "+f"(d[7]), "+f"(d[8]), "+f"(d[9]), "+f"(d[10]), "+f"(d[11]), "+f"(d[12]), "+f"(d[13]), "+f"(d[14]), "+f"(d[15]), "+f"(d[16]), "+f"(d[17]), "+f"(d[18]), "+f"(d[19]), "+f"(d[20]), "+f"(d[21]), "+f"(d[22]), "+f"(d[23]), "+f"(d[24]), "+f"(d[25]), "+f"(d[26]), "+f"(d[27]), "+f"(d[28]), "+f"(d[29]), "+f"(d[30]), "+f"(d[31]), "+f"(d[32]), "+f"(d[33]), "+f"(d[34]), "+f"(d[35]), "+f"(d[36]), "+f"(d[37]), "+f"(d[38]), "+f"(d[39]), "+f"(d[40]), "+f"(d[41]), "+f"(d[42]), "+f"(d[43]), "+f"(d[44]), "+f"(d[45]), "+f"(d[46]), "+f"(d[47]), "+f"(d[48]), "+f"(d[49]), "+f"(d[50]), "+f"(d[51]), "+f"(d[52]), "+f"(d[53]), "+f"(d[54]), "+f"(d[55]), "+f"(d[56]), "+f"(d[57]), "+f"(d[58]), "+f"(d[59]), "+f"(d[60]), "+f"(d[61]), "+f"(d[62]), "+f"(d[63]), "+f"(d[64]), "+f"(d[65]), "+f"(d[66]), "+f"(d[67]), "+f"(d[68]), "+f"(d[69]), "+f"(d[70]), "+f"(d[71]), "+f"(d[72]), "+f"(d[73]), "+f"(d[74]), "+f"(d[75]), "+f"(d[76]), "+f"(d[77]), "+f"(d[78]), "+f"(d[79]), "+f"(d[80]), "+f"(d[81]), "+f"(d[82]), "+f"(d[83]), "+f"(d[84]), "+f"(d[85]), "+f"(d[86]), "+f"(d[87]), "+f"(d[88]), "+f"(d[89]), "+f"(d[90]), "+f"(d[91]), "+f"(d[92]), "+f"(d[93]), "+f"(d[94]), "+f"(d[95]), "+f"(d[96]), "+f"(d[97]), "+f"(d[98]), "+f"(d[99]), "+f"(d[100]), "+f"(d[101]), "+f"(d[102]), "+f"(d[103]), "+f"(d[104]), "+f"(d[105]), "+f"(d[106]), "+f"(d[107]), "+f"(d[108]), "+f"(d[109]), "+f"(d[110]), "+f"(d[111])
    : "r"(da), "r"(db), "r"(scale_d));
}

constexpr int K1_NS = 5;
constexpr int K1_A_BYTES = 7 * 16384;
constexpr int K1_B_OFF = K1_A_BYTES;
constexpr int K1_STG_OFF = K1_B_OFF + K1_NS * 16384;
constexpr int K1_BAR_OFF = K1_STG_OFF + 8 * 4096;
constexpr int K1_SMEM = K1_BAR_OFF + 256 + 1024;

struct K1Ctx {
  uint32_t sb, bar_full, rel0, rel1;
  uint32_t dA, dBk, dBn;
  bool lane0;
  const CUtensorMap* tm_hs;
  const CUtensorMap* tm_abs;
};
__device__ __forceinline__ void k1_release(const K1Ctx& c, int slot) {
  if (c.lane0) {
    asm volatile("mbarrier.arrive.shared::cluster.b64 _, [%0];" ::"r"(c.rel0 + 8 * slot) : "memory");
    asm volatile("mbarrier.arrive.shared::cluster.b64 _, [%0];" ::"r"(c.rel1 + 8 * slot) : "memory");
  }
}

__device__ __forceinline__ void k1_unit_ab(const K1Ctx& c, int warp, int lane, int mt, int j) {
  const uint32_t stg = c.sb + K1_STG_OFF + warp * 4096;
  const int wq = warp & 3;
  const int st_row = (lane & 7) + 8 * ((lane >> 3) & 1);
  const int st_chunk = lane >> 4;
  float acc[2][56];
  int slot = 0; uint32_t ph = 0;
#pragma unroll 1
  for (int kb = 0; kb < 7; kb++) {
    const int pslot = (slot == 0) ? K1_NS - 1 : slot - 1;
    mbar_wait(c.bar_full + 8 * slot, ph, 3);
    if (kb == 6) named_arrive(2, 256);
    if (kb == 0 && (threadIdx.x & 127) == 0) DBG(0, 4);
    if ((threadIdx.x & 127) == 0) DBGC(1, 46 + kb);
    wg_fence();
    const uint32_t da = c.dA + kb * 1024;
    const uint32_t db = c.dBk + slot * 1024;
#pragma unroll
    for (int k = 0; k < 4; k++) {
      wgmma_n112(acc[0], da + k * 2, db + k * 2, (kb | k) != 0);
      wgmma_n112(acc[1], da + 512 + k * 2, db + k * 2, (kb | k) != 0);
    }
    wg_commit();
    if (kb > 0) { wg_wait<1>(); k1_release(c, pslot); }
    if (++slot == K1_NS) { slot = 0; ph ^= 1; }
  }
  wg_wait<0>();
  k1_release(c, 6 % K1_NS);
  if ((threadIdx.x & 127) == 0) DBG(0, 5);
  const uint32_t sgn = (j < 4) ? 0u : 0x80008000u;
  const uint32_t sa = stg + st_row * 224 + st_chunk * 16;
  const int row0 = (j < 4 ? 0 : 2048) + mt * 128 + wq * 16;
#pragma unroll
  for (int h = 0; h < 2; h++) {
    if (h == 1) { if (c.lane0) bulk_wait_read0(); __syncwarp(); }
#pragma unroll
    for (int g = 0; g < 14; g += 2) {
      const float* a = &acc[h][4 * g];
      stmatrix_x4(sa + g * 16, pack_bf16(a[0], a[1]) ^ sgn, pack_bf16(a[2], a[3]) ^ sgn, pack_bf16(a[4], a[5]) ^ sgn, pack_bf16(a[6], a[7]) ^ sgn);
    }
    fence_async_smem();
    __syncwarp();
    if (c.lane0) { tma2d_store(c.tm_abs, stg, (j & 3) * 112, row0 + h * 64); bulk_commit(); }
  }
}

__device__ __forceinline__ void k1_unit_gu(const K1Ctx& c, int warp, int lane, int mt, int unit, int fb, int hsel) {
  const uint32_t stg = c.sb + K1_STG_OFF + warp * 4096;
  const int wq = warp & 3;
  const int full = (unit < 4);
  float acc[2][64];
  const uint32_t dA0 = c.dA + (full ? 0 : hsel * 512);
  int slot = (unit * 7) % K1_NS; uint32_t ph = ((unit * 7) / K1_NS) & 1;
  named_bar(2 + ((unit - 1) & 1), 256);
  if (full) {
#pragma unroll 1
    for (int kb = 0; kb < 7; kb++) {
      const int pslot = (slot == 0) ? K1_NS - 1 : slot - 1;
      mbar_wait(c.bar_full + 8 * slot, ph, 4);
      if (kb == 6) named_arrive(2 + (unit & 1), 256);
      if (kb == 0 && (threadIdx.x & 127) == 0) DBG(0, 4 + 3 * unit);
      wg_fence();
      const uint32_t da = dA0 + kb * 1024;
      const uint32_t db = c.dBn + slot * 1024;
#pragma unroll
      for (int k = 0; k < 4; k++) {
        wgmma_n128_tb(acc[0], da + k * 2, db + k * 128, (kb | k) != 0);
        wgmma_n128_tb(acc[1], da + 512 + k * 2, db + k * 128, (kb | k) != 0);
      }
      wg_commit();
      if (kb > 0) { wg_wait<1>(); k1_release(c, pslot); }
      if (++slot == K1_NS) { slot = 0; ph ^= 1; }
    }
  } else {
#pragma unroll 1
    for (int kb = 0; kb < 7; kb++) {
      const int pslot = (slot == 0) ? K1_NS - 1 : slot - 1;
      mbar_wait(c.bar_full + 8 * slot, ph, 5);
      if (kb == 0 && (threadIdx.x & 127) == 0) DBG(0, 4 + 3 * unit);
      wg_fence();
      const uint32_t da = dA0 + kb * 1024;
      const uint32_t db = c.dBn + slot * 1024;
#pragma unroll
      for (int k = 0; k < 4; k++) wgmma_n128_tb(acc[0], da + k * 2, db + k * 128, (kb | k) != 0);
      wg_commit();
      if (kb > 0) { wg_wait<1>(); k1_release(c, pslot); }
      if (++slot == K1_NS) { slot = 0; ph ^= 1; }
    }
  }
  wg_wait<0>();
  k1_release(c, (slot == 0) ? K1_NS - 1 : slot - 1);
  if ((threadIdx.x & 127) == 0) DBG(0, 5 + 3 * unit);
  const int st_row = (lane & 7) + 8 * ((lane >> 3) & 1);
  const int st_chunk = lane >> 4;
  const uint32_t sa = stg + st_row * 128;
  const int row0 = mt * 128 + (full ? 0 : hsel * 64) + wq * 16;
  if (c.lane0) bulk_wait_read0();
  __syncwarp();
#pragma unroll
  for (int h = 0; h < 2; h++) {
    if (h == 1 && !full) break;
#pragma unroll
    for (int g = 0; g < 8; g += 2) {
      uint32_t pk[4];
#pragma unroll
      for (int e = 0; e < 4; e++) {
        const int i = 4 * g + 2 * e;
        const uint32_t g2 = pack_bf16(acc[h][i], acc[h][i + 1]);
        const uint32_t u2 = pack_bf16(acc[h][32 + i], acc[h][32 + i + 1]);
        pk[e] = hmul2_bf16(pack_bf16(gelu_tanh(bf_lo(g2)), gelu_tanh(bf_hi(g2))), u2);
      }
      stmatrix_x4(sa + h * 2048 + (((g + st_chunk) ^ (st_row & 7)) * 16), pk[0], pk[1], pk[2], pk[3]);
    }
    fence_async_smem();
    __syncwarp();
    if (c.lane0) { tma2d_store(c.tm_hs, stg + h * 2048, fb * 64, row0 + h * 64); bulk_commit(); }
  }
}

struct PfPtrs { const uint8_t* wr; const uint8_t* wi; const uint8_t* wg; const uint8_t* wu; const uint8_t* wd; const uint8_t* cr; const uint8_t* ci; };

__global__ void __cluster_dims__(2, 1, 1) __launch_bounds__(384, 1)
k1_kernel(const __grid_constant__ CUtensorMap tm_wr, const __grid_constant__ CUtensorMap tm_wi,
          const __grid_constant__ CUtensorMap tm_wg, const __grid_constant__ CUtensorMap tm_wu,
          const __grid_constant__ CUtensorMap tm_hs, const __grid_constant__ CUtensorMap tm_abs,
          const __nv_bfloat16* __restrict__ x, const PfPtrs pf) {
  extern __shared__ uint8_t smem_raw[];
  const uint32_t sb = (s2u(smem_raw) + 1023) & ~1023u;
  const int tid = threadIdx.x, warp = tid >> 5, lane = tid & 31;
  uint32_t rank;
  asm volatile("mov.u32 %0, %%cluster_ctarank;" : "=r"(rank));
  const int cid = blockIdx.x >> 1;
  const int p = cid >> 3, j = cid & 7;
  const int mt = 2 * p + (int)rank;
  const uint32_t bar_full = sb + K1_BAR_OFF;
  const uint32_t bar_empty = bar_full + 8 * K1_NS;
  const int fb_base = 7 * (j >> 1);
  const int fb0 = fb_base + ((j & 1) ? 4 : 0);
  const int fbh = fb_base + 3;
  const CUtensorMap* tw = (j < 4) ? &tm_wr : &tm_wi;
  const CUtensorMap* tgu = rank ? &tm_wu : &tm_wg;

  if (tid == 0) DBG(0, 0);
  if (tid == 256) {
    for (int i = 0; i < K1_NS; i++) { mbar_init(bar_full + 8 * i, 1); mbar_init(bar_empty + 8 * i, 8); }
    asm volatile("fence.mbarrier_init.release.cluster;" ::: "memory");
    prefetch_tmap(tw);
    prefetch_tmap(tgu);
    prefetch_tmap(&tm_abs);
    prefetch_tmap(&tm_hs);
    if (blockIdx.x < 64) g_flags[blockIdx.x] = 0;
  }
  __syncwarp();
  cluster_arrive_relaxed();
  pdl_launch();

  if (warp >= 8) {
    reg_dec<40>();
    cluster_wait();
    if (tid == 256) {
      int slot = 0; uint32_t ph = 0;
      int kb = 0, unit = 0;
#pragma unroll 1
      for (int s = 0; s < 35; s++) {
        if (s >= K1_NS) mbar_wait(bar_empty + 8 * slot, ph ^ 1, 2);
        DBG(0, 20 + s);
        const uint32_t dst = sb + K1_B_OFF + slot * 16384;
        if (unit == 0) {
          mbar_expect(bar_full + 8 * slot, 14336);
          tma2d_mc(dst + rank * 7168, tw, kb * 64, (j & 3) * 112 + rank * 56, bar_full + 8 * slot, 3);
        } else {
          const int fb = (unit == 4) ? fbh : (fb0 + unit - 1);
          mbar_expect(bar_full + 8 * slot, 16384);
          tma2d_mc(dst + rank * 8192, tgu, fb * 64, kb * 64, bar_full + 8 * slot, 3);
        }
        if (++kb == 7) { kb = 0; unit++; }
        if (++slot == K1_NS) { slot = 0; ph ^= 1; }
      }
    } else if (tid == 288) {
      const int b = blockIdx.x;
      l2_prefetch(pf.wg + b * 12544, 12544);
      l2_prefetch(pf.wu + b * 12544, 12544);
    }
  } else {
    reg_inc<232>();
    const int wg = warp >> 2;
    {
      const int c = lane & 7;
      const int r0 = warp * 16 + (lane >> 3);
      const uint4* src = reinterpret_cast<const uint4*>(x + (size_t)(mt * 128 + r0) * 448) + c;
      uint4 nx[7];
#pragma unroll
      for (int b = 0; b < 7; b++)
        asm volatile("ld.global.nc.v4.u32 {%0,%1,%2,%3}, [%4];" : "=r"(nx[b].x), "=r"(nx[b].y), "=r"(nx[b].z), "=r"(nx[b].w) : "l"(src + b * 8) : "memory");
#pragma unroll
      for (int pass = 1; pass < 4; pass++) asm volatile("prefetch.global.L2 [%0];" ::"l"(src + pass * 4 * 56 + c * 7 - c) : "memory");
#pragma unroll 1
      for (int pass = 0; pass < 4; pass++) {
        uint4 v[7];
#pragma unroll
        for (int b = 0; b < 7; b++) v[b] = nx[b];
        if (pass < 3) {
          const uint4* s2 = src + (pass + 1) * 4 * 56;
#pragma unroll
          for (int b = 0; b < 7; b++)
            asm volatile("ld.global.nc.v4.u32 {%0,%1,%2,%3}, [%4];" : "=r"(nx[b].x), "=r"(nx[b].y), "=r"(nx[b].z), "=r"(nx[b].w) : "l"(s2 + b * 8) : "memory");
        }
        float s0 = 0.f, s1 = 0.f, s2v = 0.f, s3 = 0.f;
#pragma unroll
        for (int b = 0; b < 7; b++) {
          s0 += bf_lo(v[b].x) + bf_hi(v[b].x); s1 += bf_lo(v[b].y) + bf_hi(v[b].y);
          s2v += bf_lo(v[b].z) + bf_hi(v[b].z); s3 += bf_lo(v[b].w) + bf_hi(v[b].w);
        }
        float m = (s0 + s1) + (s2v + s3);
        m += __shfl_xor_sync(0xffffffffu, m, 1);
        m += __shfl_xor_sync(0xffffffffu, m, 2);
        m += __shfl_xor_sync(0xffffffffu, m, 4);
        m *= (1.0f / 448.0f);
        float q0 = 0.f, q1 = 0.f, q2 = 0.f, q3 = 0.f;
#pragma unroll
        for (int b = 0; b < 7; b++) {
          float d;
          d = bf_lo(v[b].x) - m; q0 = fmaf(d, d, q0); d = bf_hi(v[b].x) - m; q1 = fmaf(d, d, q1);
          d = bf_lo(v[b].y) - m; q2 = fmaf(d, d, q2); d = bf_hi(v[b].y) - m; q3 = fmaf(d, d, q3);
          d = bf_lo(v[b].z) - m; q0 = fmaf(d, d, q0); d = bf_hi(v[b].z) - m; q1 = fmaf(d, d, q1);
          d = bf_lo(v[b].w) - m; q2 = fmaf(d, d, q2); d = bf_hi(v[b].w) - m; q3 = fmaf(d, d, q3);
        }
        float q = (q0 + q1) + (q2 + q3);
        q += __shfl_xor_sync(0xffffffffu, q, 1);
        q += __shfl_xor_sync(0xffffffffu, q, 2);
        q += __shfl_xor_sync(0xffffffffu, q, 4);
        const float var_b = rbf(q * (1.0f / 448.0f));
        const float den = rbf(sqrtf(rbf(var_b + 1e-5f)));
        const float ri = 1.0f / den;
        const float rih = rbf(ri);
        const uint32_t rhi2 = pack_bf16(rih, rih), rlo2 = pack_bf16(ri - rih, ri - rih);
        const uint32_t m2 = pack_bf16(m, m);
        const int r = r0 + pass * 4;
        const uint32_t a0 = sb + r * 128 + ((c ^ (r & 7)) * 16);
#pragma unroll
        for (int b = 0; b < 7; b++) {
          uint32_t w4[4] = {v[b].x, v[b].y, v[b].z, v[b].w};
#pragma unroll
          for (int qq = 0; qq < 4; qq++) {
            const uint32_t dw = hsub2_bf16(w4[qq], m2);
            w4[qq] = hfma2_bf16(dw, rhi2, hmul2_bf16(dw, rlo2));
          }
          sts128(a0 + b * 16384, make_uint4(w4[0], w4[1], w4[2], w4[3]));
        }
      }
    }
    if (lane == 0) DBG(0, 59 + (warp & 3));
    asm volatile("fence.proxy.async.shared::cta;" ::: "memory");
    named_bar(1, 256);
    cluster_wait();
    if (tid == 0) DBG(0, 3);

    K1Ctx c;
    c.sb = sb; c.bar_full = bar_full; c.lane0 = (lane == 0);
    asm volatile("mapa.shared::cluster.u32 %0, %1, %2;" : "=r"(c.rel0) : "r"(bar_empty), "r"(0));
    asm volatile("mapa.shared::cluster.u32 %0, %1, %2;" : "=r"(c.rel1) : "r"(bar_empty), "r"(1));
    c.tm_hs = &tm_hs; c.tm_abs = &tm_abs;
    c.dA = make_desc(sb, 16, 1024);
    c.dBk = make_desc(sb + K1_B_OFF, 16, 1024);
    c.dBn = make_desc(sb + K1_B_OFF, 8192, 1024);
    if (wg == 0) {
      k1_unit_ab(c, warp, lane, mt, j);
      if (tid == 0) DBG(0, 6);
    }
#pragma unroll 1
    for (int unit = 2 - wg; unit < 5; unit += 2) {
      k1_unit_gu(c, warp, lane, mt, unit, (unit == 4) ? fbh : fb0 + unit - 1, j & 1);
      if ((tid & 127) == 0) DBG(0, 6 + 3 * unit);
    }
    if (lane == 0) bulk_wait0();
  }
  __syncwarp();
  cluster_arrive_relaxed();
  cluster_wait();
}

constexpr int K2_NS = 4;
constexpr int K2_STAGE = 16384 + 32768;
constexpr int K2_BAR_OFF = K2_NS * K2_STAGE;
constexpr int K2_SMEM = K2_BAR_OFF + 256 + 1024;
constexpr int K2_PITCH = 464;

__device__ __forceinline__ void spin_flag(const unsigned int* flag, unsigned int target) {
  int it = 0;
  while (true) {
    unsigned int v;
    asm volatile("ld.acquire.gpu.global.u32 %0, [%1];" : "=r"(v) : "l"(flag) : "memory");
    if (v >= target) break;
    if (++it > SPIN_LIMIT) { TIMEOUT(20); break; }
  }
}

__global__ void __cluster_dims__(2, 1, 1) __launch_bounds__(384, 1)
k2_kernel(const __grid_constant__ CUtensorMap tm_cr, const __grid_constant__ CUtensorMap tm_ci, const __grid_constant__ CUtensorMap tm_h,
          const __grid_constant__ CUtensorMap tm_ab, const __grid_constant__ CUtensorMap tm_wd,
          const __nv_bfloat16* __restrict__ x, __nv_bfloat16* __restrict__ out) {
  extern __shared__ uint8_t smem_raw[];
  const uint32_t sb = (s2u(smem_raw) + 1023) & ~1023u;
  const int tid = threadIdx.x, warp = tid >> 5, lane = tid & 31;
  uint32_t rank;
  asm volatile("mov.u32 %0, %%cluster_ctarank;" : "=r"(rank));
  const int cid = blockIdx.x >> 1;
  const int q = cid & 3, n = (cid >> 2) & 1, p = cid >> 3;
  const int mt = 2 * p + (int)rank;
  const int tile = mt * 2 + n;
  const uint32_t bar_full = sb + K2_BAR_OFF;
  const uint32_t bar_empty = bar_full + 8 * K2_NS;
  const int g0 = (q == 0) ? 0 : (q == 1 ? 22 : (q == 2 ? 43 : 64));
  const int nkb = (q == 0) ? 22 : (q == 3 ? 28 : 21);

  if (tid == 0) DBG(1, 0);
  if (tid == 256) {
    for (int i = 0; i < K2_NS; i++) { mbar_init(bar_full + 8 * i, 1); mbar_init(bar_empty + 8 * i, 16); }
    asm volatile("fence.mbarrier_init.release.cluster;" ::: "memory");
    if (q == 3) { prefetch_tmap(&tm_h); prefetch_tmap(&tm_wd); }
    else { prefetch_tmap(&tm_cr); prefetch_tmap(&tm_ci); prefetch_tmap(&tm_ab); }
  }
  __syncwarp();
  cluster_arrive_relaxed();
  cluster_wait();

  if (warp >= 8) {
    reg_dec<40>();
    if (tid == 256) {
      const CUtensorMap* tb = (q < 3) ? &tm_ab : &tm_wd;
      const int kb0 = (q < 3) ? g0 : 0;
      int slot = 0; uint32_t ph = 0;
#pragma unroll 1
      for (int it = 0; it < nkb + K2_NS; it++) {
        const int s = (it < K2_NS) ? it : it - K2_NS;
        const bool pre = (it < K2_NS), post = (!pre && s < K2_NS);
        if (it == K2_NS) { pdl_wait(); DBG(1, 31); slot = 0; }
        if (!pre && !post) mbar_wait(bar_empty + 8 * slot, ph, 10);
        const uint32_t dst = sb + slot * K2_STAGE;
        const uint32_t fb = bar_full + 8 * slot;
        if (!post) mbar_expect(fb, K2_STAGE);
        const bool doA = pre ? (q < 3) : (post ? (q == 3) : true);
        const bool doB = pre ? (q == 3) : (post ? (q < 3) : true);
        if (doA) {
          const int g = g0 + s;
          const CUtensorMap* ta = (g < 32) ? &tm_cr : (g < 64 ? &tm_ci : &tm_h);
          tma2d(dst, ta, (g & 31) * 64 + ((g >= 96) ? 2048 : 0), mt * 128, fb);
        }
        if (doB) {
          tma3d_mc(dst + 16384 + (2 * rank) * 8192, tb, (2 * rank) * 64, n, (kb0 + s) * 64, fb, 3);
          tma3d_mc(dst + 16384 + (2 * rank + 1) * 8192, tb, (2 * rank + 1) * 64, n, (kb0 + s) * 64, fb, 3);
        }
        if (++slot == K2_NS) { slot = 0; if (!pre && !post) ph ^= 1; }
      }
    }
  } else {
    reg_inc<232>();
    const int wg = warp >> 2;
    float acc[112];
    uint32_t rel0, rel1;
    asm volatile("mapa.shared::cluster.u32 %0, %1, %2;" : "=r"(rel0) : "r"(bar_empty), "r"(0));
    asm volatile("mapa.shared::cluster.u32 %0, %1, %2;" : "=r"(rel1) : "r"(bar_empty), "r"(1));
    const uint32_t dA0 = make_desc(sb + wg * 8192, 16, 1024);
    const uint32_t dB0 = make_desc(sb + 16384, 8192, 1024);
    int slot = 0; uint32_t ph = 0;
#pragma unroll 1
    for (int s = 0; s < nkb; s++) {
      mbar_wait(bar_full + 8 * slot, ph, 11);
      if (tid == 0) DBG(1, 1 + s);
      if (tid == 0 && (s == 5 || s == 15)) DBGC(1, 53 + (s == 15));
      if (tid == 0 && (s == 23 || s == 27)) DBGC(1, 55 + (s == 27));
      wg_fence();
      const uint32_t da = dA0 + slot * (K2_STAGE / 16);
      const uint32_t db = dB0 + slot * (K2_STAGE / 16);
#pragma unroll
      for (int k = 0; k < 4; k++) wgmma_n224_tb(acc, da + k * 2, db + k * 128, (s | k) != 0);
      wg_commit();
      if (s > 0) {
        wg_wait<1>();
        const int ps = (slot == 0) ? K2_NS - 1 : slot - 1;
        if (lane == 0) {
          asm volatile("mbarrier.arrive.shared::cluster.b64 _, [%0];" ::"r"(rel0 + 8 * ps) : "memory");
          asm volatile("mbarrier.arrive.shared::cluster.b64 _, [%0];" ::"r"(rel1 + 8 * ps) : "memory");
        }
      }
      if (++slot == K2_NS) { slot = 0; ph ^= 1; }
    }
    wg_wait<0>();
    pdl_wait();
    if (tid == 0) DBG(1, 29);
    if (q < 3) {
      const int G0 = q * 10, NG = (q == 2) ? 8 : 10;
      uint2* part = g_part + (size_t)tile * (3 * 28 * 256) + tid;
      const uint32_t sl = sb + tid * 16;
      named_bar(1, 256);
#pragma unroll
      for (int g = 0; g < 28; g++) {
        if ((unsigned)(g - G0) < (unsigned)NG)
          sts128(sl + (g - G0) * 4096, make_uint4(__float_as_uint(acc[4 * g]), __float_as_uint(acc[4 * g + 1]), __float_as_uint(acc[4 * g + 2]), __float_as_uint(acc[4 * g + 3])));
        else
          part[(q * 28 + g) * 256] = make_uint2(pack_bf16(acc[4 * g], acc[4 * g + 1]), pack_bf16(acc[4 * g + 2], acc[4 * g + 3]));
      }
      __threadfence();
      named_bar(1, 256);
      if (tid == 0) { atomicAdd(&g_flags[tile], 1u); spin_flag(&g_flags[tile], 3u); }
      named_bar(1, 256);
      if (tid == 0) DBG(1, 30);
      const uint2* pa = part + (((q + 1) % 3) * 28 + G0) * 256;
      const uint2* pb = part + (((q + 2) % 3) * 28 + G0) * 256;
      const uint32_t s2 = sb + 49152 + tid * 16;
#pragma unroll 1
      for (int g = 0; g < NG; g++) {
        cp_async8(s2 + g * 4096, pa + g * 256);
        cp_async8(s2 + g * 4096 + 8, pb + g * 256);
      }
      cp_async_wait_all();
      uint32_t* sp = reinterpret_cast<uint32_t*>(g_s + (size_t)(mt * 128 + warp * 16 + (lane >> 2)) * 448 + n * 224 + (lane & 3) * 2) + G0 * 4;
#pragma unroll 2
      for (int g = 0; g < NG; g++) {
        const uint4 a = lds128(sl + g * 4096), b = lds128(s2 + g * 4096);
        sp[g * 4] = pack_bf16(__uint_as_float(a.x) + bf_lo(b.x) + bf_lo(b.z), __uint_as_float(a.y) + bf_hi(b.x) + bf_hi(b.z));
        sp[g * 4 + 8 * 224] = pack_bf16(__uint_as_float(a.z) + bf_lo(b.y) + bf_lo(b.w), __uint_as_float(a.w) + bf_hi(b.y) + bf_hi(b.w));
      }
      __threadfence();
      named_bar(1, 256);
      if (tid == 0) atomicAdd(&g_flags[32 + tile], 1u);
    } else {
      named_bar(1, 256);
      const uint32_t stg = sb + warp * 16 * K2_PITCH;
      const int st_row = (lane & 7) + 8 * ((lane >> 3) & 1);
      const uint32_t sa = stg + st_row * K2_PITCH + (lane >> 4) * 16;
#pragma unroll
      for (int g = 0; g < 28; g += 2) {
        const float* a = &acc[4 * g];
        stmatrix_x4(sa + g * 16, pack_bf16(a[0], a[1]), pack_bf16(a[2], a[3]), pack_bf16(a[4], a[5]), pack_bf16(a[6], a[7]));
      }
      const int lc = (lane < 28) ? lane : 27;
      const size_t gbase = (size_t)(mt * 128 + warp * 16) * 448 + n * 224 + lc * 8;
      const uint32_t lp = stg + lc * 16;
      const uint32_t xs = sb + 65536 + warp * 16384 + lane * 16;
#pragma unroll 1
      for (int t = 0; t < 16; t++) cp_async16(xs + t * 512, x + gbase + t * 448);
      __syncwarp();
#pragma unroll 2
      for (int t = 0; t < 16; t++) {
        const uint4 fv = lds128(lp + t * K2_PITCH);
        uint4 o;
        o.x = pack_bf16(silu_f(bf_lo(fv.x)), silu_f(bf_hi(fv.x)));
        o.y = pack_bf16(silu_f(bf_lo(fv.y)), silu_f(bf_hi(fv.y)));
        o.z = pack_bf16(silu_f(bf_lo(fv.z)), silu_f(bf_hi(fv.z)));
        o.w = pack_bf16(silu_f(bf_lo(fv.w)), silu_f(bf_hi(fv.w)));
        if (lane < 28) sts128(lp + t * K2_PITCH, o);
      }
      if (lane == 0) spin_flag(&g_flags[32 + tile], 3u);
      __syncwarp();
      if (tid == 0) DBG(1, 30);
#pragma unroll 1
      for (int t = 0; t < 16; t++) cp_async16(xs + 8192 + t * 512, g_s + gbase + t * 448);
      cp_async_wait_all();
#pragma unroll 4
      for (int t = 0; t < 16; t++) {
        const uint4 gv = lds128(lp + t * K2_PITCH), xx = lds128(xs + t * 512), ss = lds128(xs + 8192 + t * 512);
        uint4 o;
        o.x = hadd2_bf16(xx.x, hmul2_bf16(ss.x, gv.x));
        o.y = hadd2_bf16(xx.y, hmul2_bf16(ss.y, gv.y));
        o.z = hadd2_bf16(xx.z, hmul2_bf16(ss.z, gv.z));
        o.w = hadd2_bf16(xx.w, hmul2_bf16(ss.w, gv.w));
        if (lane < 28) stg128(out + gbase + t * 448, o);
      }
    }
    if (tid == 0) DBG(1, 63);
  }
  __syncwarp();
  cluster_arrive_relaxed();
  cluster_wait();
}

typedef CUresult (*EncFn)(CUtensorMap*, CUtensorMapDataType, cuuint32_t, void*, const cuuint64_t*, const cuuint64_t*, const cuuint32_t*,
                          const cuuint32_t*, CUtensorMapInterleave, CUtensorMapSwizzle, CUtensorMapL2promotion, CUtensorMapFloatOOBfill);

void make2d(EncFn enc, CUtensorMap* tm, const void* ptr, uint64_t cols, uint64_t rows, uint32_t bc, uint32_t br, bool swz = true) {
  cuuint64_t gd[2] = {cols, rows};
  cuuint64_t gs[1] = {cols * 2};
  cuuint32_t bd[2] = {bc, br};
  cuuint32_t es[2] = {1, 1};
  enc(tm, CU_TENSOR_MAP_DATA_TYPE_BFLOAT16, 2, const_cast<void*>(ptr), gd, gs, bd, es, CU_TENSOR_MAP_INTERLEAVE_NONE,
      swz ? CU_TENSOR_MAP_SWIZZLE_128B : CU_TENSOR_MAP_SWIZZLE_NONE, CU_TENSOR_MAP_L2_PROMOTION_L2_128B, CU_TENSOR_MAP_FLOAT_OOB_FILL_NONE);
}
void make3d_half(EncFn enc, CUtensorMap* tm, const void* ptr, uint64_t rows) {
  cuuint64_t gd[3] = {224, 2, rows};
  cuuint64_t gs[2] = {448, 896};
  cuuint32_t bd[3] = {64, 1, 64};
  cuuint32_t es[3] = {1, 1, 1};
  enc(tm, CU_TENSOR_MAP_DATA_TYPE_BFLOAT16, 3, const_cast<void*>(ptr), gd, gs, bd, es, CU_TENSOR_MAP_INTERLEAVE_NONE,
      CU_TENSOR_MAP_SWIZZLE_128B, CU_TENSOR_MAP_L2_PROMOTION_L2_128B, CU_TENSOR_MAP_FLOAT_OOB_FILL_NONE);
}

struct Maps { CUtensorMap wr, wi, wg, wu, cr, ci, h, ab, wd, hs, abs; };

}

extern "C" void kernel_launch(void* const* d_in, const int* in_sizes, int n_in, void* d_out, int out_size) {
  (void)in_sizes; (void)n_in; (void)out_size;
  static Maps maps;
  static const void* cached[9] = {nullptr};
  static bool attr_done = false;
  bool same = true;
  for (int i = 0; i < 9; i++) same = same && (cached[i] == d_in[i]);
  if (!same) {
    void* fn = nullptr;
    cudaDriverEntryPointQueryResult qr;
    cudaGetDriverEntryPoint("cuTensorMapEncodeTiled", &fn, cudaEnableDefault, &qr);
    EncFn enc = (EncFn)fn;
    void *p_ab = nullptr, *p_h = nullptr;
    cudaGetSymbolAddress(&p_ab, g_ab);
    cudaGetSymbolAddress(&p_h, g_h);
    make2d(enc, &maps.cr, d_in[1], 2048, 2048, 64, 128);
    make2d(enc, &maps.ci, d_in[2], 2048, 2048, 64, 128);
    make2d(enc, &maps.wr, d_in[3], 448, 448, 64, 56);
    make2d(enc, &maps.wi, d_in[4], 448, 448, 64, 56);
    make2d(enc, &maps.wg, d_in[6], 1792, 448, 64, 64);
    make2d(enc, &maps.wu, d_in[7], 1792, 448, 64, 64);
    make3d_half(enc, &maps.wd, d_in[8], 1792);
    make2d(enc, &maps.h, p_h, 1792, 2048, 64, 128);
    make3d_half(enc, &maps.ab, p_ab, 4096);
    make2d(enc, &maps.hs, p_h, 1792, 2048, 64, 16);
    make2d(enc, &maps.abs, p_ab, 448, 4096, 112, 16, false);
    for (int i = 0; i < 9; i++) cached[i] = d_in[i];
  }
  if (!attr_done) {
    cudaFuncSetAttribute(k1_kernel, cudaFuncAttributeMaxDynamicSharedMemorySize, K1_SMEM);
    cudaFuncSetAttribute(k2_kernel, cudaFuncAttributeMaxDynamicSharedMemorySize, K2_SMEM);
    attr_done = true;
  }
  PfPtrs pf;
  pf.wr = (const uint8_t*)d_in[3]; pf.wi = (const uint8_t*)d_in[4]; pf.wg = (const uint8_t*)d_in[6]; pf.wu = (const uint8_t*)d_in[7];
  pf.wd = (const uint8_t*)d_in[8]; pf.cr = (const uint8_t*)d_in[1]; pf.ci = (const uint8_t*)d_in[2];
  k1_kernel<<<128, 384, K1_SMEM>>>(maps.wr, maps.wi, maps.wg, maps.wu, maps.hs, maps.abs, (const __nv_bfloat16*)d_in[0], pf);

  cudaLaunchConfig_t cfg = {};
  cfg.gridDim = dim3(128); cfg.blockDim = dim3(384); cfg.dynamicSmemBytes = K2_SMEM; cfg.stream = cudaStreamPerThread;
  cudaLaunchAttribute at[1];
  at[0].id = cudaLaunchAttributeProgrammaticStreamSerialization;
  at[0].val.programmaticStreamSerializationAllowed = 1;
  cfg.attrs = at; cfg.numAttrs = 1;
  cudaLaunchKernelEx(&cfg, k2_kernel, maps.cr, maps.ci, maps.h, maps.ab, maps.wd, (const __nv_bfloat16*)d_in[0], (__nv_bfloat16*)d_out);
}
```

```cpp
#include <cuda_runtime.h>
#include <cuda_bf16.h>
#include <cuda.h>
#include <stdint.h>

namespace {

__device__ __align__(1024) __nv_bfloat16 g_ab[4096 * 448];
__device__ __align__(1024) __nv_bfloat16 g_h[2048 * 1792];
__device__ uint2 g_part[32 * 3 * 28 * 256];
__device__ __align__(1024) __nv_bfloat16 g_s[2048 * 448];
__device__ unsigned int g_flags[64];

#define DBG(k, i) do {} while (0)
#define DBGC(k, i) do {} while (0)

#define TIMEOUT(code) __trap()
#define SPIN_LIMIT (1 << 22)
__device__ __forceinline__ uint32_t s2u(const void* p) { return (uint32_t)__cvta_generic_to_shared(p); }
__device__ __forceinline__ void mbar_init(uint32_t b, int c) { asm volatile("mbarrier.init.shared::cta.b64 [%0], %1;" ::"r"(b), "r"(c)); }
__device__ __forceinline__ void mbar_expect(uint32_t b, uint32_t bytes) {
  asm volatile("mbarrier.arrive.expect_tx.shared::cta.b64 _, [%0], %1;" ::"r"(b), "r"(bytes) : "memory");
}
__device__ __forceinline__ void mbar_wait(uint32_t b, uint32_t ph, int code = 1) {
  uint32_t done = 0;
  int it = 0;
  while (true) {
    asm volatile("{.reg .pred p; mbarrier.try_wait.parity.shared::cta.b64 p, [%1], %2; selp.u32 %0,1,0,p;}" : "=r"(done) : "r"(b), "r"(ph) : "memory");
    if (done) break;
    if (++it > SPIN_LIMIT) { TIMEOUT(code); break; }
  }
}
__device__ __forceinline__ void mbar_arrive_cluster(uint32_t b, uint32_t cta) {
  uint32_t r;
  asm volatile("mapa.shared::cluster.u32 %0, %1, %2;" : "=r"(r) : "r"(b), "r"(cta));
  asm volatile("mbarrier.arrive.shared::cluster.b64 _, [%0];" ::"r"(r) : "memory");
}
__device__ __forceinline__ void tma2d(uint32_t dst, const CUtensorMap* m, int c0, int c1, uint32_t bar) {
  asm volatile("cp.async.bulk.tensor.2d.shared::cluster.global.mbarrier::complete_tx::bytes [%0], [%1, {%3,%4}], [%2];" ::"r"(dst), "l"(m), "r"(bar), "r"(c0), "r"(c1) : "memory");
}
__device__ __forceinline__ void tma2d_mc(uint32_t dst, const CUtensorMap* m, int c0, int c1, uint32_t bar, uint16_t mask) {
  asm volatile("cp.async.bulk.tensor.2d.shared::cluster.global.mbarrier::complete_tx::bytes.multicast::cluster [%0], [%1, {%3,%4}], [%2], %5;" ::"r"(dst), "l"(m), "r"(bar), "r"(c0), "r"(c1), "h"(mask) : "memory");
}
__device__ __forceinline__ void tma3d_mc(uint32_t dst, const CUtensorMap* m, int c0, int c1, int c2, uint32_t bar, uint16_t mask) {
  asm volatile("cp.async.bulk.tensor.3d.shared::cluster.global.mbarrier::complete_tx::bytes.multicast::cluster [%0], [%1, {%3,%4,%5}], [%2], %6;" ::"r"(dst), "l"(m), "r"(bar), "r"(c0), "r"(c1), "r"(c2), "h"(mask) : "memory");
}
__device__ __forceinline__ void tma2d_store(const CUtensorMap* m, uint32_t src, int c0, int c1) {
  asm volatile("cp.async.bulk.tensor.2d.global.shared::cta.bulk_group [%0, {%2,%3}], [%1];" ::"l"(m), "r"(src), "r"(c0), "r"(c1) : "memory");
}
__device__ __forceinline__ void bulk_commit() { asm volatile("cp.async.bulk.commit_group;" ::: "memory"); }
__device__ __forceinline__ void bulk_wait_read0() { asm volatile("cp.async.bulk.wait_group.read 0;" ::: "memory"); }
__device__ __forceinline__ void bulk_wait0() { asm volatile("cp.async.bulk.wait_group 0;" ::: "memory"); }
__device__ __forceinline__ void fence_async_smem() { asm volatile("fence.proxy.async.shared::cta;" ::: "memory"); }
__device__ __forceinline__ void prefetch_tmap(const CUtensorMap* m) { asm volatile("prefetch.tensormap [%0];" ::"l"(m) : "memory"); }
__device__ __forceinline__ void l2_prefetch(const void* p, uint32_t bytes) {
  asm volatile("cp.async.bulk.prefetch.L2.global [%0], %1;" ::"l"(p), "r"(bytes) : "memory");
}
__device__ __forceinline__ void cluster_arrive_relaxed() { asm volatile("barrier.cluster.arrive.relaxed.aligned;" ::: "memory"); }
__device__ __forceinline__ void cluster_wait() { asm volatile("barrier.cluster.wait.aligned;" ::: "memory"); }
__device__ __forceinline__ void wg_fence() { __syncwarp(); asm volatile("wgmma.fence.sync.aligned;" ::: "memory"); }
__device__ __forceinline__ void wg_commit() { asm volatile("wgmma.commit_group.sync.aligned;" ::: "memory"); }
template <int N> __device__ __forceinline__ void wg_wait() { __syncwarp(); asm volatile("wgmma.wait_group.sync.aligned %0;" ::"n"(N) : "memory"); }
__device__ __forceinline__ void named_bar(int id, int n) { asm volatile("bar.sync %0, %1;" ::"r"(id), "r"(n) : "memory"); }
__device__ __forceinline__ void named_arrive(int id, int n) { asm volatile("bar.arrive %0, %1;" ::"r"(id), "r"(n) : "memory"); }
template <int N> __device__ __forceinline__ void reg_inc() { asm volatile("setmaxnreg.inc.sync.aligned.u32 %0;" ::"n"(N)); }
template <int N> __device__ __forceinline__ void reg_dec() { asm volatile("setmaxnreg.dec.sync.aligned.u32 %0;" ::"n"(N)); }
__device__ __forceinline__ void pdl_wait() { asm volatile("griddepcontrol.wait;" ::: "memory"); }
__device__ __forceinline__ void pdl_launch() { asm volatile("griddepcontrol.launch_dependents;" ::: "memory"); }

__device__ __forceinline__ uint32_t make_desc(uint32_t addr, uint32_t lbo, uint32_t  ) {
  return ((addr & 0x3FFFF) >> 4) | ((lbo >> 4) << 16);
}
__device__ __forceinline__ void stmatrix_x4(uint32_t addr, uint32_t r0, uint32_t r1, uint32_t r2, uint32_t r3) {
  asm volatile("stmatrix.sync.aligned.m8n8.x4.shared.b16 [%0], {%1,%2,%3,%4};" ::"r"(addr), "r"(r0), "r"(r1), "r"(r2), "r"(r3) : "memory");
}
__device__ __forceinline__ uint4 lds128(uint32_t a) {
  uint4 v;
  asm volatile("ld.shared.v4.u32 {%0,%1,%2,%3}, [%4];" : "=r"(v.x), "=r"(v.y), "=r"(v.z), "=r"(v.w) : "r"(a) : "memory");
  return v;
}
__device__ __forceinline__ void sts128(uint32_t a, uint4 v) {
  asm volatile("st.shared.v4.u32 [%0], {%1,%2,%3,%4};" ::"r"(a), "r"(v.x), "r"(v.y), "r"(v.z), "r"(v.w) : "memory");
}
__device__ __forceinline__ void stg128(void* p, uint4 v) {
  asm volatile("st.global.v4.u32 [%0], {%1,%2,%3,%4};" ::"l"(p), "r"(v.x), "r"(v.y), "r"(v.z), "r"(v.w) : "memory");
}
__device__ __forceinline__ void cp_async16(uint32_t dst, const void* src) {
  asm volatile("cp.async.cg.shared.global [%0], [%1], 16;" ::"r"(dst), "l"(src) : "memory");
}
__device__ __forceinline__ void cp_async8(uint32_t dst, const void* src) {
  asm volatile("cp.async.ca.shared.global [%0], [%1], 8;" ::"r"(dst), "l"(src) : "memory");
}
__device__ __forceinline__ uint2 lds64(uint32_t a) {
  uint2 v;
  asm volatile("ld.shared.v2.u32 {%0,%1}, [%2];" : "=r"(v.x), "=r"(v.y) : "r"(a) : "memory");
  return v;
}
__device__ __forceinline__ void cp_async_wait_all() { asm volatile("cp.async.wait_all;" ::: "memory"); }
__device__ __forceinline__ uint32_t pack_bf16(float lo, float hi) {
  uint32_t r;
  asm("cvt.rn.bf16x2.f32 %0, %1, %2;" : "=r"(r) : "f"(hi), "f"(lo));
  return r;
}
__device__ __forceinline__ uint32_t hmul2_bf16(uint32_t a, uint32_t b) {
  uint32_t r;
  asm("mul.rn.bf16x2 %0, %1, %2;" : "=r"(r) : "r"(a), "r"(b));
  return r;
}
__device__ __forceinline__ uint32_t hsub2_bf16(uint32_t a, uint32_t b) {
  uint32_t r;
  asm("sub.rn.bf16x2 %0, %1, %2;" : "=r"(r) : "r"(a), "r"(b));
  return r;
}
__device__ __forceinline__ uint32_t hadd2_bf16(uint32_t a, uint32_t b) {
  uint32_t r;
  asm("add.rn.bf16x2 %0, %1, %2;" : "=r"(r) : "r"(a), "r"(b));
  return r;
}
__device__ __forceinline__ uint32_t hfma2_bf16(uint32_t a, uint32_t b, uint32_t c) {
  uint32_t r;
  asm("fma.rn.bf16x2 %0, %1, %2, %3;" : "=r"(r) : "r"(a), "r"(b), "r"(c));
  return r;
}
__device__ __forceinline__ bool mbar_test(uint32_t b, uint32_t ph) {
  uint32_t done;
  asm volatile("{.reg .pred p; mbarrier.test_wait.parity.shared::cta.b64 p, [%1], %2; selp.u32 %0,1,0,p;}" : "=r"(done) : "r"(b), "r"(ph) : "memory");
  return __all_sync(0xffffffffu, done != 0);
}
__device__ __forceinline__ uint4 ldg128_cg(const void* p) {
  uint4 v;
  asm volatile("ld.global.cg.v4.u32 {%0,%1,%2,%3}, [%4];" : "=r"(v.x), "=r"(v.y), "=r"(v.z), "=r"(v.w) : "l"(p) : "memory");
  return v;
}
__device__ __forceinline__ float bf_lo(uint32_t w) { return __uint_as_float(w << 16); }
__device__ __forceinline__ float bf_hi(uint32_t w) { return __uint_as_float(w & 0xffff0000u); }
__device__ __forceinline__ float rbf(float x) { return __bfloat162float(__float2bfloat16_rn(x)); }
__device__ __forceinline__ float ex2f(float x) { float r; asm("ex2.approx.ftz.f32 %0, %1;" : "=f"(r) : "f"(x)); return r; }
__device__ __forceinline__ float rcpf(float x) { float r; asm("rcp.approx.ftz.f32 %0, %1;" : "=f"(r) : "f"(x)); return r; }
__device__ __forceinline__ float tanhf_hw(float x) { float r; asm("tanh.approx.f32 %0, %1;" : "=f"(r) : "f"(x)); return r; }
__device__ __forceinline__ float gelu_tanh(float x) {
  const float c1 = 0.7978845608028654f;
  const float c2 = c1 * 0.044715f;
  const float t = tanhf_hw(x * fmaf(c2, x * x, c1));
  const float hx = 0.5f * x;
  return fmaf(hx, t, hx);
}
__device__ __forceinline__ float silu_f(float x) {
  const float hx = 0.5f * x;
  return fmaf(hx, tanhf_hw(hx), hx);
}

__device__ __forceinline__ void wgmma_n128_tb(float (&d)[64], uint32_t da, uint32_t db, int scale_d) {
  asm volatile(
    "{\n.reg .pred p;\n.reg .b64 da, db;\nsetp.ne.b32 p, %66, 0;\n"
    "mov.b64 da, {%64, 0x40000040};\nmov.b64 db, {%65, 0x40000040};\n"
    "wgmma.mma_async.sync.aligned.m64n128k16.f32.bf16.bf16 {%0, %1, %2, %3, %4, %5, %6, %7, %8, %9, %10, %11, %12, %13, %14, %15, %16, %17, %18, %19, %20, %21, %22, %23, %24, %25, %26, %27, %28, %29, %30, %31, %32, %33, %34, %35, %36, %37, %38, %39, %40, %41, %42, %43, %44, %45, %46, %47, %48, %49, %50, %51, %52, %53, %54, %55, %56, %57, %58, %59, %60, %61, %62, %63}, da, db, p, 1, 1, 0, 1;\n}\n"
    : "+f"(d[0]), "+f"(d[1]), "+f"(d[2]), "+f"(d[3]), "+f"(d[4]), "+f"(d[5]), "+f"(d[6]), "+f"(d[7]), "+f"(d[8]), "+f"(d[9]), "+f"(d[10]), "+f"(d[11]), "+f"(d[12]), "+f"(d[13]), "+f"(d[14]), "+f"(d[15]), "+f"(d[16]), "+f"(d[17]), "+f"(d[18]), "+f"(d[19]), "+f"(d[20]), "+f"(d[21]), "+f"(d[22]), "+f"(d[23]), "+f"(d[24]), "+f"(d[25]), "+f"(d[26]), "+f"(d[27]), "+f"(d[28]), "+f"(d[29]), "+f"(d[30]), "+f"(d[31]), "+f"(d[32]), "+f"(d[33]), "+f"(d[34]), "+f"(d[35]), "+f"(d[36]), "+f"(d[37]), "+f"(d[38]), "+f"(d[39]), "+f"(d[40]), "+f"(d[41]), "+f"(d[42]), "+f"(d[43]), "+f"(d[44]), "+f"(d[45]), "+f"(d[46]), "+f"(d[47]), "+f"(d[48]), "+f"(d[49]), "+f"(d[50]), "+f"(d[51]), "+f"(d[52]), "+f"(d[53]), "+f"(d[54]), "+f"(d[55]), "+f"(d[56]), "+f"(d[57]), "+f"(d[58]), "+f"(d[59]), "+f"(d[60]), "+f"(d[61]), "+f"(d[62]), "+f"(d[63])
    : "r"(da), "r"(db), "r"(scale_d));
}
__device__ __forceinline__ void wgmma_n128_tb_p(float (&d)[64], uint32_t da, uint32_t db, int scale_d, int enable) {
  asm volatile(
    "{\n.reg .pred p;\n.reg .b64 da, db;\nsetp.ne.b32 p, %66, 0;\n.reg .pred q;\nsetp.ne.b32 q, %67, 0;\n"
    "mov.b64 da, {%64, 0x40000040};\nmov.b64 db, {%65, 0x40000040};\n"
    "@q wgmma.mma_async.sync.aligned.m64n128k16.f32.bf16.bf16 {%0, %1, %2, %3, %4, %5, %6, %7, %8, %9, %10, %11, %12, %13, %14, %15, %16, %17, %18, %19, %20, %21, %22, %23, %24, %25, %26, %27, %28, %29, %30, %31, %32, %33, %34, %35, %36, %37, %38, %39, %40, %41, %42, %43, %44, %45, %46, %47, %48, %49, %50, %51, %52, %53, %54, %55, %56, %57, %58, %59, %60, %61, %62, %63}, da, db, p, 1, 1, 0, 1;\n}\n"
    : "+f"(d[0]), "+f"(d[1]), "+f"(d[2]), "+f"(d[3]), "+f"(d[4]), "+f"(d[5]), "+f"(d[6]), "+f"(d[7]), "+f"(d[8]), "+f"(d[9]), "+f"(d[10]), "+f"(d[11]), "+f"(d[12]), "+f"(d[13]), "+f"(d[14]), "+f"(d[15]), "+f"(d[16]), "+f"(d[17]), "+f"(d[18]), "+f"(d[19]), "+f"(d[20]), "+f"(d[21]), "+f"(d[22]), "+f"(d[23]), "+f"(d[24]), "+f"(d[25]), "+f"(d[26]), "+f"(d[27]), "+f"(d[28]), "+f"(d[29]), "+f"(d[30]), "+f"(d[31]), "+f"(d[32]), "+f"(d[33]), "+f"(d[34]), "+f"(d[35]), "+f"(d[36]), "+f"(d[37]), "+f"(d[38]), "+f"(d[39]), "+f"(d[40]), "+f"(d[41]), "+f"(d[42]), "+f"(d[43]), "+f"(d[44]), "+f"(d[45]), "+f"(d[46]), "+f"(d[47]), "+f"(d[48]), "+f"(d[49]), "+f"(d[50]), "+f"(d[51]), "+f"(d[52]), "+f"(d[53]), "+f"(d[54]), "+f"(d[55]), "+f"(d[56]), "+f"(d[57]), "+f"(d[58]), "+f"(d[59]), "+f"(d[60]), "+f"(d[61]), "+f"(d[62]), "+f"(d[63])
    : "r"(da), "r"(db), "r"(scale_d), "r"(enable));
}
__device__ __forceinline__ void wgmma_n112(float (&d)[56], uint32_t da, uint32_t db, int scale_d) {
  asm volatile(
    "{\n.reg .pred p;\n.reg .b64 da, db;\nsetp.ne.b32 p, %58, 0;\n"
    "mov.b64 da, {%56, 0x40000040};\nmov.b64 db, {%57, 0x40000040};\n"
    "wgmma.mma_async.sync.aligned.m64n112k16.f32.bf16.bf16 {%0, %1, %2, %3, %4, %5, %6, %7, %8, %9, %10, %11, %12, %13, %14, %15, %16, %17, %18, %19, %20, %21, %22, %23, %24, %25, %26, %27, %28, %29, %30, %31, %32, %33, %34, %35, %36, %37, %38, %39, %40, %41, %42, %43, %44, %45, %46, %47, %48, %49, %50, %51, %52, %53, %54, %55}, da, db, p, 1, 1, 0, 0;\n}\n"
    : "+f"(d[0]), "+f"(d[1]), "+f"(d[2]), "+f"(d[3]), "+f"(d[4]), "+f"(d[5]), "+f"(d[6]), "+f"(d[7]), "+f"(d[8]), "+f"(d[9]), "+f"(d[10]), "+f"(d[11]), "+f"(d[12]), "+f"(d[13]), "+f"(d[14]), "+f"(d[15]), "+f"(d[16]), "+f"(d[17]), "+f"(d[18]), "+f"(d[19]), "+f"(d[20]), "+f"(d[21]), "+f"(d[22]), "+f"(d[23]), "+f"(d[24]), "+f"(d[25]), "+f"(d[26]), "+f"(d[27]), "+f"(d[28]), "+f"(d[29]), "+f"(d[30]), "+f"(d[31]), "+f"(d[32]), "+f"(d[33]), "+f"(d[34]), "+f"(d[35]), "+f"(d[36]), "+f"(d[37]), "+f"(d[38]), "+f"(d[39]), "+f"(d[40]), "+f"(d[41]), "+f"(d[42]), "+f"(d[43]), "+f"(d[44]), "+f"(d[45]), "+f"(d[46]), "+f"(d[47]), "+f"(d[48]), "+f"(d[49]), "+f"(d[50]), "+f"(d[51]), "+f"(d[52]), "+f"(d[53]), "+f"(d[54]), "+f"(d[55])
    : "r"(da), "r"(db), "r"(scale_d));
}
__device__ __forceinline__ void wgmma_n224_tb(float (&d)[112], uint32_t da, uint32_t db, int scale_d) {
  asm volatile(
    "{\n.reg .pred p;\n.reg .b64 da, db;\nsetp.ne.b32 p, %114, 0;\n"
    "mov.b64 da, {%112, 0x40000040};\nmov.b64 db, {%113, 0x40000040};\n"
    "wgmma.mma_async.sync.aligned.m64n224k16.f32.bf16.bf16 {%0, %1, %2, %3, %4, %5, %6, %7, %8, %9, %10, %11, %12, %13, %14, %15, %16, %17, %18, %19, %20, %21, %22, %23, %24, %25, %26, %27, %28, %29, %30, %31, %32, %33, %34, %35, %36, %37, %38, %39, %40, %41, %42, %43, %44, %45, %46, %47, %48, %49, %50, %51, %52, %53, %54, %55, %56, %57, %58, %59, %60, %61, %62, %63, %64, %65, %66, %67, %68, %69, %70, %71, %72, %73, %74, %75, %76, %77, %78, %79, %80, %81, %82, %83, %84, %85, %86, %87, %88, %89, %90, %91, %92, %93, %94, %95, %96, %97, %98, %99, %100, %101, %102, %103, %104, %105, %106, %107, %108, %109, %110, %111}, da, db, p, 1, 1, 0, 1;\n}\n"
    : "+f"(d[0]), "+f"(d[1]), "+f"(d[2]), "+f"(d[3]), "+f"(d[4]), "+f"(d[5]), "+f"(d[6]), "+f"(d[7]), "+f"(d[8]), "+f"(d[9]), "+f"(d[10]), "+f"(d[11]), "+f"(d[12]), "+f"(d[13]), "+f"(d[14]), "+f"(d[15]), "+f"(d[16]), "+f"(d[17]), "+f"(d[18]), "+f"(d[19]), "+f"(d[20]), "+f"(d[21]), "+f"(d[22]), "+f"(d[23]), "+f"(d[24]), "+f"(d[25]), "+f"(d[26]), "+f"(d[27]), "+f"(d[28]), "+f"(d[29]), "+f"(d[30]), "+f"(d[31]), "+f"(d[32]), "+f"(d[33]), "+f"(d[34]), "+f"(d[35]), "+f"(d[36]), "+f"(d[37]), "+f"(d[38]), "+f"(d[39]), "+f"(d[40]), "+f"(d[41]), "+f"(d[42]), "+f"(d[43]), "+f"(d[44]), "+f"(d[45]), "+f"(d[46]), "+f"(d[47]), "+f"(d[48]), "+f"(d[49]), "+f"(d[50]), "+f"(d[51]), "+f"(d[52]), "+f"(d[53]), "+f"(d[54]), "+f"(d[55]), "+f"(d[56]), "+f"(d[57]), "+f"(d[58]), "+f"(d[59]), "+f"(d[60]), "+f"(d[61]), "+f"(d[62]), "+f"(d[63]), "+f"(d[64]), "+f"(d[65]), "+f"(d[66]), "+f"(d[67]), "+f"(d[68]), "+f"(d[69]), "+f"(d[70]), "+f"(d[71]), "+f"(d[72]), "+f"(d[73]), "+f"(d[74]), "+f"(d[75]), "+f"(d[76]), "+f"(d[77]), "+f"(d[78]), "+f"(d[79]), "+f"(d[80]), "+f"(d[81]), "+f"(d[82]), "+f"(d[83]), "+f"(d[84]), "+f"(d[85]), "+f"(d[86]), "+f"(d[87]), "+f"(d[88]), "+f"(d[89]), "+f"(d[90]), "+f"(d[91]), "+f"(d[92]), "+f"(d[93]), "+f"(d[94]), "+f"(d[95]), "+f"(d[96]), "+f"(d[97]), "+f"(d[98]), "+f"(d[99]), "+f"(d[100]), "+f"(d[101]), "+f"(d[102]), "+f"(d[103]), "+f"(d[104]), "+f"(d[105]), "+f"(d[106]), "+f"(d[107]), "+f"(d[108]), "+f"(d[109]), "+f"(d[110]), "+f"(d[111])
    : "r"(da), "r"(db), "r"(scale_d));
}

constexpr int K1_NS = 5;
constexpr int K1_A_BYTES = 7 * 16384;
constexpr int K1_B_OFF = K1_A_BYTES;
constexpr int K1_STG_OFF = K1_B_OFF + K1_NS * 16384;
constexpr int K1_BAR_OFF = K1_STG_OFF + 8 * 4096;
constexpr int K1_SMEM = K1_BAR_OFF + 256 + 1024;

struct K1Ctx {
  uint32_t sb, bar_full, rel0, rel1;
  uint32_t dA, dBk, dBn;
  bool lane0;
  const CUtensorMap* tm_hs;
  const CUtensorMap* tm_abs;
};
__device__ __forceinline__ void k1_release(const K1Ctx& c, int slot) {
  if (c.lane0) {
    asm volatile("mbarrier.arrive.shared::cluster.b64 _, [%0];" ::"r"(c.rel0 + 8 * slot) : "memory");
    asm volatile("mbarrier.arrive.shared::cluster.b64 _, [%0];" ::"r"(c.rel1 + 8 * slot) : "memory");
  }
}

__device__ __forceinline__ void k1_unit_ab(const K1Ctx& c, int warp, int lane, int mt, int j) {
  const uint32_t stg = c.sb + K1_STG_OFF + warp * 4096;
  const int wq = warp & 3;
  const int st_row = (lane & 7) + 8 * ((lane >> 3) & 1);
  const int st_chunk = lane >> 4;
  float acc[2][56];
  int slot = 0; uint32_t ph = 0;
#pragma unroll 1
  for (int kb = 0; kb < 7; kb++) {
    const int pslot = (slot == 0) ? K1_NS - 1 : slot - 1;
    mbar_wait(c.bar_full + 8 * slot, ph, 3);
    if (kb == 6) named_arrive(2, 256);
    if (kb == 0 && (threadIdx.x & 127) == 0) DBG(0, 4);
    if ((threadIdx.x & 127) == 0) DBGC(1, 46 + kb);
    wg_fence();
    const uint32_t da = c.dA + kb * 1024;
    const uint32_t db = c.dBk + slot * 1024;
#pragma unroll
    for (int k = 0; k < 4; k++) {
      wgmma_n112(acc[0], da + k * 2, db + k * 2, (kb | k) != 0);
      wgmma_n112(acc[1], da + 512 + k * 2, db + k * 2, (kb | k) != 0);
    }
    wg_commit();
    if (kb > 0) { wg_wait<1>(); k1_release(c, pslot); }
    if (++slot == K1_NS) { slot = 0; ph ^= 1; }
  }
  wg_wait<0>();
  k1_release(c, 6 % K1_NS);
  if ((threadIdx.x & 127) == 0) DBG(0, 5);
  const uint32_t sgn = (j < 4) ? 0u : 0x80008000u;
  const uint32_t sa = stg + st_row * 224 + st_chunk * 16;
  const int row0 = (j < 4 ? 0 : 2048) + mt * 128 + wq * 16;
#pragma unroll
  for (int h = 0; h < 2; h++) {
    if (h == 1) { if (c.lane0) bulk_wait_read0(); __syncwarp(); }
#pragma unroll
    for (int g = 0; g < 14; g += 2) {
      const float* a = &acc[h][4 * g];
      stmatrix_x4(sa + g * 16, pack_bf16(a[0], a[1]) ^ sgn, pack_bf16(a[2], a[3]) ^ sgn, pack_bf16(a[4], a[5]) ^ sgn, pack_bf16(a[6], a[7]) ^ sgn);
    }
    fence_async_smem();
    __syncwarp();
    if (c.lane0) { tma2d_store(c.tm_abs, stg, (j & 3) * 112, row0 + h * 64); bulk_commit(); }
  }
}

__device__ __forceinline__ void k1_unit_gu(const K1Ctx& c, int warp, int lane, int mt, int unit, int fb, int hsel) {
  const uint32_t stg = c.sb + K1_STG_OFF + warp * 4096;
  const int wq = warp & 3;
  const int full = (unit < 4);
  float acc[2][64];
  const uint32_t dA0 = c.dA + (full ? 0 : hsel * 512);
  int slot = (unit * 7) % K1_NS; uint32_t ph = ((unit * 7) / K1_NS) & 1;
  named_bar(2 + ((unit - 1) & 1), 256);
  if (full) {
#pragma unroll 1
    for (int kb = 0; kb < 7; kb++) {
      const int pslot = (slot == 0) ? K1_NS - 1 : slot - 1;
      mbar_wait(c.bar_full + 8 * slot, ph, 4);
      if (kb == 6) named_arrive(2 + (unit & 1), 256);
      if (kb == 0 && (threadIdx.x & 127) == 0) DBG(0, 4 + 3 * unit);
      wg_fence();
      const uint32_t da = dA0 + kb * 1024;
      const uint32_t db = c.dBn + slot * 1024;
#pragma unroll
      for (int k = 0; k < 4; k++) {
        wgmma_n128_tb(acc[0], da + k * 2, db + k * 128, (kb | k) != 0);
        wgmma_n128_tb(acc[1], da + 512 + k * 2, db + k * 128, (kb | k) != 0);
      }
      wg_commit();
      if (kb > 0) { wg_wait<1>(); k1_release(c, pslot); }
      if (++slot == K1_NS) { slot = 0; ph ^= 1; }
    }
  } else {
#pragma unroll 1
    for (int kb = 0; kb < 7; kb++) {
      const int pslot = (slot == 0) ? K1_NS - 1 : slot - 1;
      mbar_wait(c.bar_full + 8 * slot, ph, 5);
      if (kb == 0 && (threadIdx.x & 127) == 0) DBG(0, 4 + 3 * unit);
      wg_fence();
      const uint32_t da = dA0 + kb * 1024;
      const uint32_t db = c.dBn + slot * 1024;
#pragma unroll
      for (int k = 0; k < 4; k++) wgmma_n128_tb(acc[0], da + k * 2, db + k * 128, (kb | k) != 0);
      wg_commit();
      if (kb > 0) { wg_wait<1>(); k1_release(c, pslot); }
      if (++slot == K1_NS) { slot = 0; ph ^= 1; }
    }
  }
  wg_wait<0>();
  k1_release(c, (slot == 0) ? K1_NS - 1 : slot - 1);
  if ((threadIdx.x & 127) == 0) DBG(0, 5 + 3 * unit);
  const int st_row = (lane & 7) + 8 * ((lane >> 3) & 1);
  const int st_chunk = lane >> 4;
  const uint32_t sa = stg + st_row * 128;
  const int row0 = mt * 128 + (full ? 0 : hsel * 64) + wq * 16;
  if (c.lane0) bulk_wait_read0();
  __syncwarp();
#pragma unroll
  for (int h = 0; h < 2; h++) {
    if (h == 1 && !full) break;
#pragma unroll
    for (int g = 0; g < 8; g += 2) {
      uint32_t pk[4];
#pragma unroll
      for (int e = 0; e < 4; e++) {
        const int i = 4 * g + 2 * e;
        const uint32_t g2 = pack_bf16(acc[h][i], acc[h][i + 1]);
        const uint32_t u2 = pack_bf16(acc[h][32 + i], acc[h][32 + i + 1]);
        pk[e] = hmul2_bf16(pack_bf16(gelu_tanh(bf_lo(g2)), gelu_tanh(bf_hi(g2))), u2);
      }
      stmatrix_x4(sa + h * 2048 + (((g + st_chunk) ^ (st_row & 7)) * 16), pk[0], pk[1], pk[2], pk[3]);
    }
    fence_async_smem();
    __syncwarp();
    if (c.lane0) { tma2d_store(c.tm_hs, stg + h * 2048, fb * 64, row0 + h * 64); bulk_commit(); }
  }
}

struct PfPtrs { const uint8_t* wr; const uint8_t* wi; const uint8_t* wg; const uint8_t* wu; const uint8_t* wd; const uint8_t* cr; const uint8_t* ci; };

__global__ void __cluster_dims__(2, 1, 1) __launch_bounds__(384, 1)
k1_kernel(const __grid_constant__ CUtensorMap tm_wr, const __grid_constant__ CUtensorMap tm_wi,
          const __grid_constant__ CUtensorMap tm_wg, const __grid_constant__ CUtensorMap tm_wu,
          const __grid_constant__ CUtensorMap tm_hs, const __grid_constant__ CUtensorMap tm_abs,
          const __nv_bfloat16* __restrict__ x, const PfPtrs pf) {
  extern __shared__ uint8_t smem_raw[];
  const uint32_t sb = (s2u(smem_raw) + 1023) & ~1023u;
  const int tid = threadIdx.x, warp = tid >> 5, lane = tid & 31;
  uint32_t rank;
  asm volatile("mov.u32 %0, %%cluster_ctarank;" : "=r"(rank));
  const int cid = blockIdx.x >> 1;
  const int p = cid >> 3, j = cid & 7;
  const int mt = 2 * p + (int)rank;
  const uint32_t bar_full = sb + K1_BAR_OFF;
  const uint32_t bar_empty = bar_full + 8 * K1_NS;
  const int fb_base = 7 * (j >> 1);
  const int fb0 = fb_base + ((j & 1) ? 4 : 0);
  const int fbh = fb_base + 3;
  const CUtensorMap* tw = (j < 4) ? &tm_wr : &tm_wi;
  const CUtensorMap* tgu = rank ? &tm_wu : &tm_wg;

  if (tid == 0) DBG(0, 0);
  if (tid == 256) {
    for (int i = 0; i < K1_NS; i++) { mbar_init(bar_full + 8 * i, 1); mbar_init(bar_empty + 8 * i, 8); }
    asm volatile("fence.mbarrier_init.release.cluster;" ::: "memory");
    prefetch_tmap(tw);
    prefetch_tmap(tgu);
    prefetch_tmap(&tm_abs);
    prefetch_tmap(&tm_hs);
    if (blockIdx.x < 64) g_flags[blockIdx.x] = 0;
  }
  __syncwarp();
  cluster_arrive_relaxed();
  pdl_launch();

  if (warp >= 8) {
    reg_dec<40>();
    cluster_wait();
    if (tid == 256) {
      int slot = 0; uint32_t ph = 0;
      int kb = 0, unit = 0;
#pragma unroll 1
      for (int s = 0; s < 35; s++) {
        if (s >= K1_NS) mbar_wait(bar_empty + 8 * slot, ph ^ 1, 2);
        DBG(0, 20 + s);
        const uint32_t dst = sb + K1_B_OFF + slot * 16384;
        if (unit == 0) {
          mbar_expect(bar_full + 8 * slot, 14336);
          tma2d_mc(dst + rank * 7168, tw, kb * 64, (j & 3) * 112 + rank * 56, bar_full + 8 * slot, 3);
        } else {
          const int fb = (unit == 4) ? fbh : (fb0 + unit - 1);
          mbar_expect(bar_full + 8 * slot, 16384);
          tma2d_mc(dst + rank * 8192, tgu, fb * 64, kb * 64, bar_full + 8 * slot, 3);
        }
        if (++kb == 7) { kb = 0; unit++; }
        if (++slot == K1_NS) { slot = 0; ph ^= 1; }
      }
    } else if (tid == 288) {
      const int b = blockIdx.x;
      l2_prefetch(pf.wg + b * 12544, 12544);
      l2_prefetch(pf.wu + b * 12544, 12544);
    }
  } else {
    reg_inc<232>();
    const int wg = warp >> 2;
    {
      const int c = lane & 7;
      const int r0 = warp * 16 + (lane >> 3);
      const uint4* src = reinterpret_cast<const uint4*>(x + (size_t)(mt * 128 + r0) * 448) + c;
      uint4 nx[7];
#pragma unroll
      for (int b = 0; b < 7; b++)
        asm volatile("ld.global.nc.v4.u32 {%0,%1,%2,%3}, [%4];" : "=r"(nx[b].x), "=r"(nx[b].y), "=r"(nx[b].z), "=r"(nx[b].w) : "l"(src + b * 8) : "memory");
#pragma unroll
      for (int pass = 1; pass < 4; pass++) asm volatile("prefetch.global.L2 [%0];" ::"l"(src + pass * 4 * 56 + c * 7 - c) : "memory");
#pragma unroll 1
      for (int pass = 0; pass < 4; pass++) {
        uint4 v[7];
#pragma unroll
        for (int b = 0; b < 7; b++) v[b] = nx[b];
        if (pass < 3) {
          const uint4* s2 = src + (pass + 1) * 4 * 56;
#pragma unroll
          for (int b = 0; b < 7; b++)
            asm volatile("ld.global.nc.v4.u32 {%0,%1,%2,%3}, [%4];" : "=r"(nx[b].x), "=r"(nx[b].y), "=r"(nx[b].z), "=r"(nx[b].w) : "l"(s2 + b * 8) : "memory");
        }
        float s0 = 0.f, s1 = 0.f, s2v = 0.f, s3 = 0.f;
#pragma unroll
        for (int b = 0; b < 7; b++) {
          s0 += bf_lo(v[b].x) + bf_hi(v[b].x); s1 += bf_lo(v[b].y) + bf_hi(v[b].y);
          s2v += bf_lo(v[b].z) + bf_hi(v[b].z); s3 += bf_lo(v[b].w) + bf_hi(v[b].w);
        }
        float m = (s0 + s1) + (s2v + s3);
        m += __shfl_xor_sync(0xffffffffu, m, 1);
        m += __shfl_xor_sync(0xffffffffu, m, 2);
        m += __shfl_xor_sync(0xffffffffu, m, 4);
        m *= (1.0f / 448.0f);
        float q0 = 0.f, q1 = 0.f, q2 = 0.f, q3 = 0.f;
#pragma unroll
        for (int b = 0; b < 7; b++) {
          float d;
          d = bf_lo(v[b].x) - m; q0 = fmaf(d, d, q0); d = bf_hi(v[b].x) - m; q1 = fmaf(d, d, q1);
          d = bf_lo(v[b].y) - m; q2 = fmaf(d, d, q2); d = bf_hi(v[b].y) - m; q3 = fmaf(d, d, q3);
          d = bf_lo(v[b].z) - m; q0 = fmaf(d, d, q0); d = bf_hi(v[b].z) - m; q1 = fmaf(d, d, q1);
          d = bf_lo(v[b].w) - m; q2 = fmaf(d, d, q2); d = bf_hi(v[b].w) - m; q3 = fmaf(d, d, q3);
        }
        float q = (q0 + q1) + (q2 + q3);
        q += __shfl_xor_sync(0xffffffffu, q, 1);
        q += __shfl_xor_sync(0xffffffffu, q, 2);
        q += __shfl_xor_sync(0xffffffffu, q, 4);
        const float var_b = rbf(q * (1.0f / 448.0f));
        const float den = rbf(sqrtf(rbf(var_b + 1e-5f)));
        const float ri = 1.0f / den;
        const float rih = rbf(ri);
        const uint32_t rhi2 = pack_bf16(rih, rih), rlo2 = pack_bf16(ri - rih, ri - rih);
        const uint32_t m2 = pack_bf16(m, m);
        const int r = r0 + pass * 4;
        const uint32_t a0 = sb + r * 128 + ((c ^ (r & 7)) * 16);
#pragma unroll
        for (int b = 0; b < 7; b++) {
          uint32_t w4[4] = {v[b].x, v[b].y, v[b].z, v[b].w};
#pragma unroll
          for (int qq = 0; qq < 4; qq++) {
            const uint32_t dw = hsub2_bf16(w4[qq], m2);
            w4[qq] = hfma2_bf16(dw, rhi2, hmul2_bf16(dw, rlo2));
          }
          sts128(a0 + b * 16384, make_uint4(w4[0], w4[1], w4[2], w4[3]));
        }
      }
    }
    if (lane == 0) DBG(0, 59 + (warp & 3));
    asm volatile("fence.proxy.async.shared::cta;" ::: "memory");
    named_bar(1, 256);
    cluster_wait();
    if (tid == 0) DBG(0, 3);

    K1Ctx c;
    c.sb = sb; c.bar_full = bar_full; c.lane0 = (lane == 0);
    asm volatile("mapa.shared::cluster.u32 %0, %1, %2;" : "=r"(c.rel0) : "r"(bar_empty), "r"(0));
    asm volatile("mapa.shared::cluster.u32 %0, %1, %2;" : "=r"(c.rel1) : "r"(bar_empty), "r"(1));
    c.tm_hs = &tm_hs; c.tm_abs = &tm_abs;
    c.dA = make_desc(sb, 16, 1024);
    c.dBk = make_desc(sb + K1_B_OFF, 16, 1024);
    c.dBn = make_desc(sb + K1_B_OFF, 8192, 1024);
    if (wg == 0) {
      k1_unit_ab(c, warp, lane, mt, j);
      if (tid == 0) DBG(0, 6);
    }
#pragma unroll 1
    for (int unit = 2 - wg; unit < 5; unit += 2) {
      k1_unit_gu(c, warp, lane, mt, unit, (unit == 4) ? fbh : fb0 + unit - 1, j & 1);
      if ((tid & 127) == 0) DBG(0, 6 + 3 * unit);
    }
    if (lane == 0) bulk_wait0();
  }
  __syncwarp();
  cluster_arrive_relaxed();
  cluster_wait();
}

constexpr int K2_NS = 4;
constexpr int K2_STAGE = 16384 + 32768;
constexpr int K2_BAR_OFF = K2_NS * K2_STAGE;
constexpr int K2_SMEM = K2_BAR_OFF + 256 + 1024;
constexpr int K2_PITCH = 464;

__device__ __forceinline__ void spin_flag(const unsigned int* flag, unsigned int target) {
  int it = 0;
  while (true) {
    unsigned int v;
    asm volatile("ld.acquire.gpu.global.u32 %0, [%1];" : "=r"(v) : "l"(flag) : "memory");
    if (v >= target) break;
    if (++it > SPIN_LIMIT) { TIMEOUT(20); break; }
  }
}

__global__ void __cluster_dims__(2, 1, 1) __launch_bounds__(384, 1)
k2_kernel(const __grid_constant__ CUtensorMap tm_cr, const __grid_constant__ CUtensorMap tm_ci, const __grid_constant__ CUtensorMap tm_h,
          const __grid_constant__ CUtensorMap tm_ab, const __grid_constant__ CUtensorMap tm_wd,
          const __nv_bfloat16* __restrict__ x, __nv_bfloat16* __restrict__ out) {
  extern __shared__ uint8_t smem_raw[];
  const uint32_t sb = (s2u(smem_raw) + 1023) & ~1023u;
  const int tid = threadIdx.x, warp = tid >> 5, lane = tid & 31;
  uint32_t rank;
  asm volatile("mov.u32 %0, %%cluster_ctarank;" : "=r"(rank));
  const int cid = blockIdx.x >> 1;
  const int q = cid & 3, n = (cid >> 2) & 1, p = cid >> 3;
  const int mt = 2 * p + (int)rank;
  const int tile = mt * 2 + n;
  const uint32_t bar_full = sb + K2_BAR_OFF;
  const uint32_t bar_empty = bar_full + 8 * K2_NS;
  const int g0 = (q == 0) ? 0 : (q == 1 ? 22 : (q == 2 ? 43 : 64));
  const int nkb = (q == 0) ? 22 : (q == 3 ? 28 : 21);

  if (tid == 0) DBG(1, 0);
  if (tid == 256) {
    for (int i = 0; i < K2_NS; i++) { mbar_init(bar_full + 8 * i, 1); mbar_init(bar_empty + 8 * i, 16); }
    asm volatile("fence.mbarrier_init.release.cluster;" ::: "memory");
    if (q == 3) { prefetch_tmap(&tm_h); prefetch_tmap(&tm_wd); }
    else { prefetch_tmap(&tm_cr); prefetch_tmap(&tm_ci); prefetch_tmap(&tm_ab); }
  }
  __syncwarp();
  cluster_arrive_relaxed();
  cluster_wait();

  if (warp >= 8) {
    reg_dec<40>();
    if (tid == 256) {
      const CUtensorMap* tb = (q < 3) ? &tm_ab : &tm_wd;
      const int kb0 = (q < 3) ? g0 : 0;
      int slot = 0; uint32_t ph = 0;
#pragma unroll 1
      for (int it = 0; it < nkb + K2_NS; it++) {
        const int s = (it < K2_NS) ? it : it - K2_NS;
        const bool pre = (it < K2_NS), post = (!pre && s < K2_NS);
        if (it == K2_NS) { pdl_wait(); DBG(1, 31); slot = 0; }
        if (!pre && !post) mbar_wait(bar_empty + 8 * slot, ph, 10);
        const uint32_t dst = sb + slot * K2_STAGE;
        const uint32_t fb = bar_full + 8 * slot;
        if (!post) mbar_expect(fb, K2_STAGE);
        const bool doA = pre ? (q < 3) : (post ? (q == 3) : true);
        const bool doB = pre ? (q == 3) : (post ? (q < 3) : true);
        if (doA) {
          const int g = g0 + s;
          const CUtensorMap* ta = (g < 32) ? &tm_cr : (g < 64 ? &tm_ci : &tm_h);
          tma2d(dst, ta, (g & 31) * 64 + ((g >= 96) ? 2048 : 0), mt * 128, fb);
        }
        if (doB) {
          tma3d_mc(dst + 16384 + (2 * rank) * 8192, tb, (2 * rank) * 64, n, (kb0 + s) * 64, fb, 3);
          tma3d_mc(dst + 16384 + (2 * rank + 1) * 8192, tb, (2 * rank + 1) * 64, n, (kb0 + s) * 64, fb, 3);
        }
        if (++slot == K2_NS) { slot = 0; if (!pre && !post) ph ^= 1; }
      }
    }
  } else {
    reg_inc<232>();
    const int wg = warp >> 2;
    float acc[112];
    uint32_t rel0, rel1;
    asm volatile("mapa.shared::cluster.u32 %0, %1, %2;" : "=r"(rel0) : "r"(bar_empty), "r"(0));
    asm volatile("mapa.shared::cluster.u32 %0, %1, %2;" : "=r"(rel1) : "r"(bar_empty), "r"(1));
    const uint32_t dA0 = make_desc(sb + wg * 8192, 16, 1024);
    const uint32_t dB0 = make_desc(sb + 16384, 8192, 1024);
    int slot = 0; uint32_t ph = 0;
#pragma unroll 1
    for (int s = 0; s < nkb; s++) {
      mbar_wait(bar_full + 8 * slot, ph, 11);
      if (tid == 0) DBG(1, 1 + s);
      if (tid == 0 && (s == 5 || s == 15)) DBGC(1, 53 + (s == 15));
      if (tid == 0 && (s == 23 || s == 27)) DBGC(1, 55 + (s == 27));
      wg_fence();
      const uint32_t da = dA0 + slot * (K2_STAGE / 16);
      const uint32_t db = dB0 + slot * (K2_STAGE / 16);
#pragma unroll
      for (int k = 0; k < 4; k++) wgmma_n224_tb(acc, da + k * 2, db + k * 128, (s | k) != 0);
      wg_commit();
      if (s > 0) {
        wg_wait<1>();
        const int ps = (slot == 0) ? K2_NS - 1 : slot - 1;
        if (lane == 0) {
          asm volatile("mbarrier.arrive.shared::cluster.b64 _, [%0];" ::"r"(rel0 + 8 * ps) : "memory");
          asm volatile("mbarrier.arrive.shared::cluster.b64 _, [%0];" ::"r"(rel1 + 8 * ps) : "memory");
        }
      }
      if (++slot == K2_NS) { slot = 0; ph ^= 1; }
    }
    wg_wait<0>();
    pdl_wait();
    if (tid == 0) DBG(1, 29);
    if (q < 3) {
      const int G0 = q * 10, NG = (q == 2) ? 8 : 10;
      uint2* part = g_part + (size_t)tile * (3 * 28 * 256) + tid;
      const uint32_t sl = sb + tid * 16;
      named_bar(1, 256);
#pragma unroll
      for (int g = 0; g < 28; g++) {
        if ((unsigned)(g - G0) < (unsigned)NG)
          sts128(sl + (g - G0) * 4096, make_uint4(__float_as_uint(acc[4 * g]), __float_as_uint(acc[4 * g + 1]), __float_as_uint(acc[4 * g + 2]), __float_as_uint(acc[4 * g + 3])));
        else
          part[(q * 28 + g) * 256] = make_uint2(pack_bf16(acc[4 * g], acc[4 * g + 1]), pack_bf16(acc[4 * g + 2], acc[4 * g + 3]));
      }
      __threadfence();
      named_bar(1, 256);
      if (tid == 0) DBG(1, 62);
      if (tid == 0) { atomicAdd(&g_flags[tile], 1u); spin_flag(&g_flags[tile], 3u); }
      named_bar(1, 256);
      if (tid == 0) DBG(1, 30);
      const uint2* pa = part + (((q + 1) % 3) * 28 + G0) * 256;
      const uint2* pb = part + (((q + 2) % 3) * 28 + G0) * 256;
      const uint32_t s2 = sb + 49152 + tid * 16;
#pragma unroll 1
      for (int g = 0; g < NG; g++) {
        cp_async8(s2 + g * 4096, pa + g * 256);
        cp_async8(s2 + g * 4096 + 8, pb + g * 256);
      }
      cp_async_wait_all();
      uint32_t* sp = reinterpret_cast<uint32_t*>(g_s + (size_t)(mt * 128 + warp * 16 + (lane >> 2)) * 448 + n * 224 + (lane & 3) * 2) + G0 * 4;
#pragma unroll 2
      for (int g = 0; g < NG; g++) {
        const uint4 a = lds128(sl + g * 4096), b = lds128(s2 + g * 4096);
        sp[g * 4] = pack_bf16(__uint_as_float(a.x) + bf_lo(b.x) + bf_lo(b.z), __uint_as_float(a.y) + bf_hi(b.x) + bf_hi(b.z));
        sp[g * 4 + 8 * 224] = pack_bf16(__uint_as_float(a.z) + bf_lo(b.y) + bf_lo(b.w), __uint_as_float(a.w) + bf_hi(b.y) + bf_hi(b.w));
      }
      __threadfence();
      named_bar(1, 256);
      if (tid == 0) atomicAdd(&g_flags[32 + tile], 1u);
    } else {
      named_bar(1, 256);
      const uint32_t stg = sb + warp * 16 * K2_PITCH;
      const int lc = (lane < 28) ? lane : 27;
      const size_t gbase = (size_t)(mt * 128 + warp * 16) * 448 + n * 224 + lc * 8;
      const uint32_t lp = stg + lc * 16;
      const uint32_t xs = sb + 65536 + warp * 16384 + lane * 16;
#pragma unroll 1
      for (int t = 0; t < 16; t++) cp_async16(xs + t * 512, x + gbase + t * 448);
      if (lane == 0) spin_flag(&g_flags[32 + tile], 3u);
      __syncwarp();
      if (tid == 0) DBG(1, 30);
#pragma unroll 1
      for (int t = 0; t < 16; t++) cp_async16(xs + 8192 + t * 512, g_s + gbase + t * 448);
      const int st_row = (lane & 7) + 8 * ((lane >> 3) & 1);
      const uint32_t sa = stg + st_row * K2_PITCH + (lane >> 4) * 16;
#pragma unroll
      for (int g = 0; g < 28; g += 2) {
        uint32_t pk[4];
#pragma unroll
        for (int e = 0; e < 4; e++) {
          const uint32_t f2 = pack_bf16(acc[4 * g + 2 * e], acc[4 * g + 2 * e + 1]);
          pk[e] = pack_bf16(silu_f(bf_lo(f2)), silu_f(bf_hi(f2)));
        }
        stmatrix_x4(sa + g * 16, pk[0], pk[1], pk[2], pk[3]);
      }
      if (tid == 0) DBG(1, 62);
      __syncwarp();
      cp_async_wait_all();
#pragma unroll 4
      for (int t = 0; t < 16; t++) {
        const uint4 gv = lds128(lp + t * K2_PITCH), xx = lds128(xs + t * 512), ss = lds128(xs + 8192 + t * 512);
        uint4 o;
        o.x = hadd2_bf16(xx.x, hmul2_bf16(ss.x, gv.x));
        o.y = hadd2_bf16(xx.y, hmul2_bf16(ss.y, gv.y));
        o.z = hadd2_bf16(xx.z, hmul2_bf16(ss.z, gv.z));
        o.w = hadd2_bf16(xx.w, hmul2_bf16(ss.w, gv.w));
        if (lane < 28) stg128(out + gbase + t * 448, o);
      }
    }
    if (tid == 0) DBG(1, 63);
  }
  __syncwarp();
  cluster_arrive_relaxed();
  cluster_wait();
}

typedef CUresult (*EncFn)(CUtensorMap*, CUtensorMapDataType, cuuint32_t, void*, const cuuint64_t*, const cuuint64_t*, const cuuint32_t*,
                          const cuuint32_t*, CUtensorMapInterleave, CUtensorMapSwizzle, CUtensorMapL2promotion, CUtensorMapFloatOOBfill);

void make2d(EncFn enc, CUtensorMap* tm, const void* ptr, uint64_t cols, uint64_t rows, uint32_t bc, uint32_t br, bool swz = true) {
  cuuint64_t gd[2] = {cols, rows};
  cuuint64_t gs[1] = {cols * 2};
  cuuint32_t bd[2] = {bc, br};
  cuuint32_t es[2] = {1, 1};
  enc(tm, CU_TENSOR_MAP_DATA_TYPE_BFLOAT16, 2, const_cast<void*>(ptr), gd, gs, bd, es, CU_TENSOR_MAP_INTERLEAVE_NONE,
      swz ? CU_TENSOR_MAP_SWIZZLE_128B : CU_TENSOR_MAP_SWIZZLE_NONE, CU_TENSOR_MAP_L2_PROMOTION_L2_128B, CU_TENSOR_MAP_FLOAT_OOB_FILL_NONE);
}
void make3d_half(EncFn enc, CUtensorMap* tm, const void* ptr, uint64_t rows) {
  cuuint64_t gd[3] = {224, 2, rows};
  cuuint64_t gs[2] = {448, 896};
  cuuint32_t bd[3] = {64, 1, 64};
  cuuint32_t es[3] = {1, 1, 1};
  enc(tm, CU_TENSOR_MAP_DATA_TYPE_BFLOAT16, 3, const_cast<void*>(ptr), gd, gs, bd, es, CU_TENSOR_MAP_INTERLEAVE_NONE,
      CU_TENSOR_MAP_SWIZZLE_128B, CU_TENSOR_MAP_L2_PROMOTION_L2_128B, CU_TENSOR_MAP_FLOAT_OOB_FILL_NONE);
}

struct Maps { CUtensorMap wr, wi, wg, wu, cr, ci, h, ab, wd, hs, abs; };

}

extern "C" void kernel_launch(void* const* d_in, const int* in_sizes, int n_in, void* d_out, int out_size) {
  (void)in_sizes; (void)n_in; (void)out_size;
  static Maps maps;
  static const void* cached[9] = {nullptr};
  static bool attr_done = false;
  bool same = true;
  for (int i = 0; i < 9; i++) same = same && (cached[i] == d_in[i]);
  if (!same) {
    void* fn = nullptr;
    cudaDriverEntryPointQueryResult qr;
    cudaGetDriverEntryPoint("cuTensorMapEncodeTiled", &fn, cudaEnableDefault, &qr);
    EncFn enc = (EncFn)fn;
    void *p_ab = nullptr, *p_h = nullptr;
    cudaGetSymbolAddress(&p_ab, g_ab);
    cudaGetSymbolAddress(&p_h, g_h);
    make2d(enc, &maps.cr, d_in[1], 2048, 2048, 64, 128);
    make2d(enc, &maps.ci, d_in[2], 2048, 2048, 64, 128);
    make2d(enc, &maps.wr, d_in[3], 448, 448, 64, 56);
    make2d(enc, &maps.wi, d_in[4], 448, 448, 64, 56);
    make2d(enc, &maps.wg, d_in[6], 1792, 448, 64, 64);
    make2d(enc, &maps.wu, d_in[7], 1792, 448, 64, 64);
    make3d_half(enc, &maps.wd, d_in[8], 1792);
    make2d(enc, &maps.h, p_h, 1792, 2048, 64, 128);
    make3d_half(enc, &maps.ab, p_ab, 4096);
    make2d(enc, &maps.hs, p_h, 1792, 2048, 64, 16);
    make2d(enc, &maps.abs, p_ab, 448, 4096, 112, 16, false);
    for (int i = 0; i < 9; i++) cached[i] = d_in[i];
  }
  if (!attr_done) {
    cudaFuncSetAttribute(k1_kernel, cudaFuncAttributeMaxDynamicSharedMemorySize, K1_SMEM);
    cudaFuncSetAttribute(k2_kernel, cudaFuncAttributeMaxDynamicSharedMemorySize, K2_SMEM);
    attr_done = true;
  }
  PfPtrs pf;
  pf.wr = (const uint8_t*)d_in[3]; pf.wi = (const uint8_t*)d_in[4]; pf.wg = (const uint8_t*)d_in[6]; pf.wu = (const uint8_t*)d_in[7];
  pf.wd = (const uint8_t*)d_in[8]; pf.cr = (const uint8_t*)d_in[1]; pf.ci = (const uint8_t*)d_in[2];
  k1_kernel<<<128, 384, K1_SMEM>>>(maps.wr, maps.wi, maps.wg, maps.wu, maps.hs, maps.abs, (const __nv_bfloat16*)d_in[0], pf);

  cudaLaunchConfig_t cfg = {};
  cfg.gridDim = dim3(128); cfg.blockDim = dim3(384); cfg.dynamicSmemBytes = K2_SMEM; cfg.stream = cudaStreamPerThread;
  cudaLaunchAttribute at[1];
  at[0].id = cudaLaunchAttributeProgrammaticStreamSerialization;
  at[0].val.programmaticStreamSerializationAllowed = 1;
  cfg.attrs = at; cfg.numAttrs = 1;
  cudaLaunchKernelEx(&cfg, k2_kernel, maps.cr, maps.ci, maps.h, maps.ab, maps.wd, (const __nv_bfloat16*)d_in[0], (__nv_bfloat16*)d_out);
}
```

```cpp
#include <cuda_runtime.h>
#include <cuda_bf16.h>
#include <cuda.h>
#include <stdint.h>

namespace {

__device__ __align__(1024) __nv_bfloat16 g_ab[4096 * 448];
__device__ __align__(1024) __nv_bfloat16 g_h[2048 * 1792];
__device__ uint2 g_part[32 * 3 * 28 * 256];
__device__ __align__(1024) __nv_bfloat16 g_s[2048 * 448];
__device__ unsigned int g_flags[64];

#define DBG(k, i) do {} while (0)
#define DBGC(k, i) do {} while (0)

#define TIMEOUT(code) __trap()
#define SPIN_LIMIT (1 << 22)
__device__ __forceinline__ uint32_t s2u(const void* p) { return (uint32_t)__cvta_generic_to_shared(p); }
__device__ __forceinline__ void mbar_init(uint32_t b, int c) { asm volatile("mbarrier.init.shared::cta.b64 [%0], %1;" ::"r"(b), "r"(c)); }
__device__ __forceinline__ void mbar_expect(uint32_t b, uint32_t bytes) {
  asm volatile("mbarrier.arrive.expect_tx.shared::cta.b64 _, [%0], %1;" ::"r"(b), "r"(bytes) : "memory");
}
__device__ __forceinline__ void mbar_wait(uint32_t b, uint32_t ph, int code = 1) {
  uint32_t done = 0;
  int it = 0;
  while (true) {
    asm volatile("{.reg .pred p; mbarrier.try_wait.parity.shared::cta.b64 p, [%1], %2; selp.u32 %0,1,0,p;}" : "=r"(done) : "r"(b), "r"(ph) : "memory");
    if (done) break;
    if (++it > SPIN_LIMIT) { TIMEOUT(code); break; }
  }
}
__device__ __forceinline__ void mbar_arrive_cluster(uint32_t b, uint32_t cta) {
  uint32_t r;
  asm volatile("mapa.shared::cluster.u32 %0, %1, %2;" : "=r"(r) : "r"(b), "r"(cta));
  asm volatile("mbarrier.arrive.shared::cluster.b64 _, [%0];" ::"r"(r) : "memory");
}
__device__ __forceinline__ void tma2d(uint32_t dst, const CUtensorMap* m, int c0, int c1, uint32_t bar) {
  asm volatile("cp.async.bulk.tensor.2d.shared::cluster.global.mbarrier::complete_tx::bytes [%0], [%1, {%3,%4}], [%2];" ::"r"(dst), "l"(m), "r"(bar), "r"(c0), "r"(c1) : "memory");
}
__device__ __forceinline__ void tma2d_mc(uint32_t dst, const CUtensorMap* m, int c0, int c1, uint32_t bar, uint16_t mask) {
  asm volatile("cp.async.bulk.tensor.2d.shared::cluster.global.mbarrier::complete_tx::bytes.multicast::cluster [%0], [%1, {%3,%4}], [%2], %5;" ::"r"(dst), "l"(m), "r"(bar), "r"(c0), "r"(c1), "h"(mask) : "memory");
}
__device__ __forceinline__ void tma3d_mc(uint32_t dst, const CUtensorMap* m, int c0, int c1, int c2, uint32_t bar, uint16_t mask) {
  asm volatile("cp.async.bulk.tensor.3d.shared::cluster.global.mbarrier::complete_tx::bytes.multicast::cluster [%0], [%1, {%3,%4,%5}], [%2], %6;" ::"r"(dst), "l"(m), "r"(bar), "r"(c0), "r"(c1), "r"(c2), "h"(mask) : "memory");
}
__device__ __forceinline__ void tma2d_store(const CUtensorMap* m, uint32_t src, int c0, int c1) {
  asm volatile("cp.async.bulk.tensor.2d.global.shared::cta.bulk_group [%0, {%2,%3}], [%1];" ::"l"(m), "r"(src), "r"(c0), "r"(c1) : "memory");
}
__device__ __forceinline__ void bulk_commit() { asm volatile("cp.async.bulk.commit_group;" ::: "memory"); }
__device__ __forceinline__ void bulk_wait_read0() { asm volatile("cp.async.bulk.wait_group.read 0;" ::: "memory"); }
__device__ __forceinline__ void bulk_wait0() { asm volatile("cp.async.bulk.wait_group 0;" ::: "memory"); }
__device__ __forceinline__ void fence_async_smem() { asm volatile("fence.proxy.async.shared::cta;" ::: "memory"); }
__device__ __forceinline__ void prefetch_tmap(const CUtensorMap* m) { asm volatile("prefetch.tensormap [%0];" ::"l"(m) : "memory"); }
__device__ __forceinline__ void l2_prefetch(const void* p, uint32_t bytes) {
  asm volatile("cp.async.bulk.prefetch.L2.global [%0], %1;" ::"l"(p), "r"(bytes) : "memory");
}
__device__ __forceinline__ void cluster_arrive_relaxed() { asm volatile("barrier.cluster.arrive.relaxed.aligned;" ::: "memory"); }
__device__ __forceinline__ void cluster_wait() { asm volatile("barrier.cluster.wait.aligned;" ::: "memory"); }
__device__ __forceinline__ void wg_fence() { __syncwarp(); asm volatile("wgmma.fence.sync.aligned;" ::: "memory"); }
__device__ __forceinline__ void wg_commit() { asm volatile("wgmma.commit_group.sync.aligned;" ::: "memory"); }
template <int N> __device__ __forceinline__ void wg_wait() { __syncwarp(); asm volatile("wgmma.wait_group.sync.aligned %0;" ::"n"(N) : "memory"); }
__device__ __forceinline__ void named_bar(int id, int n) { asm volatile("bar.sync %0, %1;" ::"r"(id), "r"(n) : "memory"); }
__device__ __forceinline__ void named_arrive(int id, int n) { asm volatile("bar.arrive %0, %1;" ::"r"(id), "r"(n) : "memory"); }
template <int N> __device__ __forceinline__ void reg_inc() { asm volatile("setmaxnreg.inc.sync.aligned.u32 %0;" ::"n"(N)); }
template <int N> __device__ __forceinline__ void reg_dec() { asm volatile("setmaxnreg.dec.sync.aligned.u32 %0;" ::"n"(N)); }
__device__ __forceinline__ void pdl_wait() { asm volatile("griddepcontrol.wait;" ::: "memory"); }
__device__ __forceinline__ void pdl_launch() { asm volatile("griddepcontrol.launch_dependents;" ::: "memory"); }

__device__ __forceinline__ uint32_t make_desc(uint32_t addr, uint32_t lbo, uint32_t  ) {
  return ((addr & 0x3FFFF) >> 4) | ((lbo >> 4) << 16);
}
__device__ __forceinline__ void stmatrix_x4(uint32_t addr, uint32_t r0, uint32_t r1, uint32_t r2, uint32_t r3) {
  asm volatile("stmatrix.sync.aligned.m8n8.x4.shared.b16 [%0], {%1,%2,%3,%4};" ::"r"(addr), "r"(r0), "r"(r1), "r"(r2), "r"(r3) : "memory");
}
__device__ __forceinline__ uint4 lds128(uint32_t a) {
  uint4 v;
  asm volatile("ld.shared.v4.u32 {%0,%1,%2,%3}, [%4];" : "=r"(v.x), "=r"(v.y), "=r"(v.z), "=r"(v.w) : "r"(a) : "memory");
  return v;
}
__device__ __forceinline__ void sts128(uint32_t a, uint4 v) {
  asm volatile("st.shared.v4.u32 [%0], {%1,%2,%3,%4};" ::"r"(a), "r"(v.x), "r"(v.y), "r"(v.z), "r"(v.w) : "memory");
}
__device__ __forceinline__ void stg128(void* p, uint4 v) {
  asm volatile("st.global.v4.u32 [%0], {%1,%2,%3,%4};" ::"l"(p), "r"(v.x), "r"(v.y), "r"(v.z), "r"(v.w) : "memory");
}
__device__ __forceinline__ void cp_async16(uint32_t dst, const void* src) {
  asm volatile("cp.async.cg.shared.global [%0], [%1], 16;" ::"r"(dst), "l"(src) : "memory");
}
__device__ __forceinline__ void cp_async8(uint32_t dst, const void* src) {
  asm volatile("cp.async.ca.shared.global [%0], [%1], 8;" ::"r"(dst), "l"(src) : "memory");
}
__device__ __forceinline__ uint2 lds64(uint32_t a) {
  uint2 v;
  asm volatile("ld.shared.v2.u32 {%0,%1}, [%2];" : "=r"(v.x), "=r"(v.y) : "r"(a) : "memory");
  return v;
}
__device__ __forceinline__ void cp_async_wait_all() { asm volatile("cp.async.wait_all;" ::: "memory"); }
__device__ __forceinline__ uint32_t pack_bf16(float lo, float hi) {
  uint32_t r;
  asm("cvt.rn.bf16x2.f32 %0, %1, %2;" : "=r"(r) : "f"(hi), "f"(lo));
  return r;
}
__device__ __forceinline__ uint32_t hmul2_bf16(uint32_t a, uint32_t b) {
  uint32_t r;
  asm("mul.rn.bf16x2 %0, %1, %2;" : "=r"(r) : "r"(a), "r"(b));
  return r;
}
__device__ __forceinline__ uint32_t hsub2_bf16(uint32_t a, uint32_t b) {
  uint32_t r;
  asm("sub.rn.bf16x2 %0, %1, %2;" : "=r"(r) : "r"(a), "r"(b));
  return r;
}
__device__ __forceinline__ uint32_t hadd2_bf16(uint32_t a, uint32_t b) {
  uint32_t r;
  asm("add.rn.bf16x2 %0, %1, %2;" : "=r"(r) : "r"(a), "r"(b));
  return r;
}
__device__ __forceinline__ uint32_t hfma2_bf16(uint32_t a, uint32_t b, uint32_t c) {
  uint32_t r;
  asm("fma.rn.bf16x2 %0, %1, %2, %3;" : "=r"(r) : "r"(a), "r"(b), "r"(c));
  return r;
}
__device__ __forceinline__ bool mbar_test(uint32_t b, uint32_t ph) {
  uint32_t done;
  asm volatile("{.reg .pred p; mbarrier.test_wait.parity.shared::cta.b64 p, [%1], %2; selp.u32 %0,1,0,p;}" : "=r"(done) : "r"(b), "r"(ph) : "memory");
  return __all_sync(0xffffffffu, done != 0);
}
__device__ __forceinline__ uint4 ldg128_cg(const void* p) {
  uint4 v;
  asm volatile("ld.global.cg.v4.u32 {%0,%1,%2,%3}, [%4];" : "=r"(v.x), "=r"(v.y), "=r"(v.z), "=r"(v.w) : "l"(p) : "memory");
  return v;
}
__device__ __forceinline__ float bf_lo(uint32_t w) { return __uint_as_float(w << 16); }
__device__ __forceinline__ float bf_hi(uint32_t w) { return __uint_as_float(w & 0xffff0000u); }
__device__ __forceinline__ float rbf(float x) { return __bfloat162float(__float2bfloat16_rn(x)); }
__device__ __forceinline__ float ex2f(float x) { float r; asm("ex2.approx.ftz.f32 %0, %1;" : "=f"(r) : "f"(x)); return r; }
__device__ __forceinline__ float rcpf(float x) { float r; asm("rcp.approx.ftz.f32 %0, %1;" : "=f"(r) : "f"(x)); return r; }
__device__ __forceinline__ float tanhf_hw(float x) { float r; asm("tanh.approx.f32 %0, %1;" : "=f"(r) : "f"(x)); return r; }
__device__ __forceinline__ float gelu_tanh(float x) {
  const float c1 = 0.7978845608028654f;
  const float c2 = c1 * 0.044715f;
  const float t = tanhf_hw(x * fmaf(c2, x * x, c1));
  const float hx = 0.5f * x;
  return fmaf(hx, t, hx);
}
__device__ __forceinline__ float silu_f(float x) {
  const float hx = 0.5f * x;
  return fmaf(hx, tanhf_hw(hx), hx);
}

__device__ __forceinline__ void wgmma_n128_tb(float (&d)[64], uint32_t da, uint32_t db, int scale_d) {
  asm volatile(
    "{\n.reg .pred p;\n.reg .b64 da, db;\nsetp.ne.b32 p, %66, 0;\n"
    "mov.b64 da, {%64, 0x40000040};\nmov.b64 db, {%65, 0x40000040};\n"
    "wgmma.mma_async.sync.aligned.m64n128k16.f32.bf16.bf16 {%0, %1, %2, %3, %4, %5, %6, %7, %8, %9, %10, %11, %12, %13, %14, %15, %16, %17, %18, %19, %20, %21, %22, %23, %24, %25, %26, %27, %28, %29, %30, %31, %32, %33, %34, %35, %36, %37, %38, %39, %40, %41, %42, %43, %44, %45, %46, %47, %48, %49, %50, %51, %52, %53, %54, %55, %56, %57, %58, %59, %60, %61, %62, %63}, da, db, p, 1, 1, 0, 1;\n}\n"
    : "+f"(d[0]), "+f"(d[1]), "+f"(d[2]), "+f"(d[3]), "+f"(d[4]), "+f"(d[5]), "+f"(d[6]), "+f"(d[7]), "+f"(d[8]), "+f"(d[9]), "+f"(d[10]), "+f"(d[11]), "+f"(d[12]), "+f"(d[13]), "+f"(d[14]), "+f"(d[15]), "+f"(d[16]), "+f"(d[17]), "+f"(d[18]), "+f"(d[19]), "+f"(d[20]), "+f"(d[21]), "+f"(d[22]), "+f"(d[23]), "+f"(d[24]), "+f"(d[25]), "+f"(d[26]), "+f"(d[27]), "+f"(d[28]), "+f"(d[29]), "+f"(d[30]), "+f"(d[31]), "+f"(d[32]), "+f"(d[33]), "+f"(d[34]), "+f"(d[35]), "+f"(d[36]), "+f"(d[37]), "+f"(d[38]), "+f"(d[39]), "+f"(d[40]), "+f"(d[41]), "+f"(d[42]), "+f"(d[43]), "+f"(d[44]), "+f"(d[45]), "+f"(d[46]), "+f"(d[47]), "+f"(d[48]), "+f"(d[49]), "+f"(d[50]), "+f"(d[51]), "+f"(d[52]), "+f"(d[53]), "+f"(d[54]), "+f"(d[55]), "+f"(d[56]), "+f"(d[57]), "+f"(d[58]), "+f"(d[59]), "+f"(d[60]), "+f"(d[61]), "+f"(d[62]), "+f"(d[63])
    : "r"(da), "r"(db), "r"(scale_d));
}
__device__ __forceinline__ void wgmma_n128_tb_p(float (&d)[64], uint32_t da, uint32_t db, int scale_d, int enable) {
  asm volatile(
    "{\n.reg .pred p;\n.reg .b64 da, db;\nsetp.ne.b32 p, %66, 0;\n.reg .pred q;\nsetp.ne.b32 q, %67, 0;\n"
    "mov.b64 da, {%64, 0x40000040};\nmov.b64 db, {%65, 0x40000040};\n"
    "@q wgmma.mma_async.sync.aligned.m64n128k16.f32.bf16.bf16 {%0, %1, %2, %3, %4, %5, %6, %7, %8, %9, %10, %11, %12, %13, %14, %15, %16, %17, %18, %19, %20, %21, %22, %23, %24, %25, %26, %27, %28, %29, %30, %31, %32, %33, %34, %35, %36, %37, %38, %39, %40, %41, %42, %43, %44, %45, %46, %47, %48, %49, %50, %51, %52, %53, %54, %55, %56, %57, %58, %59, %60, %61, %62, %63}, da, db, p, 1, 1, 0, 1;\n}\n"
    : "+f"(d[0]), "+f"(d[1]), "+f"(d[2]), "+f"(d[3]), "+f"(d[4]), "+f"(d[5]), "+f"(d[6]), "+f"(d[7]), "+f"(d[8]), "+f"(d[9]), "+f"(d[10]), "+f"(d[11]), "+f"(d[12]), "+f"(d[13]), "+f"(d[14]), "+f"(d[15]), "+f"(d[16]), "+f"(d[17]), "+f"(d[18]), "+f"(d[19]), "+f"(d[20]), "+f"(d[21]), "+f"(d[22]), "+f"(d[23]), "+f"(d[24]), "+f"(d[25]), "+f"(d[26]), "+f"(d[27]), "+f"(d[28]), "+f"(d[29]), "+f"(d[30]), "+f"(d[31]), "+f"(d[32]), "+f"(d[33]), "+f"(d[34]), "+f"(d[35]), "+f"(d[36]), "+f"(d[37]), "+f"(d[38]), "+f"(d[39]), "+f"(d[40]), "+f"(d[41]), "+f"(d[42]), "+f"(d[43]), "+f"(d[44]), "+f"(d[45]), "+f"(d[46]), "+f"(d[47]), "+f"(d[48]), "+f"(d[49]), "+f"(d[50]), "+f"(d[51]), "+f"(d[52]), "+f"(d[53]), "+f"(d[54]), "+f"(d[55]), "+f"(d[56]), "+f"(d[57]), "+f"(d[58]), "+f"(d[59]), "+f"(d[60]), "+f"(d[61]), "+f"(d[62]), "+f"(d[63])
    : "r"(da), "r"(db), "r"(scale_d), "r"(enable));
}
__device__ __forceinline__ void wgmma_n112(float (&d)[56], uint32_t da, uint32_t db, int scale_d) {
  asm volatile(
    "{\n.reg .pred p;\n.reg .b64 da, db;\nsetp.ne.b32 p, %58, 0;\n"
    "mov.b64 da, {%56, 0x40000040};\nmov.b64 db, {%57, 0x40000040};\n"
    "wgmma.mma_async.sync.aligned.m64n112k16.f32.bf16.bf16 {%0, %1, %2, %3, %4, %5, %6, %7, %8, %9, %10, %11, %12, %13, %14, %15, %16, %17, %18, %19, %20, %21, %22, %23, %24, %25, %26, %27, %28, %29, %30, %31, %32, %33, %34, %35, %36, %37, %38, %39, %40, %41, %42, %43, %44, %45, %46, %47, %48, %49, %50, %51, %52, %53, %54, %55}, da, db, p, 1, 1, 0, 0;\n}\n"
    : "+f"(d[0]), "+f"(d[1]), "+f"(d[2]), "+f"(d[3]), "+f"(d[4]), "+f"(d[5]), "+f"(d[6]), "+f"(d[7]), "+f"(d[8]), "+f"(d[9]), "+f"(d[10]), "+f"(d[11]), "+f"(d[12]), "+f"(d[13]), "+f"(d[14]), "+f"(d[15]), "+f"(d[16]), "+f"(d[17]), "+f"(d[18]), "+f"(d[19]), "+f"(d[20]), "+f"(d[21]), "+f"(d[22]), "+f"(d[23]), "+f"(d[24]), "+f"(d[25]), "+f"(d[26]), "+f"(d[27]), "+f"(d[28]), "+f"(d[29]), "+f"(d[30]), "+f"(d[31]), "+f"(d[32]), "+f"(d[33]), "+f"(d[34]), "+f"(d[35]), "+f"(d[36]), "+f"(d[37]), "+f"(d[38]), "+f"(d[39]), "+f"(d[40]), "+f"(d[41]), "+f"(d[42]), "+f"(d[43]), "+f"(d[44]), "+f"(d[45]), "+f"(d[46]), "+f"(d[47]), "+f"(d[48]), "+f"(d[49]), "+f"(d[50]), "+f"(d[51]), "+f"(d[52]), "+f"(d[53]), "+f"(d[54]), "+f"(d[55])
    : "r"(da), "r"(db), "r"(scale_d));
}
__device__ __forceinline__ void wgmma_n224_tb(float (&d)[112], uint32_t da, uint32_t db, int scale_d) {
  asm volatile(
    "{\n.reg .pred p;\n.reg .b64 da, db;\nsetp.ne.b32 p, %114, 0;\n"
    "mov.b64 da, {%112, 0x40000040};\nmov.b64 db, {%113, 0x40000040};\n"
    "wgmma.mma_async.sync.aligned.m64n224k16.f32.bf16.bf16 {%0, %1, %2, %3, %4, %5, %6, %7, %8, %9, %10, %11, %12, %13, %14, %15, %16, %17, %18, %19, %20, %21, %22, %23, %24, %25, %26, %27, %28, %29, %30, %31, %32, %33, %34, %35, %36, %37, %38, %39, %40, %41, %42, %43, %44, %45, %46, %47, %48, %49, %50, %51, %52, %53, %54, %55, %56, %57, %58, %59, %60, %61, %62, %63, %64, %65, %66, %67, %68, %69, %70, %71, %72, %73, %74, %75, %76, %77, %78, %79, %80, %81, %82, %83, %84, %85, %86, %87, %88, %89, %90, %91, %92, %93, %94, %95, %96, %97, %98, %99, %100, %101, %102, %103, %104, %105, %106, %107, %108, %109, %110, %111}, da, db, p, 1, 1, 0, 1;\n}\n"
    : "+f"(d[0]), "+f"(d[1]), "+f"(d[2]), "+f"(d[3]), "+f"(d[4]), "+f"(d[5]), "+f"(d[6]), "+f"(d[7]), "+f"(d[8]), "+f"(d[9]), "+f"(d[10]), "+f"(d[11]), "+f"(d[12]), "+f"(d[13]), "+f"(d[14]), "+f"(d[15]), "+f"(d[16]), "+f"(d[17]), "+f"(d[18]), "+f"(d[19]), "+f"(d[20]), "+f"(d[21]), "+f"(d[22]), "+f"(d[23]), "+f"(d[24]), "+f"(d[25]), "+f"(d[26]), "+f"(d[27]), "+f"(d[28]), "+f"(d[29]), "+f"(d[30]), "+f"(d[31]), "+f"(d[32]), "+f"(d[33]), "+f"(d[34]), "+f"(d[35]), "+f"(d[36]), "+f"(d[37]), "+f"(d[38]), "+f"(d[39]), "+f"(d[40]), "+f"(d[41]), "+f"(d[42]), "+f"(d[43]), "+f"(d[44]), "+f"(d[45]), "+f"(d[46]), "+f"(d[47]), "+f"(d[48]), "+f"(d[49]), "+f"(d[50]), "+f"(d[51]), "+f"(d[52]), "+f"(d[53]), "+f"(d[54]), "+f"(d[55]), "+f"(d[56]), "+f"(d[57]), "+f"(d[58]), "+f"(d[59]), "+f"(d[60]), "+f"(d[61]), "+f"(d[62]), "+f"(d[63]), "+f"(d[64]), "+f"(d[65]), "+f"(d[66]), "+f"(d[67]), "+f"(d[68]), "+f"(d[69]), "+f"(d[70]), "+f"(d[71]), "+f"(d[72]), "+f"(d[73]), "+f"(d[74]), "+f"(d[75]), "+f"(d[76]), "+f"(d[77]), "+f"(d[78]), "+f"(d[79]), "+f"(d[80]), "+f"(d[81]), "+f"(d[82]), "+f"(d[83]), "+f"(d[84]), "+f"(d[85]), "+f"(d[86]), "+f"(d[87]), "+f"(d[88]), "+f"(d[89]), "+f"(d[90]), "+f"(d[91]), "+f"(d[92]), "+f"(d[93]), "+f"(d[94]), "+f"(d[95]), "+f"(d[96]), "+f"(d[97]), "+f"(d[98]), "+f"(d[99]), "+f"(d[100]), "+f"(d[101]), "+f"(d[102]), "+f"(d[103]), "+f"(d[104]), "+f"(d[105]), "+f"(d[106]), "+f"(d[107]), "+f"(d[108]), "+f"(d[109]), "+f"(d[110]), "+f"(d[111])
    : "r"(da), "r"(db), "r"(scale_d));
}

constexpr int K1_NS = 5;
constexpr int K1_A_BYTES = 7 * 16384;
constexpr int K1_B_OFF = K1_A_BYTES;
constexpr int K1_STG_OFF = K1_B_OFF + K1_NS * 16384;
constexpr int K1_BAR_OFF = K1_STG_OFF + 8 * 4096;
constexpr int K1_SMEM = K1_BAR_OFF + 256 + 1024;

struct K1Ctx {
  uint32_t sb, bar_full, rel0, rel1;
  uint32_t dA, dBk, dBn;
  bool lane0;
  const CUtensorMap* tm_hs;
  const CUtensorMap* tm_abs;
};
__device__ __forceinline__ void k1_release(const K1Ctx& c, int slot) {
  if (c.lane0) {
    asm volatile("mbarrier.arrive.shared::cluster.b64 _, [%0];" ::"r"(c.rel0 + 8 * slot) : "memory");
    asm volatile("mbarrier.arrive.shared::cluster.b64 _, [%0];" ::"r"(c.rel1 + 8 * slot) : "memory");
  }
}

__device__ __forceinline__ void k1_unit_ab(const K1Ctx& c, int warp, int lane, int mt, int j) {
  const uint32_t stg = c.sb + K1_STG_OFF + warp * 4096;
  const int wq = warp & 3;
  const int st_row = (lane & 7) + 8 * ((lane >> 3) & 1);
  const int st_chunk = lane >> 4;
  float acc[2][56];
  int slot = 0; uint32_t ph = 0;
#pragma unroll 1
  for (int kb = 0; kb < 7; kb++) {
    const int pslot = (slot == 0) ? K1_NS - 1 : slot - 1;
    mbar_wait(c.bar_full + 8 * slot, ph, 3);
    if (kb == 6) named_arrive(2, 256);
    if (kb == 0 && (threadIdx.x & 127) == 0) DBG(0, 4);
    if ((threadIdx.x & 127) == 0) DBGC(1, 46 + kb);
    wg_fence();
    const uint32_t da = c.dA + kb * 1024;
    const uint32_t db = c.dBk + slot * 1024;
#pragma unroll
    for (int k = 0; k < 4; k++) {
      wgmma_n112(acc[0], da + k * 2, db + k * 2, (kb | k) != 0);
      wgmma_n112(acc[1], da + 512 + k * 2, db + k * 2, (kb | k) != 0);
    }
    wg_commit();
    if (kb > 0) { wg_wait<1>(); k1_release(c, pslot); }
    if (++slot == K1_NS) { slot = 0; ph ^= 1; }
  }
  wg_wait<0>();
  k1_release(c, 6 % K1_NS);
  if ((threadIdx.x & 127) == 0) DBG(0, 5);
  const uint32_t sgn = (j < 4) ? 0u : 0x80008000u;
  const uint32_t sa = stg + st_row * 224 + st_chunk * 16;
  const int row0 = (j < 4 ? 0 : 2048) + mt * 128 + wq * 16;
#pragma unroll
  for (int h = 0; h < 2; h++) {
    if (h == 1) { if (c.lane0) bulk_wait_read0(); __syncwarp(); }
#pragma unroll
    for (int g = 0; g < 14; g += 2) {
      const float* a = &acc[h][4 * g];
      stmatrix_x4(sa + g * 16, pack_bf16(a[0], a[1]) ^ sgn, pack_bf16(a[2], a[3]) ^ sgn, pack_bf16(a[4], a[5]) ^ sgn, pack_bf16(a[6], a[7]) ^ sgn);
    }
    fence_async_smem();
    __syncwarp();
    if (c.lane0) { tma2d_store(c.tm_abs, stg, (j & 3) * 112, row0 + h * 64); bulk_commit(); }
  }
}

__device__ __forceinline__ void k1_unit_gu(const K1Ctx& c, int warp, int lane, int mt, int unit, int fb, int hsel) {
  const uint32_t stg = c.sb + K1_STG_OFF + warp * 4096;
  const int wq = warp & 3;
  const int full = (unit < 4);
  float acc[2][64];
  const uint32_t dA0 = c.dA + (full ? 0 : hsel * 512);
  int slot = (unit * 7) % K1_NS; uint32_t ph = ((unit * 7) / K1_NS) & 1;
  named_bar(2 + ((unit - 1) & 1), 256);
  if (full) {
#pragma unroll 1
    for (int kb = 0; kb < 7; kb++) {
      const int pslot = (slot == 0) ? K1_NS - 1 : slot - 1;
      mbar_wait(c.bar_full + 8 * slot, ph, 4);
      if (kb == 6) named_arrive(2 + (unit & 1), 256);
      if (kb == 0 && (threadIdx.x & 127) == 0) DBG(0, 4 + 3 * unit);
      wg_fence();
      const uint32_t da = dA0 + kb * 1024;
      const uint32_t db = c.dBn + slot * 1024;
#pragma unroll
      for (int k = 0; k < 4; k++) {
        wgmma_n128_tb(acc[0], da + k * 2, db + k * 128, (kb | k) != 0);
        wgmma_n128_tb(acc[1], da + 512 + k * 2, db + k * 128, (kb | k) != 0);
      }
      wg_commit();
      if (kb > 0) { wg_wait<1>(); k1_release(c, pslot); }
      if (++slot == K1_NS) { slot = 0; ph ^= 1; }
    }
  } else {
#pragma unroll 1
    for (int kb = 0; kb < 7; kb++) {
      const int pslot = (slot == 0) ? K1_NS - 1 : slot - 1;
      mbar_wait(c.bar_full + 8 * slot, ph, 5);
      if (kb == 0 && (threadIdx.x & 127) == 0) DBG(0, 4 + 3 * unit);
      wg_fence();
      const uint32_t da = dA0 + kb * 1024;
      const uint32_t db = c.dBn + slot * 1024;
#pragma unroll
      for (int k = 0; k < 4; k++) wgmma_n128_tb(acc[0], da + k * 2, db + k * 128, (kb | k) != 0);
      wg_commit();
      if (kb > 0) { wg_wait<1>(); k1_release(c, pslot); }
      if (++slot == K1_NS) { slot = 0; ph ^= 1; }
    }
  }
  wg_wait<0>();
  k1_release(c, (slot == 0) ? K1_NS - 1 : slot - 1);
  if ((threadIdx.x & 127) == 0) DBG(0, 5 + 3 * unit);
  const int st_row = (lane & 7) + 8 * ((lane >> 3) & 1);
  const int st_chunk = lane >> 4;
  const uint32_t sa = stg + st_row * 128;
  const int row0 = mt * 128 + (full ? 0 : hsel * 64) + wq * 16;
  if (c.lane0) bulk_wait_read0();
  __syncwarp();
#pragma unroll
  for (int h = 0; h < 2; h++) {
    if (h == 1 && !full) break;
#pragma unroll
    for (int g = 0; g < 8; g += 2) {
      uint32_t pk[4];
#pragma unroll
      for (int e = 0; e < 4; e++) {
        const int i = 4 * g + 2 * e;
        const uint32_t g2 = pack_bf16(acc[h][i], acc[h][i + 1]);
        const uint32_t u2 = pack_bf16(acc[h][32 + i], acc[h][32 + i + 1]);
        pk[e] = hmul2_bf16(pack_bf16(gelu_tanh(bf_lo(g2)), gelu_tanh(bf_hi(g2))), u2);
      }
      stmatrix_x4(sa + h * 2048 + (((g + st_chunk) ^ (st_row & 7)) * 16), pk[0], pk[1], pk[2], pk[3]);
    }
    fence_async_smem();
    __syncwarp();
    if (c.lane0) { tma2d_store(c.tm_hs, stg + h * 2048, fb * 64, row0 + h * 64); bulk_commit(); }
  }
}

struct PfPtrs { const uint8_t* wr; const uint8_t* wi; const uint8_t* wg; const uint8_t* wu; const uint8_t* wd; const uint8_t* cr; const uint8_t* ci; };

__global__ void __cluster_dims__(2, 1, 1) __launch_bounds__(384, 1)
k1_kernel(const __grid_constant__ CUtensorMap tm_wr, const __grid_constant__ CUtensorMap tm_wi,
          const __grid_constant__ CUtensorMap tm_wg, const __grid_constant__ CUtensorMap tm_wu,
          const __grid_constant__ CUtensorMap tm_hs, const __grid_constant__ CUtensorMap tm_abs,
          const __nv_bfloat16* __restrict__ x, const PfPtrs pf) {
  extern __shared__ uint8_t smem_raw[];
  const uint32_t sb = (s2u(smem_raw) + 1023) & ~1023u;
  const int tid = threadIdx.x, warp = tid >> 5, lane = tid & 31;
  uint32_t rank;
  asm volatile("mov.u32 %0, %%cluster_ctarank;" : "=r"(rank));
  const int cid = blockIdx.x >> 1;
  const int p = cid >> 3, j = cid & 7;
  const int mt = 2 * p + (int)rank;
  const uint32_t bar_full = sb + K1_BAR_OFF;
  const uint32_t bar_empty = bar_full + 8 * K1_NS;
  const int fb_base = 7 * (j >> 1);
  const int fb0 = fb_base + ((j & 1) ? 4 : 0);
  const int fbh = fb_base + 3;
  const CUtensorMap* tw = (j < 4) ? &tm_wr : &tm_wi;
  const CUtensorMap* tgu = rank ? &tm_wu : &tm_wg;

  if (tid == 0) DBG(0, 0);
  if (tid == 256) {
    for (int i = 0; i < K1_NS; i++) { mbar_init(bar_full + 8 * i, 1); mbar_init(bar_empty + 8 * i, 8); }
    asm volatile("fence.mbarrier_init.release.cluster;" ::: "memory");
    prefetch_tmap(tw);
    prefetch_tmap(tgu);
    prefetch_tmap(&tm_abs);
    prefetch_tmap(&tm_hs);
    if (blockIdx.x < 64) g_flags[blockIdx.x] = 0;
  }
  __syncwarp();
  cluster_arrive_relaxed();
  pdl_launch();

  if (warp >= 8) {
    reg_dec<40>();
    cluster_wait();
    if (tid == 256) {
      int slot = 0; uint32_t ph = 0;
      int kb = 0, unit = 0;
#pragma unroll 1
      for (int s = 0; s < 35; s++) {
        if (s >= K1_NS) mbar_wait(bar_empty + 8 * slot, ph ^ 1, 2);
        DBG(0, 20 + s);
        const uint32_t dst = sb + K1_B_OFF + slot * 16384;
        if (unit == 0) {
          mbar_expect(bar_full + 8 * slot, 14336);
          tma2d_mc(dst + rank * 7168, tw, kb * 64, (j & 3) * 112 + rank * 56, bar_full + 8 * slot, 3);
        } else {
          const int fb = (unit == 4) ? fbh : (fb0 + unit - 1);
          mbar_expect(bar_full + 8 * slot, 16384);
          tma2d_mc(dst + rank * 8192, tgu, fb * 64, kb * 64, bar_full + 8 * slot, 3);
        }
        if (++kb == 7) { kb = 0; unit++; }
        if (++slot == K1_NS) { slot = 0; ph ^= 1; }
      }
    } else if (tid == 288) {
      const int b = blockIdx.x;
      l2_prefetch(pf.wg + b * 12544, 12544);
      l2_prefetch(pf.wu + b * 12544, 12544);
    }
  } else {
    reg_inc<232>();
    const int wg = warp >> 2;
    {
      const int c = lane & 7;
      const int r0 = warp * 16 + (lane >> 3);
      const uint4* src = reinterpret_cast<const uint4*>(x + (size_t)(mt * 128 + r0) * 448) + c;
      uint4 nx[7];
#pragma unroll
      for (int b = 0; b < 7; b++)
        asm volatile("ld.global.nc.v4.u32 {%0,%1,%2,%3}, [%4];" : "=r"(nx[b].x), "=r"(nx[b].y), "=r"(nx[b].z), "=r"(nx[b].w) : "l"(src + b * 8) : "memory");
#pragma unroll
      for (int pass = 1; pass < 4; pass++) asm volatile("prefetch.global.L2 [%0];" ::"l"(src + pass * 4 * 56 + c * 7 - c) : "memory");
#pragma unroll 1
      for (int pass = 0; pass < 4; pass++) {
        uint4 v[7];
#pragma unroll
        for (int b = 0; b < 7; b++) v[b] = nx[b];
        if (pass < 3) {
          const uint4* s2 = src + (pass + 1) * 4 * 56;
#pragma unroll
          for (int b = 0; b < 7; b++)
            asm volatile("ld.global.nc.v4.u32 {%0,%1,%2,%3}, [%4];" : "=r"(nx[b].x), "=r"(nx[b].y), "=r"(nx[b].z), "=r"(nx[b].w) : "l"(s2 + b * 8) : "memory");
        }
        float s0 = 0.f, s1 = 0.f, s2v = 0.f, s3 = 0.f;
#pragma unroll
        for (int b = 0; b < 7; b++) {
          s0 += bf_lo(v[b].x) + bf_hi(v[b].x); s1 += bf_lo(v[b].y) + bf_hi(v[b].y);
          s2v += bf_lo(v[b].z) + bf_hi(v[b].z); s3 += bf_lo(v[b].w) + bf_hi(v[b].w);
        }
        float m = (s0 + s1) + (s2v + s3);
        m += __shfl_xor_sync(0xffffffffu, m, 1);
        m += __shfl_xor_sync(0xffffffffu, m, 2);
        m += __shfl_xor_sync(0xffffffffu, m, 4);
        m *= (1.0f / 448.0f);
        float q0 = 0.f, q1 = 0.f, q2 = 0.f, q3 = 0.f;
#pragma unroll
        for (int b = 0; b < 7; b++) {
          float d;
          d = bf_lo(v[b].x) - m; q0 = fmaf(d, d, q0); d = bf_hi(v[b].x) - m; q1 = fmaf(d, d, q1);
          d = bf_lo(v[b].y) - m; q2 = fmaf(d, d, q2); d = bf_hi(v[b].y) - m; q3 = fmaf(d, d, q3);
          d = bf_lo(v[b].z) - m; q0 = fmaf(d, d, q0); d = bf_hi(v[b].z) - m; q1 = fmaf(d, d, q1);
          d = bf_lo(v[b].w) - m; q2 = fmaf(d, d, q2); d = bf_hi(v[b].w) - m; q3 = fmaf(d, d, q3);
        }
        float q = (q0 + q1) + (q2 + q3);
        q += __shfl_xor_sync(0xffffffffu, q, 1);
        q += __shfl_xor_sync(0xffffffffu, q, 2);
        q += __shfl_xor_sync(0xffffffffu, q, 4);
        const float var_b = rbf(q * (1.0f / 448.0f));
        const float den = rbf(sqrtf(rbf(var_b + 1e-5f)));
        const float ri = 1.0f / den;
        const float rih = rbf(ri);
        const uint32_t rhi2 = pack_bf16(rih, rih), rlo2 = pack_bf16(ri - rih, ri - rih);
        const uint32_t m2 = pack_bf16(m, m);
        const int r = r0 + pass * 4;
        const uint32_t a0 = sb + r * 128 + ((c ^ (r & 7)) * 16);
#pragma unroll
        for (int b = 0; b < 7; b++) {
          uint32_t w4[4] = {v[b].x, v[b].y, v[b].z, v[b].w};
#pragma unroll
          for (int qq = 0; qq < 4; qq++) {
            const uint32_t dw = hsub2_bf16(w4[qq], m2);
            w4[qq] = hfma2_bf16(dw, rhi2, hmul2_bf16(dw, rlo2));
          }
          sts128(a0 + b * 16384, make_uint4(w4[0], w4[1], w4[2], w4[3]));
        }
      }
    }
    if (lane == 0) DBG(0, 59 + (warp & 3));
    asm volatile("fence.proxy.async.shared::cta;" ::: "memory");
    named_bar(1, 256);
    cluster_wait();
    if (tid == 0) DBG(0, 3);

    K1Ctx c;
    c.sb = sb; c.bar_full = bar_full; c.lane0 = (lane == 0);
    asm volatile("mapa.shared::cluster.u32 %0, %1, %2;" : "=r"(c.rel0) : "r"(bar_empty), "r"(0));
    asm volatile("mapa.shared::cluster.u32 %0, %1, %2;" : "=r"(c.rel1) : "r"(bar_empty), "r"(1));
    c.tm_hs = &tm_hs; c.tm_abs = &tm_abs;
    c.dA = make_desc(sb, 16, 1024);
    c.dBk = make_desc(sb + K1_B_OFF, 16, 1024);
    c.dBn = make_desc(sb + K1_B_OFF, 8192, 1024);
    if (wg == 0) {
      k1_unit_ab(c, warp, lane, mt, j);
      if (tid == 0) DBG(0, 6);
    }
#pragma unroll 1
    for (int unit = 2 - wg; unit < 5; unit += 2) {
      k1_unit_gu(c, warp, lane, mt, unit, (unit == 4) ? fbh : fb0 + unit - 1, j & 1);
      if ((tid & 127) == 0) DBG(0, 6 + 3 * unit);
    }
    if (lane == 0) bulk_wait0();
  }
  __syncwarp();
  cluster_arrive_relaxed();
  cluster_wait();
}

constexpr int K2_NS = 4;
constexpr int K2_STAGE = 16384 + 32768;
constexpr int K2_BAR_OFF = K2_NS * K2_STAGE;
constexpr int K2_SMEM = K2_BAR_OFF + 256 + 1024;
constexpr int K2_PITCH = 464;

__device__ __forceinline__ void spin_flag(const unsigned int* flag, unsigned int target) {
  int it = 0;
  while (true) {
    unsigned int v;
    asm volatile("ld.acquire.gpu.global.u32 %0, [%1];" : "=r"(v) : "l"(flag) : "memory");
    if (v >= target) break;
    if (++it > SPIN_LIMIT) { TIMEOUT(20); break; }
  }
}

__global__ void __cluster_dims__(2, 1, 1) __launch_bounds__(384, 1)
k2_kernel(const __grid_constant__ CUtensorMap tm_cr, const __grid_constant__ CUtensorMap tm_ci, const __grid_constant__ CUtensorMap tm_h,
          const __grid_constant__ CUtensorMap tm_ab, const __grid_constant__ CUtensorMap tm_wd,
          const __nv_bfloat16* __restrict__ x, __nv_bfloat16* __restrict__ out) {
  extern __shared__ uint8_t smem_raw[];
  const uint32_t sb = (s2u(smem_raw) + 1023) & ~1023u;
  const int tid = threadIdx.x, warp = tid >> 5, lane = tid & 31;
  uint32_t rank;
  asm volatile("mov.u32 %0, %%cluster_ctarank;" : "=r"(rank));
  const int cid = blockIdx.x >> 1;
  const int q = cid & 3, n = (cid >> 2) & 1, p = cid >> 3;
  const int mt = 2 * p + (int)rank;
  const int tile = mt * 2 + n;
  const uint32_t bar_full = sb + K2_BAR_OFF;
  const uint32_t bar_empty = bar_full + 8 * K2_NS;
  const int g0 = (q == 0) ? 0 : (q == 1 ? 22 : (q == 2 ? 43 : 64));
  const int nkb = (q == 0) ? 22 : (q == 3 ? 28 : 21);

  if (tid == 0) DBG(1, 0);
  if (tid == 256) {
    for (int i = 0; i < K2_NS; i++) { mbar_init(bar_full + 8 * i, 1); mbar_init(bar_empty + 8 * i, 16); }
    asm volatile("fence.mbarrier_init.release.cluster;" ::: "memory");
    if (q == 3) { prefetch_tmap(&tm_h); prefetch_tmap(&tm_wd); }
    else { prefetch_tmap(&tm_cr); prefetch_tmap(&tm_ci); prefetch_tmap(&tm_ab); }
  }
  __syncwarp();
  cluster_arrive_relaxed();
  cluster_wait();

  if (warp >= 8) {
    reg_dec<40>();
    if (tid == 256) {
      const CUtensorMap* tb = (q < 3) ? &tm_ab : &tm_wd;
      const int kb0 = (q < 3) ? g0 : 0;
      int slot = 0; uint32_t ph = 0;
#pragma unroll 1
      for (int it = 0; it < nkb + K2_NS; it++) {
        const int s = (it < K2_NS) ? it : it - K2_NS;
        const bool pre = (it < K2_NS), post = (!pre && s < K2_NS);
        if (it == K2_NS) { pdl_wait(); DBG(1, 31); slot = 0; }
        if (!pre && !post) mbar_wait(bar_empty + 8 * slot, ph, 10);
        const uint32_t dst = sb + slot * K2_STAGE;
        const uint32_t fb = bar_full + 8 * slot;
        if (!post) mbar_expect(fb, K2_STAGE);
        const bool doA = pre ? (q < 3) : (post ? (q == 3) : true);
        const bool doB = pre ? (q == 3) : (post ? (q < 3) : true);
        if (doA) {
          const int g = g0 + s;
          const CUtensorMap* ta = (g < 32) ? &tm_cr : (g < 64 ? &tm_ci : &tm_h);
          tma2d(dst, ta, (g & 31) * 64 + ((g >= 96) ? 2048 : 0), mt * 128, fb);
        }
        if (doB) {
          tma3d_mc(dst + 16384 + (2 * rank) * 8192, tb, (2 * rank) * 64, n, (kb0 + s) * 64, fb, 3);
          tma3d_mc(dst + 16384 + (2 * rank + 1) * 8192, tb, (2 * rank + 1) * 64, n, (kb0 + s) * 64, fb, 3);
        }
        if (++slot == K2_NS) { slot = 0; if (!pre && !post) ph ^= 1; }
      }
    }
  } else {
    reg_inc<232>();
    const int wg = warp >> 2;
    float acc[112];
    uint32_t rel0, rel1;
    asm volatile("mapa.shared::cluster.u32 %0, %1, %2;" : "=r"(rel0) : "r"(bar_empty), "r"(0));
    asm volatile("mapa.shared::cluster.u32 %0, %1, %2;" : "=r"(rel1) : "r"(bar_empty), "r"(1));
    const uint32_t dA0 = make_desc(sb + wg * 8192, 16, 1024);
    const uint32_t dB0 = make_desc(sb + 16384, 8192, 1024);
    int slot = 0; uint32_t ph = 0;
#pragma unroll 1
    for (int s = 0; s < nkb; s++) {
      mbar_wait(bar_full + 8 * slot, ph, 11);
      if (tid == 0) DBG(1, 1 + s);
      if (tid == 0 && (s == 5 || s == 15)) DBGC(1, 53 + (s == 15));
      if (tid == 0 && (s == 23 || s == 27)) DBGC(1, 55 + (s == 27));
      wg_fence();
      const uint32_t da = dA0 + slot * (K2_STAGE / 16);
      const uint32_t db = dB0 + slot * (K2_STAGE / 16);
#pragma unroll
      for (int k = 0; k < 4; k++) wgmma_n224_tb(acc, da + k * 2, db + k * 128, (s | k) != 0);
      wg_commit();
      if (s > 0) {
        wg_wait<1>();
        const int ps = (slot == 0) ? K2_NS - 1 : slot - 1;
        if (lane == 0) {
          asm volatile("mbarrier.arrive.shared::cluster.b64 _, [%0];" ::"r"(rel0 + 8 * ps) : "memory");
          asm volatile("mbarrier.arrive.shared::cluster.b64 _, [%0];" ::"r"(rel1 + 8 * ps) : "memory");
        }
      }
      if (++slot == K2_NS) { slot = 0; ph ^= 1; }
    }
    wg_wait<0>();
    pdl_wait();
    if (tid == 0) DBG(1, 29);
    if (q < 3) {
      uint2* part = g_part + (size_t)(tile * 3 + q) * (28 * 256) + tid;
#pragma unroll
      for (int g = 0; g < 28; g++)
        part[g * 256] = make_uint2(pack_bf16(acc[4 * g], acc[4 * g + 1]), pack_bf16(acc[4 * g + 2], acc[4 * g + 3]));
      __threadfence();
      named_bar(1, 256);
      if (tid == 0) atomicAdd(&g_flags[tile], 1u);
    } else {
      uint32_t gw[56];
#pragma unroll
      for (int i = 0; i < 56; i++) {
        const uint32_t f2 = pack_bf16(acc[2 * i], acc[2 * i + 1]);
        gw[i] = pack_bf16(silu_f(bf_lo(f2)), silu_f(bf_hi(f2)));
      }
      const int lc = (lane < 28) ? lane : 27;
      const size_t gbase = (size_t)(mt * 128 + warp * 16) * 448 + n * 224 + lc * 8;
      uint4 xv[16];
#pragma unroll
      for (int t = 0; t < 16; t++) xv[t] = ldg128_cg(x + gbase + t * 448);
      named_bar(1, 256);
      if (tid == 0) DBG(1, 62);
      if (lane == 0) spin_flag(&g_flags[tile], 3u);
      __syncwarp();
      if (tid == 0) DBG(1, 30);
      const uint32_t wbase = sb + warp * (84 * 256);
      const uint2* pp = g_part + (size_t)tile * (3 * 28 * 256) + tid;
#pragma unroll 4
      for (int i = 0; i < 84; i++) cp_async8(wbase + i * 256 + lane * 8, pp + i * 256);
      cp_async_wait_all();
#pragma unroll
      for (int g = 0; g < 28; g++) {
        const uint2 a = lds64(wbase + g * 256 + lane * 8), b = lds64(wbase + (28 + g) * 256 + lane * 8), cc = lds64(wbase + (56 + g) * 256 + lane * 8);
        gw[2 * g] = hmul2_bf16(pack_bf16(bf_lo(a.x) + bf_lo(b.x) + bf_lo(cc.x), bf_hi(a.x) + bf_hi(b.x) + bf_hi(cc.x)), gw[2 * g]);
        gw[2 * g + 1] = hmul2_bf16(pack_bf16(bf_lo(a.y) + bf_lo(b.y) + bf_lo(cc.y), bf_hi(a.y) + bf_hi(b.y) + bf_hi(cc.y)), gw[2 * g + 1]);
      }
      __syncwarp();
      const int st_row = (lane & 7) + 8 * ((lane >> 3) & 1);
      const uint32_t sa = wbase + st_row * K2_PITCH + (lane >> 4) * 16;
#pragma unroll
      for (int g = 0; g < 28; g += 2) stmatrix_x4(sa + g * 16, gw[2 * g], gw[2 * g + 1], gw[2 * g + 2], gw[2 * g + 3]);
      __syncwarp();
      const uint32_t lp = wbase + lc * 16;
#pragma unroll
      for (int t = 0; t < 16; t++) {
        const uint4 tv = lds128(lp + t * K2_PITCH);
        uint4 o;
        o.x = hadd2_bf16(xv[t].x, tv.x); o.y = hadd2_bf16(xv[t].y, tv.y); o.z = hadd2_bf16(xv[t].z, tv.z); o.w = hadd2_bf16(xv[t].w, tv.w);
        if (lane < 28) stg128(out + gbase + t * 448, o);
      }
    }
    if (tid == 0) DBG(1, 63);
  }
  __syncwarp();
  cluster_arrive_relaxed();
  cluster_wait();
}

typedef CUresult (*EncFn)(CUtensorMap*, CUtensorMapDataType, cuuint32_t, void*, const cuuint64_t*, const cuuint64_t*, const cuuint32_t*,
                          const cuuint32_t*, CUtensorMapInterleave, CUtensorMapSwizzle, CUtensorMapL2promotion, CUtensorMapFloatOOBfill);

void make2d(EncFn enc, CUtensorMap* tm, const void* ptr, uint64_t cols, uint64_t rows, uint32_t bc, uint32_t br, bool swz = true) {
  cuuint64_t gd[2] = {cols, rows};
  cuuint64_t gs[1] = {cols * 2};
  cuuint32_t bd[2] = {bc, br};
  cuuint32_t es[2] = {1, 1};
  enc(tm, CU_TENSOR_MAP_DATA_TYPE_BFLOAT16, 2, const_cast<void*>(ptr), gd, gs, bd, es, CU_TENSOR_MAP_INTERLEAVE_NONE,
      swz ? CU_TENSOR_MAP_SWIZZLE_128B : CU_TENSOR_MAP_SWIZZLE_NONE, CU_TENSOR_MAP_L2_PROMOTION_L2_128B, CU_TENSOR_MAP_FLOAT_OOB_FILL_NONE);
}
void make3d_half(EncFn enc, CUtensorMap* tm, const void* ptr, uint64_t rows) {
  cuuint64_t gd[3] = {224, 2, rows};
  cuuint64_t gs[2] = {448, 896};
  cuuint32_t bd[3] = {64, 1, 64};
  cuuint32_t es[3] = {1, 1, 1};
  enc(tm, CU_TENSOR_MAP_DATA_TYPE_BFLOAT16, 3, const_cast<void*>(ptr), gd, gs, bd, es, CU_TENSOR_MAP_INTERLEAVE_NONE,
      CU_TENSOR_MAP_SWIZZLE_128B, CU_TENSOR_MAP_L2_PROMOTION_L2_128B, CU_TENSOR_MAP_FLOAT_OOB_FILL_NONE);
}

struct Maps { CUtensorMap wr, wi, wg, wu, cr, ci, h, ab, wd, hs, abs; };

}

extern "C" void kernel_launch(void* const* d_in, const int* in_sizes, int n_in, void* d_out, int out_size) {
  (void)in_sizes; (void)n_in; (void)out_size;
  static Maps maps;
  static const void* cached[9] = {nullptr};
  static bool attr_done = false;
  bool same = true;
  for (int i = 0; i < 9; i++) same = same && (cached[i] == d_in[i]);
  if (!same) {
    void* fn = nullptr;
    cudaDriverEntryPointQueryResult qr;
    cudaGetDriverEntryPoint("cuTensorMapEncodeTiled", &fn, cudaEnableDefault, &qr);
    EncFn enc = (EncFn)fn;
    void *p_ab = nullptr, *p_h = nullptr;
    cudaGetSymbolAddress(&p_ab, g_ab);
    cudaGetSymbolAddress(&p_h, g_h);
    make2d(enc, &maps.cr, d_in[1], 2048, 2048, 64, 128);
    make2d(enc, &maps.ci, d_in[2], 2048, 2048, 64, 128);
    make2d(enc, &maps.wr, d_in[3], 448, 448, 64, 56);
    make2d(enc, &maps.wi, d_in[4], 448, 448, 64, 56);
    make2d(enc, &maps.wg, d_in[6], 1792, 448, 64, 64);
    make2d(enc, &maps.wu, d_in[7], 1792, 448, 64, 64);
    make3d_half(enc, &maps.wd, d_in[8], 1792);
    make2d(enc, &maps.h, p_h, 1792, 2048, 64, 128);
    make3d_half(enc, &maps.ab, p_ab, 4096);
    make2d(enc, &maps.hs, p_h, 1792, 2048, 64, 16);
    make2d(enc, &maps.abs, p_ab, 448, 4096, 112, 16, false);
    for (int i = 0; i < 9; i++) cached[i] = d_in[i];
  }
  if (!attr_done) {
    cudaFuncSetAttribute(k1_kernel, cudaFuncAttributeMaxDynamicSharedMemorySize, K1_SMEM);
    cudaFuncSetAttribute(k2_kernel, cudaFuncAttributeMaxDynamicSharedMemorySize, K2_SMEM);
    attr_done = true;
  }
  PfPtrs pf;
  pf.wr = (const uint8_t*)d_in[3]; pf.wi = (const uint8_t*)d_in[4]; pf.wg = (const uint8_t*)d_in[6]; pf.wu = (const uint8_t*)d_in[7];
  pf.wd = (const uint8_t*)d_in[8]; pf.cr = (const uint8_t*)d_in[1]; pf.ci = (const uint8_t*)d_in[2];
  k1_kernel<<<128, 384, K1_SMEM>>>(maps.wr, maps.wi, maps.wg, maps.wu, maps.hs, maps.abs, (const __nv_bfloat16*)d_in[0], pf);

  cudaLaunchConfig_t cfg = {};
  cfg.gridDim = dim3(128); cfg.blockDim = dim3(384); cfg.dynamicSmemBytes = K2_SMEM; cfg.stream = cudaStreamPerThread;
  cudaLaunchAttribute at[1];
  at[0].id = cudaLaunchAttributeProgrammaticStreamSerialization;
  at[0].val.programmaticStreamSerializationAllowed = 1;
  cfg.attrs = at; cfg.numAttrs = 1;
  cudaLaunchKernelEx(&cfg, k2_kernel, maps.cr, maps.ci, maps.h, maps.ab, maps.wd, (const __nv_bfloat16*)d_in[0], (__nv_bfloat16*)d_out);
}
```

```cpp
#include <cuda_runtime.h>
#include <cuda_bf16.h>
#include <cuda.h>
#include <stdint.h>

namespace {

__device__ __align__(1024) __nv_bfloat16 g_ab[4096 * 448];
__device__ __align__(1024) __nv_bfloat16 g_h[2048 * 1792];
__device__ uint4 g_part[32 * 3 * 14 * 256];
__device__ __align__(1024) __nv_bfloat16 g_s[2048 * 448];
__device__ unsigned int g_flags[64];

#define DBG(k, i) do {} while (0)
#define DBGC(k, i) do {} while (0)

#define TIMEOUT(code) __trap()
#define SPIN_LIMIT (1 << 22)
__device__ __forceinline__ uint32_t s2u(const void* p) { return (uint32_t)__cvta_generic_to_shared(p); }
__device__ __forceinline__ void mbar_init(uint32_t b, int c) { asm volatile("mbarrier.init.shared::cta.b64 [%0], %1;" ::"r"(b), "r"(c)); }
__device__ __forceinline__ void mbar_expect(uint32_t b, uint32_t bytes) {
  asm volatile("mbarrier.arrive.expect_tx.shared::cta.b64 _, [%0], %1;" ::"r"(b), "r"(bytes) : "memory");
}
__device__ __forceinline__ void mbar_wait(uint32_t b, uint32_t ph, int code = 1) {
  uint32_t done = 0;
  int it = 0;
  while (true) {
    asm volatile("{.reg .pred p; mbarrier.try_wait.parity.shared::cta.b64 p, [%1], %2; selp.u32 %0,1,0,p;}" : "=r"(done) : "r"(b), "r"(ph) : "memory");
    if (done) break;
    if (++it > SPIN_LIMIT) { TIMEOUT(code); break; }
  }
}
__device__ __forceinline__ void mbar_arrive_cluster(uint32_t b, uint32_t cta) {
  uint32_t r;
  asm volatile("mapa.shared::cluster.u32 %0, %1, %2;" : "=r"(r) : "r"(b), "r"(cta));
  asm volatile("mbarrier.arrive.shared::cluster.b64 _, [%0];" ::"r"(r) : "memory");
}
__device__ __forceinline__ void tma2d(uint32_t dst, const CUtensorMap* m, int c0, int c1, uint32_t bar) {
  asm volatile("cp.async.bulk.tensor.2d.shared::cluster.global.mbarrier::complete_tx::bytes [%0], [%1, {%3,%4}], [%2];" ::"r"(dst), "l"(m), "r"(bar), "r"(c0), "r"(c1) : "memory");
}
__device__ __forceinline__ void tma2d_mc(uint32_t dst, const CUtensorMap* m, int c0, int c1, uint32_t bar, uint16_t mask) {
  asm volatile("cp.async.bulk.tensor.2d.shared::cluster.global.mbarrier::complete_tx::bytes.multicast::cluster [%0], [%1, {%3,%4}], [%2], %5;" ::"r"(dst), "l"(m), "r"(bar), "r"(c0), "r"(c1), "h"(mask) : "memory");
}
__device__ __forceinline__ void tma3d_mc(uint32_t dst, const CUtensorMap* m, int c0, int c1, int c2, uint32_t bar, uint16_t mask) {
  asm volatile("cp.async.bulk.tensor.3d.shared::cluster.global.mbarrier::complete_tx::bytes.multicast::cluster [%0], [%1, {%3,%4,%5}], [%2], %6;" ::"r"(dst), "l"(m), "r"(bar), "r"(c0), "r"(c1), "r"(c2), "h"(mask) : "memory");
}
__device__ __forceinline__ void tma2d_store(const CUtensorMap* m, uint32_t src, int c0, int c1) {
  asm volatile("cp.async.bulk.tensor.2d.global.shared::cta.bulk_group [%0, {%2,%3}], [%1];" ::"l"(m), "r"(src), "r"(c0), "r"(c1) : "memory");
}
__device__ __forceinline__ void bulk_commit() { asm volatile("cp.async.bulk.commit_group;" ::: "memory"); }
__device__ __forceinline__ void bulk_wait_read0() { asm volatile("cp.async.bulk.wait_group.read 0;" ::: "memory"); }
__device__ __forceinline__ void bulk_wait0() { asm volatile("cp.async.bulk.wait_group 0;" ::: "memory"); }
__device__ __forceinline__ void fence_async_smem() { asm volatile("fence.proxy.async.shared::cta;" ::: "memory"); }
__device__ __forceinline__ void prefetch_tmap(const CUtensorMap* m) { asm volatile("prefetch.tensormap [%0];" ::"l"(m) : "memory"); }
__device__ __forceinline__ void l2_prefetch(const void* p, uint32_t bytes) {
  asm volatile("cp.async.bulk.prefetch.L2.global [%0], %1;" ::"l"(p), "r"(bytes) : "memory");
}
__device__ __forceinline__ void cluster_arrive_relaxed() { asm volatile("barrier.cluster.arrive.relaxed.aligned;" ::: "memory"); }
__device__ __forceinline__ void cluster_wait() { asm volatile("barrier.cluster.wait.aligned;" ::: "memory"); }
__device__ __forceinline__ void wg_fence() { __syncwarp(); asm volatile("wgmma.fence.sync.aligned;" ::: "memory"); }
__device__ __forceinline__ void wg_commit() { asm volatile("wgmma.commit_group.sync.aligned;" ::: "memory"); }
template <int N> __device__ __forceinline__ void wg_wait() { __syncwarp(); asm volatile("wgmma.wait_group.sync.aligned %0;" ::"n"(N) : "memory"); }
__device__ __forceinline__ void named_bar(int id, int n) { asm volatile("bar.sync %0, %1;" ::"r"(id), "r"(n) : "memory"); }
__device__ __forceinline__ void named_arrive(int id, int n) { asm volatile("bar.arrive %0, %1;" ::"r"(id), "r"(n) : "memory"); }
template <int N> __device__ __forceinline__ void reg_inc() { asm volatile("setmaxnreg.inc.sync.aligned.u32 %0;" ::"n"(N)); }
template <int N> __device__ __forceinline__ void reg_dec() { asm volatile("setmaxnreg.dec.sync.aligned.u32 %0;" ::"n"(N)); }
__device__ __forceinline__ void pdl_wait() { asm volatile("griddepcontrol.wait;" ::: "memory"); }
__device__ __forceinline__ void pdl_launch() { asm volatile("griddepcontrol.launch_dependents;" ::: "memory"); }

__device__ __forceinline__ uint32_t make_desc(uint32_t addr, uint32_t lbo, uint32_t  ) {
  return ((addr & 0x3FFFF) >> 4) | ((lbo >> 4) << 16);
}
__device__ __forceinline__ void stmatrix_x4(uint32_t addr, uint32_t r0, uint32_t r1, uint32_t r2, uint32_t r3) {
  asm volatile("stmatrix.sync.aligned.m8n8.x4.shared.b16 [%0], {%1,%2,%3,%4};" ::"r"(addr), "r"(r0), "r"(r1), "r"(r2), "r"(r3) : "memory");
}
__device__ __forceinline__ uint4 lds128(uint32_t a) {
  uint4 v;
  asm volatile("ld.shared.v4.u32 {%0,%1,%2,%3}, [%4];" : "=r"(v.x), "=r"(v.y), "=r"(v.z), "=r"(v.w) : "r"(a) : "memory");
  return v;
}
__device__ __forceinline__ void sts128(uint32_t a, uint4 v) {
  asm volatile("st.shared.v4.u32 [%0], {%1,%2,%3,%4};" ::"r"(a), "r"(v.x), "r"(v.y), "r"(v.z), "r"(v.w) : "memory");
}
__device__ __forceinline__ void stg128(void* p, uint4 v) {
  asm volatile("st.global.v4.u32 [%0], {%1,%2,%3,%4};" ::"l"(p), "r"(v.x), "r"(v.y), "r"(v.z), "r"(v.w) : "memory");
}
__device__ __forceinline__ void cp_async16(uint32_t dst, const void* src) {
  asm volatile("cp.async.cg.shared.global [%0], [%1], 16;" ::"r"(dst), "l"(src) : "memory");
}
__device__ __forceinline__ void cp_async8(uint32_t dst, const void* src) {
  asm volatile("cp.async.ca.shared.global [%0], [%1], 8;" ::"r"(dst), "l"(src) : "memory");
}
__device__ __forceinline__ uint2 lds64(uint32_t a) {
  uint2 v;
  asm volatile("ld.shared.v2.u32 {%0,%1}, [%2];" : "=r"(v.x), "=r"(v.y) : "r"(a) : "memory");
  return v;
}
__device__ __forceinline__ void cp_async_wait_all() { asm volatile("cp.async.wait_all;" ::: "memory"); }
__device__ __forceinline__ uint32_t pack_bf16(float lo, float hi) {
  uint32_t r;
  asm("cvt.rn.bf16x2.f32 %0, %1, %2;" : "=r"(r) : "f"(hi), "f"(lo));
  return r;
}
__device__ __forceinline__ uint32_t hmul2_bf16(uint32_t a, uint32_t b) {
  uint32_t r;
  asm("mul.rn.bf16x2 %0, %1, %2;" : "=r"(r) : "r"(a), "r"(b));
  return r;
}
__device__ __forceinline__ uint32_t hsub2_bf16(uint32_t a, uint32_t b) {
  uint32_t r;
  asm("sub.rn.bf16x2 %0, %1, %2;" : "=r"(r) : "r"(a), "r"(b));
  return r;
}
__device__ __forceinline__ uint32_t hadd2_bf16(uint32_t a, uint32_t b) {
  uint32_t r;
  asm("add.rn.bf16x2 %0, %1, %2;" : "=r"(r) : "r"(a), "r"(b));
  return r;
}
__device__ __forceinline__ uint32_t hfma2_bf16(uint32_t a, uint32_t b, uint32_t c) {
  uint32_t r;
  asm("fma.rn.bf16x2 %0, %1, %2, %3;" : "=r"(r) : "r"(a), "r"(b), "r"(c));
  return r;
}
__device__ __forceinline__ bool mbar_test(uint32_t b, uint32_t ph) {
  uint32_t done;
  asm volatile("{.reg .pred p; mbarrier.test_wait.parity.shared::cta.b64 p, [%1], %2; selp.u32 %0,1,0,p;}" : "=r"(done) : "r"(b), "r"(ph) : "memory");
  return __all_sync(0xffffffffu, done != 0);
}
__device__ __forceinline__ uint4 ldg128_cg(const void* p) {
  uint4 v;
  asm volatile("ld.global.cg.v4.u32 {%0,%1,%2,%3}, [%4];" : "=r"(v.x), "=r"(v.y), "=r"(v.z), "=r"(v.w) : "l"(p) : "memory");
  return v;
}
__device__ __forceinline__ float bf_lo(uint32_t w) { return __uint_as_float(w << 16); }
__device__ __forceinline__ float bf_hi(uint32_t w) { return __uint_as_float(w & 0xffff0000u); }
__device__ __forceinline__ float rbf(float x) { return __bfloat162float(__float2bfloat16_rn(x)); }
__device__ __forceinline__ float ex2f(float x) { float r; asm("ex2.approx.ftz.f32 %0, %1;" : "=f"(r) : "f"(x)); return r; }
__device__ __forceinline__ float rcpf(float x) { float r; asm("rcp.approx.ftz.f32 %0, %1;" : "=f"(r) : "f"(x)); return r; }
__device__ __forceinline__ float tanhf_hw(float x) { float r; asm("tanh.approx.f32 %0, %1;" : "=f"(r) : "f"(x)); return r; }
__device__ __forceinline__ float gelu_tanh(float x) {
  const float c1 = 0.7978845608028654f;
  const float c2 = c1 * 0.044715f;
  const float t = tanhf_hw(x * fmaf(c2, x * x, c1));
  const float hx = 0.5f * x;
  return fmaf(hx, t, hx);
}
__device__ __forceinline__ float silu_f(float x) {
  const float hx = 0.5f * x;
  return fmaf(hx, tanhf_hw(hx), hx);
}

__device__ __forceinline__ void wgmma_n128_tb(float (&d)[64], uint32_t da, uint32_t db, int scale_d) {
  asm volatile(
    "{\n.reg .pred p;\n.reg .b64 da, db;\nsetp.ne.b32 p, %66, 0;\n"
    "mov.b64 da, {%64, 0x40000040};\nmov.b64 db, {%65, 0x40000040};\n"
    "wgmma.mma_async.sync.aligned.m64n128k16.f32.bf16.bf16 {%0, %1, %2, %3, %4, %5, %6, %7, %8, %9, %10, %11, %12, %13, %14, %15, %16, %17, %18, %19, %20, %21, %22, %23, %24, %25, %26, %27, %28, %29, %30, %31, %32, %33, %34, %35, %36, %37, %38, %39, %40, %41, %42, %43, %44, %45, %46, %47, %48, %49, %50, %51, %52, %53, %54, %55, %56, %57, %58, %59, %60, %61, %62, %63}, da, db, p, 1, 1, 0, 1;\n}\n"
    : "+f"(d[0]), "+f"(d[1]), "+f"(d[2]), "+f"(d[3]), "+f"(d[4]), "+f"(d[5]), "+f"(d[6]), "+f"(d[7]), "+f"(d[8]), "+f"(d[9]), "+f"(d[10]), "+f"(d[11]), "+f"(d[12]), "+f"(d[13]), "+f"(d[14]), "+f"(d[15]), "+f"(d[16]), "+f"(d[17]), "+f"(d[18]), "+f"(d[19]), "+f"(d[20]), "+f"(d[21]), "+f"(d[22]), "+f"(d[23]), "+f"(d[24]), "+f"(d[25]), "+f"(d[26]), "+f"(d[27]), "+f"(d[28]), "+f"(d[29]), "+f"(d[30]), "+f"(d[31]), "+f"(d[32]), "+f"(d[33]), "+f"(d[34]), "+f"(d[35]), "+f"(d[36]), "+f"(d[37]), "+f"(d[38]), "+f"(d[39]), "+f"(d[40]), "+f"(d[41]), "+f"(d[42]), "+f"(d[43]), "+f"(d[44]), "+f"(d[45]), "+f"(d[46]), "+f"(d[47]), "+f"(d[48]), "+f"(d[49]), "+f"(d[50]), "+f"(d[51]), "+f"(d[52]), "+f"(d[53]), "+f"(d[54]), "+f"(d[55]), "+f"(d[56]), "+f"(d[57]), "+f"(d[58]), "+f"(d[59]), "+f"(d[60]), "+f"(d[61]), "+f"(d[62]), "+f"(d[63])
    : "r"(da), "r"(db), "r"(scale_d));
}
__device__ __forceinline__ void wgmma_n128_tb_p(float (&d)[64], uint32_t da, uint32_t db, int scale_d, int enable) {
  asm volatile(
    "{\n.reg .pred p;\n.reg .b64 da, db;\nsetp.ne.b32 p, %66, 0;\n.reg .pred q;\nsetp.ne.b32 q, %67, 0;\n"
    "mov.b64 da, {%64, 0x40000040};\nmov.b64 db, {%65, 0x40000040};\n"
    "@q wgmma.mma_async.sync.aligned.m64n128k16.f32.bf16.bf16 {%0, %1, %2, %3, %4, %5, %6, %7, %8, %9, %10, %11, %12, %13, %14, %15, %16, %17, %18, %19, %20, %21, %22, %23, %24, %25, %26, %27, %28, %29, %30, %31, %32, %33, %34, %35, %36, %37, %38, %39, %40, %41, %42, %43, %44, %45, %46, %47, %48, %49, %50, %51, %52, %53, %54, %55, %56, %57, %58, %59, %60, %61, %62, %63}, da, db, p, 1, 1, 0, 1;\n}\n"
    : "+f"(d[0]), "+f"(d[1]), "+f"(d[2]), "+f"(d[3]), "+f"(d[4]), "+f"(d[5]), "+f"(d[6]), "+f"(d[7]), "+f"(d[8]), "+f"(d[9]), "+f"(d[10]), "+f"(d[11]), "+f"(d[12]), "+f"(d[13]), "+f"(d[14]), "+f"(d[15]), "+f"(d[16]), "+f"(d[17]), "+f"(d[18]), "+f"(d[19]), "+f"(d[20]), "+f"(d[21]), "+f"(d[22]), "+f"(d[23]), "+f"(d[24]), "+f"(d[25]), "+f"(d[26]), "+f"(d[27]), "+f"(d[28]), "+f"(d[29]), "+f"(d[30]), "+f"(d[31]), "+f"(d[32]), "+f"(d[33]), "+f"(d[34]), "+f"(d[35]), "+f"(d[36]), "+f"(d[37]), "+f"(d[38]), "+f"(d[39]), "+f"(d[40]), "+f"(d[41]), "+f"(d[42]), "+f"(d[43]), "+f"(d[44]), "+f"(d[45]), "+f"(d[46]), "+f"(d[47]), "+f"(d[48]), "+f"(d[49]), "+f"(d[50]), "+f"(d[51]), "+f"(d[52]), "+f"(d[53]), "+f"(d[54]), "+f"(d[55]), "+f"(d[56]), "+f"(d[57]), "+f"(d[58]), "+f"(d[59]), "+f"(d[60]), "+f"(d[61]), "+f"(d[62]), "+f"(d[63])
    : "r"(da), "r"(db), "r"(scale_d), "r"(enable));
}
__device__ __forceinline__ void wgmma_n112(float (&d)[56], uint32_t da, uint32_t db, int scale_d) {
  asm volatile(
    "{\n.reg .pred p;\n.reg .b64 da, db;\nsetp.ne.b32 p, %58, 0;\n"
    "mov.b64 da, {%56, 0x40000040};\nmov.b64 db, {%57, 0x40000040};\n"
    "wgmma.mma_async.sync.aligned.m64n112k16.f32.bf16.bf16 {%0, %1, %2, %3, %4, %5, %6, %7, %8, %9, %10, %11, %12, %13, %14, %15, %16, %17, %18, %19, %20, %21, %22, %23, %24, %25, %26, %27, %28, %29, %30, %31, %32, %33, %34, %35, %36, %37, %38, %39, %40, %41, %42, %43, %44, %45, %46, %47, %48, %49, %50, %51, %52, %53, %54, %55}, da, db, p, 1, 1, 0, 0;\n}\n"
    : "+f"(d[0]), "+f"(d[1]), "+f"(d[2]), "+f"(d[3]), "+f"(d[4]), "+f"(d[5]), "+f"(d[6]), "+f"(d[7]), "+f"(d[8]), "+f"(d[9]), "+f"(d[10]), "+f"(d[11]), "+f"(d[12]), "+f"(d[13]), "+f"(d[14]), "+f"(d[15]), "+f"(d[16]), "+f"(d[17]), "+f"(d[18]), "+f"(d[19]), "+f"(d[20]), "+f"(d[21]), "+f"(d[22]), "+f"(d[23]), "+f"(d[24]), "+f"(d[25]), "+f"(d[26]), "+f"(d[27]), "+f"(d[28]), "+f"(d[29]), "+f"(d[30]), "+f"(d[31]), "+f"(d[32]), "+f"(d[33]), "+f"(d[34]), "+f"(d[35]), "+f"(d[36]), "+f"(d[37]), "+f"(d[38]), "+f"(d[39]), "+f"(d[40]), "+f"(d[41]), "+f"(d[42]), "+f"(d[43]), "+f"(d[44]), "+f"(d[45]), "+f"(d[46]), "+f"(d[47]), "+f"(d[48]), "+f"(d[49]), "+f"(d[50]), "+f"(d[51]), "+f"(d[52]), "+f"(d[53]), "+f"(d[54]), "+f"(d[55])
    : "r"(da), "r"(db), "r"(scale_d));
}
__device__ __forceinline__ void wgmma_n224_tb(float (&d)[112], uint32_t da, uint32_t db, int scale_d) {
  asm volatile(
    "{\n.reg .pred p;\n.reg .b64 da, db;\nsetp.ne.b32 p, %114, 0;\n"
    "mov.b64 da, {%112, 0x40000040};\nmov.b64 db, {%113, 0x40000040};\n"
    "wgmma.mma_async.sync.aligned.m64n224k16.f32.bf16.bf16 {%0, %1, %2, %3, %4, %5, %6, %7, %8, %9, %10, %11, %12, %13, %14, %15, %16, %17, %18, %19, %20, %21, %22, %23, %24, %25, %26, %27, %28, %29, %30, %31, %32, %33, %34, %35, %36, %37, %38, %39, %40, %41, %42, %43, %44, %45, %46, %47, %48, %49, %50, %51, %52, %53, %54, %55, %56, %57, %58, %59, %60, %61, %62, %63, %64, %65, %66, %67, %68, %69, %70, %71, %72, %73, %74, %75, %76, %77, %78, %79, %80, %81, %82, %83, %84, %85, %86, %87, %88, %89, %90, %91, %92, %93, %94, %95, %96, %97, %98, %99, %100, %101, %102, %103, %104, %105, %106, %107, %108, %109, %110, %111}, da, db, p, 1, 1, 0, 1;\n}\n"
    : "+f"(d[0]), "+f"(d[1]), "+f"(d[2]), "+f"(d[3]), "+f"(d[4]), "+f"(d[5]), "+f"(d[6]), "+f"(d[7]), "+f"(d[8]), "+f"(d[9]), "+f"(d[10]), "+f"(d[11]), "+f"(d[12]), "+f"(d[13]), "+f"(d[14]), "+f"(d[15]), "+f"(d[16]), "+f"(d[17]), "+f"(d[18]), "+f"(d[19]), "+f"(d[20]), "+f"(d[21]), "+f"(d[22]), "+f"(d[23]), "+f"(d[24]), "+f"(d[25]), "+f"(d[26]), "+f"(d[27]), "+f"(d[28]), "+f"(d[29]), "+f"(d[30]), "+f"(d[31]), "+f"(d[32]), "+f"(d[33]), "+f"(d[34]), "+f"(d[35]), "+f"(d[36]), "+f"(d[37]), "+f"(d[38]), "+f"(d[39]), "+f"(d[40]), "+f"(d[41]), "+f"(d[42]), "+f"(d[43]), "+f"(d[44]), "+f"(d[45]), "+f"(d[46]), "+f"(d[47]), "+f"(d[48]), "+f"(d[49]), "+f"(d[50]), "+f"(d[51]), "+f"(d[52]), "+f"(d[53]), "+f"(d[54]), "+f"(d[55]), "+f"(d[56]), "+f"(d[57]), "+f"(d[58]), "+f"(d[59]), "+f"(d[60]), "+f"(d[61]), "+f"(d[62]), "+f"(d[63]), "+f"(d[64]), "+f"(d[65]), "+f"(d[66]), "+f"(d[67]), "+f"(d[68]), "+f"(d[69]), "+f"(d[70]), "+f"(d[71]), "+f"(d[72]), "+f"(d[73]), "+f"(d[74]), "+f"(d[75]), "+f"(d[76]), "+f"(d[77]), "+f"(d[78]), "+f"(d[79]), "+f"(d[80]), "+f"(d[81]), "+f"(d[82]), "+f"(d[83]), "+f"(d[84]), "+f"(d[85]), "+f"(d[86]), "+f"(d[87]), "+f"(d[88]), "+f"(d[89]), "+f"(d[90]), "+f"(d[91]), "+f"(d[92]), "+f"(d[93]), "+f"(d[94]), "+f"(d[95]), "+f"(d[96]), "+f"(d[97]), "+f"(d[98]), "+f"(d[99]), "+f"(d[100]), "+f"(d[101]), "+f"(d[102]), "+f"(d[103]), "+f"(d[104]), "+f"(d[105]), "+f"(d[106]), "+f"(d[107]), "+f"(d[108]), "+f"(d[109]), "+f"(d[110]), "+f"(d[111])
    : "r"(da), "r"(db), "r"(scale_d));
}

constexpr int K1_NS = 5;
constexpr int K1_A_BYTES = 7 * 16384;
constexpr int K1_B_OFF = K1_A_BYTES;
constexpr int K1_STG_OFF = K1_B_OFF + K1_NS * 16384;
constexpr int K1_BAR_OFF = K1_STG_OFF + 8 * 4096;
constexpr int K1_SMEM = K1_BAR_OFF + 256 + 1024;

struct K1Ctx {
  uint32_t sb, bar_full, rel0, rel1;
  uint32_t dA, dBk, dBn;
  bool lane0;
  const CUtensorMap* tm_hs;
  const CUtensorMap* tm_abs;
};
__device__ __forceinline__ void k1_release(const K1Ctx& c, int slot) {
  if (c.lane0) {
    asm volatile("mbarrier.arrive.shared::cluster.b64 _, [%0];" ::"r"(c.rel0 + 8 * slot) : "memory");
    asm volatile("mbarrier.arrive.shared::cluster.b64 _, [%0];" ::"r"(c.rel1 + 8 * slot) : "memory");
  }
}

__device__ __forceinline__ void k1_unit_ab(const K1Ctx& c, int warp, int lane, int mt, int j) {
  const uint32_t stg = c.sb + K1_STG_OFF + warp * 4096;
  const int wq = warp & 3;
  const int st_row = (lane & 7) + 8 * ((lane >> 3) & 1);
  const int st_chunk = lane >> 4;
  float acc[2][56];
  int slot = 0; uint32_t ph = 0;
#pragma unroll 1
  for (int kb = 0; kb < 7; kb++) {
    const int pslot = (slot == 0) ? K1_NS - 1 : slot - 1;
    mbar_wait(c.bar_full + 8 * slot, ph, 3);
    if (kb == 6) named_arrive(2, 256);
    if (kb == 0 && (threadIdx.x & 127) == 0) DBG(0, 4);
    if ((threadIdx.x & 127) == 0) DBGC(1, 46 + kb);
    wg_fence();
    const uint32_t da = c.dA + kb * 1024;
    const uint32_t db = c.dBk + slot * 1024;
#pragma unroll
    for (int k = 0; k < 4; k++) {
      wgmma_n112(acc[0], da + k * 2, db + k * 2, (kb | k) != 0);
      wgmma_n112(acc[1], da + 512 + k * 2, db + k * 2, (kb | k) != 0);
    }
    wg_commit();
    if (kb > 0) { wg_wait<1>(); k1_release(c, pslot); }
    if (++slot == K1_NS) { slot = 0; ph ^= 1; }
  }
  wg_wait<0>();
  k1_release(c, 6 % K1_NS);
  if ((threadIdx.x & 127) == 0) DBG(0, 5);
  const uint32_t sgn = (j < 4) ? 0u : 0x80008000u;
  const uint32_t sa = stg + st_row * 224 + st_chunk * 16;
  const int row0 = (j < 4 ? 0 : 2048) + mt * 128 + wq * 16;
#pragma unroll
  for (int h = 0; h < 2; h++) {
    if (h == 1) { if (c.lane0) bulk_wait_read0(); __syncwarp(); }
#pragma unroll
    for (int g = 0; g < 14; g += 2) {
      const float* a = &acc[h][4 * g];
      stmatrix_x4(sa + g * 16, pack_bf16(a[0], a[1]) ^ sgn, pack_bf16(a[2], a[3]) ^ sgn, pack_bf16(a[4], a[5]) ^ sgn, pack_bf16(a[6], a[7]) ^ sgn);
    }
    fence_async_smem();
    __syncwarp();
    if (c.lane0) { tma2d_store(c.tm_abs, stg, (j & 3) * 112, row0 + h * 64); bulk_commit(); }
  }
}

__device__ __forceinline__ void k1_unit_gu(const K1Ctx& c, int warp, int lane, int mt, int unit, int fb, int hsel) {
  const uint32_t stg = c.sb + K1_STG_OFF + warp * 4096;
  const int wq = warp & 3;
  const int full = (unit < 4);
  float acc[2][64];
  const uint32_t dA0 = c.dA + (full ? 0 : hsel * 512);
  int slot = (unit * 7) % K1_NS; uint32_t ph = ((unit * 7) / K1_NS) & 1;
  named_bar(2 + ((unit - 1) & 1), 256);
  if (full) {
#pragma unroll 1
    for (int kb = 0; kb < 7; kb++) {
      const int pslot = (slot == 0) ? K1_NS - 1 : slot - 1;
      mbar_wait(c.bar_full + 8 * slot, ph, 4);
      if (kb == 6) named_arrive(2 + (unit & 1), 256);
      if (kb == 0 && (threadIdx.x & 127) == 0) DBG(0, 4 + 3 * unit);
      wg_fence();
      const uint32_t da = dA0 + kb * 1024;
      const uint32_t db = c.dBn + slot * 1024;
#pragma unroll
      for (int k = 0; k < 4; k++) {
        wgmma_n128_tb(acc[0], da + k * 2, db + k * 128, (kb | k) != 0);
        wgmma_n128_tb(acc[1], da + 512 + k * 2, db + k * 128, (kb | k) != 0);
      }
      wg_commit();
      if (kb > 0) { wg_wait<1>(); k1_release(c, pslot); }
      if (++slot == K1_NS) { slot = 0; ph ^= 1; }
    }
  } else {
#pragma unroll 1
    for (int kb = 0; kb < 7; kb++) {
      const int pslot = (slot == 0) ? K1_NS - 1 : slot - 1;
      mbar_wait(c.bar_full + 8 * slot, ph, 5);
      if (kb == 0 && (threadIdx.x & 127) == 0) DBG(0, 4 + 3 * unit);
      wg_fence();
      const uint32_t da = dA0 + kb * 1024;
      const uint32_t db = c.dBn + slot * 1024;
#pragma unroll
      for (int k = 0; k < 4; k++) wgmma_n128_tb(acc[0], da + k * 2, db + k * 128, (kb | k) != 0);
      wg_commit();
      if (kb > 0) { wg_wait<1>(); k1_release(c, pslot); }
      if (++slot == K1_NS) { slot = 0; ph ^= 1; }
    }
  }
  wg_wait<0>();
  k1_release(c, (slot == 0) ? K1_NS - 1 : slot - 1);
  if ((threadIdx.x & 127) == 0) DBG(0, 5 + 3 * unit);
  const int st_row = (lane & 7) + 8 * ((lane >> 3) & 1);
  const int st_chunk = lane >> 4;
  const uint32_t sa = stg + st_row * 128;
  const int row0 = mt * 128 + (full ? 0 : hsel * 64) + wq * 16;
  if (c.lane0) bulk_wait_read0();
  __syncwarp();
#pragma unroll
  for (int h = 0; h < 2; h++) {
    if (h == 1 && !full) break;
#pragma unroll
    for (int g = 0; g < 8; g += 2) {
      uint32_t pk[4];
#pragma unroll
      for (int e = 0; e < 4; e++) {
        const int i = 4 * g + 2 * e;
        const uint32_t g2 = pack_bf16(acc[h][i], acc[h][i + 1]);
        const uint32_t u2 = pack_bf16(acc[h][32 + i], acc[h][32 + i + 1]);
        pk[e] = hmul2_bf16(pack_bf16(gelu_tanh(bf_lo(g2)), gelu_tanh(bf_hi(g2))), u2);
      }
      stmatrix_x4(sa + h * 2048 + (((g + st_chunk) ^ (st_row & 7)) * 16), pk[0], pk[1], pk[2], pk[3]);
    }
    fence_async_smem();
    __syncwarp();
    if (c.lane0) { tma2d_store(c.tm_hs, stg + h * 2048, fb * 64, row0 + h * 64); bulk_commit(); }
  }
}

struct PfPtrs { const uint8_t* wr; const uint8_t* wi; const uint8_t* wg; const uint8_t* wu; const uint8_t* wd; const uint8_t* cr; const uint8_t* ci; };

__global__ void __cluster_dims__(2, 1, 1) __launch_bounds__(384, 1)
k1_kernel(const __grid_constant__ CUtensorMap tm_wr, const __grid_constant__ CUtensorMap tm_wi,
          const __grid_constant__ CUtensorMap tm_wg, const __grid_constant__ CUtensorMap tm_wu,
          const __grid_constant__ CUtensorMap tm_hs, const __grid_constant__ CUtensorMap tm_abs,
          const __nv_bfloat16* __restrict__ x, const PfPtrs pf) {
  extern __shared__ uint8_t smem_raw[];
  const uint32_t sb = (s2u(smem_raw) + 1023) & ~1023u;
  const int tid = threadIdx.x, warp = tid >> 5, lane = tid & 31;
  uint32_t rank;
  asm volatile("mov.u32 %0, %%cluster_ctarank;" : "=r"(rank));
  const int cid = blockIdx.x >> 1;
  const int p = cid >> 3, j = cid & 7;
  const int mt = 2 * p + (int)rank;
  const uint32_t bar_full = sb + K1_BAR_OFF;
  const uint32_t bar_empty = bar_full + 8 * K1_NS;
  const int fb_base = 7 * (j >> 1);
  const int fb0 = fb_base + ((j & 1) ? 4 : 0);
  const int fbh = fb_base + 3;
  const CUtensorMap* tw = (j < 4) ? &tm_wr : &tm_wi;
  const CUtensorMap* tgu = rank ? &tm_wu : &tm_wg;

  if (tid == 0) DBG(0, 0);
  if (tid == 256) {
    for (int i = 0; i < K1_NS; i++) { mbar_init(bar_full + 8 * i, 1); mbar_init(bar_empty + 8 * i, 8); }
    asm volatile("fence.mbarrier_init.release.cluster;" ::: "memory");
    prefetch_tmap(tw);
    prefetch_tmap(tgu);
    prefetch_tmap(&tm_abs);
    prefetch_tmap(&tm_hs);
    if (blockIdx.x < 64) g_flags[blockIdx.x] = 0;
  }
  __syncwarp();
  cluster_arrive_relaxed();
  pdl_launch();

  if (warp >= 8) {
    reg_dec<40>();
    cluster_wait();
    if (tid == 256) {
      int slot = 0; uint32_t ph = 0;
      int kb = 0, unit = 0;
#pragma unroll 1
      for (int s = 0; s < 35; s++) {
        if (s >= K1_NS) mbar_wait(bar_empty + 8 * slot, ph ^ 1, 2);
        DBG(0, 20 + s);
        const uint32_t dst = sb + K1_B_OFF + slot * 16384;
        if (unit == 0) {
          mbar_expect(bar_full + 8 * slot, 14336);
          tma2d_mc(dst + rank * 7168, tw, kb * 64, (j & 3) * 112 + rank * 56, bar_full + 8 * slot, 3);
        } else {
          const int fb = (unit == 4) ? fbh : (fb0 + unit - 1);
          mbar_expect(bar_full + 8 * slot, 16384);
          tma2d_mc(dst + rank * 8192, tgu, fb * 64, kb * 64, bar_full + 8 * slot, 3);
        }
        if (++kb == 7) { kb = 0; unit++; }
        if (++slot == K1_NS) { slot = 0; ph ^= 1; }
      }
    } else if (tid == 288) {
      const int b = blockIdx.x;
      l2_prefetch(pf.wg + b * 12544, 12544);
      l2_prefetch(pf.wu + b * 12544, 12544);
    }
  } else {
    reg_inc<232>();
    const int wg = warp >> 2;
    {
      const int c = lane & 7;
      const int r0 = warp * 16 + (lane >> 3);
      const uint4* src = reinterpret_cast<const uint4*>(x + (size_t)(mt * 128 + r0) * 448) + c;
      uint4 nx[7];
#pragma unroll
      for (int b = 0; b < 7; b++)
        asm volatile("ld.global.nc.v4.u32 {%0,%1,%2,%3}, [%4];" : "=r"(nx[b].x), "=r"(nx[b].y), "=r"(nx[b].z), "=r"(nx[b].w) : "l"(src + b * 8) : "memory");
#pragma unroll
      for (int pass = 1; pass < 4; pass++) asm volatile("prefetch.global.L2 [%0];" ::"l"(src + pass * 4 * 56 + c * 7 - c) : "memory");
#pragma unroll 1
      for (int pass = 0; pass < 4; pass++) {
        uint4 v[7];
#pragma unroll
        for (int b = 0; b < 7; b++) v[b] = nx[b];
        if (pass < 3) {
          const uint4* s2 = src + (pass + 1) * 4 * 56;
#pragma unroll
          for (int b = 0; b < 7; b++)
            asm volatile("ld.global.nc.v4.u32 {%0,%1,%2,%3}, [%4];" : "=r"(nx[b].x), "=r"(nx[b].y), "=r"(nx[b].z), "=r"(nx[b].w) : "l"(s2 + b * 8) : "memory");
        }
        float s0 = 0.f, s1 = 0.f, s2v = 0.f, s3 = 0.f;
#pragma unroll
        for (int b = 0; b < 7; b++) {
          s0 += bf_lo(v[b].x) + bf_hi(v[b].x); s1 += bf_lo(v[b].y) + bf_hi(v[b].y);
          s2v += bf_lo(v[b].z) + bf_hi(v[b].z); s3 += bf_lo(v[b].w) + bf_hi(v[b].w);
        }
        float m = (s0 + s1) + (s2v + s3);
        m += __shfl_xor_sync(0xffffffffu, m, 1);
        m += __shfl_xor_sync(0xffffffffu, m, 2);
        m += __shfl_xor_sync(0xffffffffu, m, 4);
        m *= (1.0f / 448.0f);
        float q0 = 0.f, q1 = 0.f, q2 = 0.f, q3 = 0.f;
#pragma unroll
        for (int b = 0; b < 7; b++) {
          float d;
          d = bf_lo(v[b].x) - m; q0 = fmaf(d, d, q0); d = bf_hi(v[b].x) - m; q1 = fmaf(d, d, q1);
          d = bf_lo(v[b].y) - m; q2 = fmaf(d, d, q2); d = bf_hi(v[b].y) - m; q3 = fmaf(d, d, q3);
          d = bf_lo(v[b].z) - m; q0 = fmaf(d, d, q0); d = bf_hi(v[b].z) - m; q1 = fmaf(d, d, q1);
          d = bf_lo(v[b].w) - m; q2 = fmaf(d, d, q2); d = bf_hi(v[b].w) - m; q3 = fmaf(d, d, q3);
        }
        float q = (q0 + q1) + (q2 + q3);
        q += __shfl_xor_sync(0xffffffffu, q, 1);
        q += __shfl_xor_sync(0xffffffffu, q, 2);
        q += __shfl_xor_sync(0xffffffffu, q, 4);
        const float var_b = rbf(q * (1.0f / 448.0f));
        const float den = rbf(sqrtf(rbf(var_b + 1e-5f)));
        const float ri = 1.0f / den;
        const float rih = rbf(ri);
        const uint32_t rhi2 = pack_bf16(rih, rih), rlo2 = pack_bf16(ri - rih, ri - rih);
        const uint32_t m2 = pack_bf16(m, m);
        const int r = r0 + pass * 4;
        const uint32_t a0 = sb + r * 128 + ((c ^ (r & 7)) * 16);
#pragma unroll
        for (int b = 0; b < 7; b++) {
          uint32_t w4[4] = {v[b].x, v[b].y, v[b].z, v[b].w};
#pragma unroll
          for (int qq = 0; qq < 4; qq++) {
            const uint32_t dw = hsub2_bf16(w4[qq], m2);
            w4[qq] = hfma2_bf16(dw, rhi2, hmul2_bf16(dw, rlo2));
          }
          sts128(a0 + b * 16384, make_uint4(w4[0], w4[1], w4[2], w4[3]));
        }
      }
    }
    if (lane == 0) DBG(0, 59 + (warp & 3));
    asm volatile("fence.proxy.async.shared::cta;" ::: "memory");
    named_bar(1, 256);
    cluster_wait();
    if (tid == 0) DBG(0, 3);

    K1Ctx c;
    c.sb = sb; c.bar_full = bar_full; c.lane0 = (lane == 0);
    asm volatile("mapa.shared::cluster.u32 %0, %1, %2;" : "=r"(c.rel0) : "r"(bar_empty), "r"(0));
    asm volatile("mapa.shared::cluster.u32 %0, %1, %2;" : "=r"(c.rel1) : "r"(bar_empty), "r"(1));
    c.tm_hs = &tm_hs; c.tm_abs = &tm_abs;
    c.dA = make_desc(sb, 16, 1024);
    c.dBk = make_desc(sb + K1_B_OFF, 16, 1024);
    c.dBn = make_desc(sb + K1_B_OFF, 8192, 1024);
    if (wg == 0) {
      k1_unit_ab(c, warp, lane, mt, j);
      if (tid == 0) DBG(0, 6);
    }
#pragma unroll 1
    for (int unit = 2 - wg; unit < 5; unit += 2) {
      k1_unit_gu(c, warp, lane, mt, unit, (unit == 4) ? fbh : fb0 + unit - 1, j & 1);
      if ((tid & 127) == 0) DBG(0, 6 + 3 * unit);
    }
    if (lane == 0) bulk_wait0();
  }
  __syncwarp();
  cluster_arrive_relaxed();
  cluster_wait();
}

constexpr int K2_NS = 4;
constexpr int K2_STAGE = 16384 + 32768;
constexpr int K2_BAR_OFF = K2_NS * K2_STAGE;
constexpr int K2_SMEM = K2_BAR_OFF + 256 + 1024;
constexpr int K2_PITCH = 464;

__device__ __forceinline__ void spin_flag(const unsigned int* flag, unsigned int target) {
  int it = 0;
  while (true) {
    unsigned int v;
    asm volatile("ld.acquire.gpu.global.u32 %0, [%1];" : "=r"(v) : "l"(flag) : "memory");
    if (v >= target) break;
    if (++it > SPIN_LIMIT) { TIMEOUT(20); break; }
  }
}

__global__ void __cluster_dims__(2, 1, 1) __launch_bounds__(384, 1)
k2_kernel(const __grid_constant__ CUtensorMap tm_cr, const __grid_constant__ CUtensorMap tm_ci, const __grid_constant__ CUtensorMap tm_h,
          const __grid_constant__ CUtensorMap tm_ab, const __grid_constant__ CUtensorMap tm_wd,
          const __nv_bfloat16* __restrict__ x, __nv_bfloat16* __restrict__ out) {
  extern __shared__ uint8_t smem_raw[];
  const uint32_t sb = (s2u(smem_raw) + 1023) & ~1023u;
  const int tid = threadIdx.x, warp = tid >> 5, lane = tid & 31;
  uint32_t rank;
  asm volatile("mov.u32 %0, %%cluster_ctarank;" : "=r"(rank));
  const int cid = blockIdx.x >> 1;
  const int q = cid & 3, n = (cid >> 2) & 1, p = cid >> 3;
  const int mt = 2 * p + (int)rank;
  const int tile = mt * 2 + n;
  const uint32_t bar_full = sb + K2_BAR_OFF;
  const uint32_t bar_empty = bar_full + 8 * K2_NS;
  const int g0 = (q == 0) ? 0 : (q == 1 ? 22 : (q == 2 ? 43 : 64));
  const int nkb = (q == 0) ? 22 : (q == 3 ? 28 : 21);

  if (tid == 0) DBG(1, 0);
  if (tid == 256) {
    for (int i = 0; i < K2_NS; i++) { mbar_init(bar_full + 8 * i, 1); mbar_init(bar_empty + 8 * i, 16); }
    asm volatile("fence.mbarrier_init.release.cluster;" ::: "memory");
    if (q == 3) { prefetch_tmap(&tm_h); prefetch_tmap(&tm_wd); }
    else { prefetch_tmap(&tm_cr); prefetch_tmap(&tm_ci); prefetch_tmap(&tm_ab); }
  }
  __syncwarp();
  cluster_arrive_relaxed();
  cluster_wait();

  if (warp >= 8) {
    reg_dec<40>();
    if (tid == 256) {
      const CUtensorMap* tb = (q < 3) ? &tm_ab : &tm_wd;
      const int kb0 = (q < 3) ? g0 : 0;
      int slot = 0; uint32_t ph = 0;
#pragma unroll 1
      for (int it = 0; it < nkb + K2_NS; it++) {
        const int s = (it < K2_NS) ? it : it - K2_NS;
        const bool pre = (it < K2_NS), post = (!pre && s < K2_NS);
        if (it == K2_NS) { pdl_wait(); DBG(1, 31); slot = 0; }
        if (!pre && !post) mbar_wait(bar_empty + 8 * slot, ph, 10);
        const uint32_t dst = sb + slot * K2_STAGE;
        const uint32_t fb = bar_full + 8 * slot;
        if (!post) mbar_expect(fb, K2_STAGE);
        const bool doA = pre ? (q < 3) : (post ? (q == 3) : true);
        const bool doB = pre ? (q == 3) : (post ? (q < 3) : true);
        if (doA) {
          const int g = g0 + s;
          const CUtensorMap* ta = (g < 32) ? &tm_cr : (g < 64 ? &tm_ci : &tm_h);
          tma2d(dst, ta, (g & 31) * 64 + ((g >= 96) ? 2048 : 0), mt * 128, fb);
        }
        if (doB) {
          tma3d_mc(dst + 16384 + (2 * rank) * 8192, tb, (2 * rank) * 64, n, (kb0 + s) * 64, fb, 3);
          tma3d_mc(dst + 16384 + (2 * rank + 1) * 8192, tb, (2 * rank + 1) * 64, n, (kb0 + s) * 64, fb, 3);
        }
        if (++slot == K2_NS) { slot = 0; if (!pre && !post) ph ^= 1; }
      }
    }
  } else {
    reg_inc<232>();
    const int wg = warp >> 2;
    float acc[112];
    uint32_t rel0, rel1;
    asm volatile("mapa.shared::cluster.u32 %0, %1, %2;" : "=r"(rel0) : "r"(bar_empty), "r"(0));
    asm volatile("mapa.shared::cluster.u32 %0, %1, %2;" : "=r"(rel1) : "r"(bar_empty), "r"(1));
    const uint32_t dA0 = make_desc(sb + wg * 8192, 16, 1024);
    const uint32_t dB0 = make_desc(sb + 16384, 8192, 1024);
    int slot = 0; uint32_t ph = 0;
#pragma unroll 1
    for (int s = 0; s < nkb; s++) {
      mbar_wait(bar_full + 8 * slot, ph, 11);
      if (tid == 0) DBG(1, 1 + s);
      if (tid == 0 && (s == 5 || s == 15)) DBGC(1, 53 + (s == 15));
      if (tid == 0 && (s == 23 || s == 27)) DBGC(1, 55 + (s == 27));
      wg_fence();
      const uint32_t da = dA0 + slot * (K2_STAGE / 16);
      const uint32_t db = dB0 + slot * (K2_STAGE / 16);
#pragma unroll
      for (int k = 0; k < 4; k++) wgmma_n224_tb(acc, da + k * 2, db + k * 128, (s | k) != 0);
      wg_commit();
      if (s > 0) {
        wg_wait<1>();
        const int ps = (slot == 0) ? K2_NS - 1 : slot - 1;
        if (lane == 0) {
          asm volatile("mbarrier.arrive.shared::cluster.b64 _, [%0];" ::"r"(rel0 + 8 * ps) : "memory");
          asm volatile("mbarrier.arrive.shared::cluster.b64 _, [%0];" ::"r"(rel1 + 8 * ps) : "memory");
        }
      }
      if (++slot == K2_NS) { slot = 0; ph ^= 1; }
    }
    wg_wait<0>();
    pdl_wait();
    if (tid == 0) DBG(1, 29);
    if (q < 3) {
      uint4* part = g_part + (size_t)(tile * 3 + q) * (14 * 256) + tid;
#pragma unroll
      for (int g = 0; g < 14; g++)
        part[g * 256] = make_uint4(pack_bf16(acc[8 * g], acc[8 * g + 1]), pack_bf16(acc[8 * g + 2], acc[8 * g + 3]),
                                   pack_bf16(acc[8 * g + 4], acc[8 * g + 5]), pack_bf16(acc[8 * g + 6], acc[8 * g + 7]));
      __threadfence();
      named_bar(1, 256);
      if (tid == 0) atomicAdd(&g_flags[tile], 1u);
    } else {
      if (lane == 0) spin_flag(&g_flags[tile], 3u);
      named_bar(1, 256);
      if (tid == 0) DBG(1, 30);
      const uint32_t wbase = sb + warp * (42 * 512);
      const uint4* pp = g_part + (size_t)tile * (3 * 14 * 256) + tid;
#pragma unroll 6
      for (int i = 0; i < 42; i++) cp_async16(wbase + i * 512 + lane * 16, pp + i * 256);
      const int lc = (lane < 28) ? lane : 27;
      const size_t gbase = (size_t)(mt * 128 + warp * 16) * 448 + n * 224 + lc * 8;
      const uint32_t xs = sb + 8 * (42 * 512) + warp * 2048 + lane * 16;
      (void)xs;
      uint32_t gw[56];
#pragma unroll
      for (int i = 0; i < 56; i++) {
        const uint32_t f2 = pack_bf16(acc[2 * i], acc[2 * i + 1]);
        gw[i] = pack_bf16(silu_f(bf_lo(f2)), silu_f(bf_hi(f2)));
      }
      uint4 xv[16];
#pragma unroll
      for (int t = 0; t < 16; t++) xv[t] = ldg128_cg(x + gbase + t * 448);
      if (tid == 0) DBG(1, 62);
      cp_async_wait_all();
#pragma unroll
      for (int g = 0; g < 14; g++) {
        const uint4 a = lds128(wbase + g * 512 + lane * 16), b = lds128(wbase + (14 + g) * 512 + lane * 16), cc = lds128(wbase + (28 + g) * 512 + lane * 16);
        gw[4 * g] = hmul2_bf16(pack_bf16(bf_lo(a.x) + bf_lo(b.x) + bf_lo(cc.x), bf_hi(a.x) + bf_hi(b.x) + bf_hi(cc.x)), gw[4 * g]);
        gw[4 * g + 1] = hmul2_bf16(pack_bf16(bf_lo(a.y) + bf_lo(b.y) + bf_lo(cc.y), bf_hi(a.y) + bf_hi(b.y) + bf_hi(cc.y)), gw[4 * g + 1]);
        gw[4 * g + 2] = hmul2_bf16(pack_bf16(bf_lo(a.z) + bf_lo(b.z) + bf_lo(cc.z), bf_hi(a.z) + bf_hi(b.z) + bf_hi(cc.z)), gw[4 * g + 2]);
        gw[4 * g + 3] = hmul2_bf16(pack_bf16(bf_lo(a.w) + bf_lo(b.w) + bf_lo(cc.w), bf_hi(a.w) + bf_hi(b.w) + bf_hi(cc.w)), gw[4 * g + 3]);
      }
      __syncwarp();
      const int st_row = (lane & 7) + 8 * ((lane >> 3) & 1);
      const uint32_t sa = wbase + st_row * K2_PITCH + (lane >> 4) * 16;
#pragma unroll
      for (int g = 0; g < 28; g += 2) stmatrix_x4(sa + g * 16, gw[2 * g], gw[2 * g + 1], gw[2 * g + 2], gw[2 * g + 3]);
      __syncwarp();
      const uint32_t lp = wbase + lc * 16;
#pragma unroll
      for (int t = 0; t < 16; t++) {
        const uint4 tv = lds128(lp + t * K2_PITCH);
        uint4 o;
        o.x = hadd2_bf16(xv[t].x, tv.x); o.y = hadd2_bf16(xv[t].y, tv.y); o.z = hadd2_bf16(xv[t].z, tv.z); o.w = hadd2_bf16(xv[t].w, tv.w);
        if (lane < 28) stg128(out + gbase + t * 448, o);
      }
    }
    if (tid == 0) DBG(1, 63);
  }
  __syncwarp();
  cluster_arrive_relaxed();
  cluster_wait();
}

typedef CUresult (*EncFn)(CUtensorMap*, CUtensorMapDataType, cuuint32_t, void*, const cuuint64_t*, const cuuint64_t*, const cuuint32_t*,
                          const cuuint32_t*, CUtensorMapInterleave, CUtensorMapSwizzle, CUtensorMapL2promotion, CUtensorMapFloatOOBfill);

void make2d(EncFn enc, CUtensorMap* tm, const void* ptr, uint64_t cols, uint64_t rows, uint32_t bc, uint32_t br, bool swz = true) {
  cuuint64_t gd[2] = {cols, rows};
  cuuint64_t gs[1] = {cols * 2};
  cuuint32_t bd[2] = {bc, br};
  cuuint32_t es[2] = {1, 1};
  enc(tm, CU_TENSOR_MAP_DATA_TYPE_BFLOAT16, 2, const_cast<void*>(ptr), gd, gs, bd, es, CU_TENSOR_MAP_INTERLEAVE_NONE,
      swz ? CU_TENSOR_MAP_SWIZZLE_128B : CU_TENSOR_MAP_SWIZZLE_NONE, CU_TENSOR_MAP_L2_PROMOTION_L2_128B, CU_TENSOR_MAP_FLOAT_OOB_FILL_NONE);
}
void make3d_half(EncFn enc, CUtensorMap* tm, const void* ptr, uint64_t rows) {
  cuuint64_t gd[3] = {224, 2, rows};
  cuuint64_t gs[2] = {448, 896};
  cuuint32_t bd[3] = {64, 1, 64};
  cuuint32_t es[3] = {1, 1, 1};
  enc(tm, CU_TENSOR_MAP_DATA_TYPE_BFLOAT16, 3, const_cast<void*>(ptr), gd, gs, bd, es, CU_TENSOR_MAP_INTERLEAVE_NONE,
      CU_TENSOR_MAP_SWIZZLE_128B, CU_TENSOR_MAP_L2_PROMOTION_L2_128B, CU_TENSOR_MAP_FLOAT_OOB_FILL_NONE);
}

struct Maps { CUtensorMap wr, wi, wg, wu, cr, ci, h, ab, wd, hs, abs; };

}

extern "C" void kernel_launch(void* const* d_in, const int* in_sizes, int n_in, void* d_out, int out_size) {
  (void)in_sizes; (void)n_in; (void)out_size;
  static Maps maps;
  static const void* cached[9] = {nullptr};
  static bool attr_done = false;
  bool same = true;
  for (int i = 0; i < 9; i++) same = same && (cached[i] == d_in[i]);
  if (!same) {
    void* fn = nullptr;
    cudaDriverEntryPointQueryResult qr;
    cudaGetDriverEntryPoint("cuTensorMapEncodeTiled", &fn, cudaEnableDefault, &qr);
    EncFn enc = (EncFn)fn;
    void *p_ab = nullptr, *p_h = nullptr;
    cudaGetSymbolAddress(&p_ab, g_ab);
    cudaGetSymbolAddress(&p_h, g_h);
    make2d(enc, &maps.cr, d_in[1], 2048, 2048, 64, 128);
    make2d(enc, &maps.ci, d_in[2], 2048, 2048, 64, 128);
    make2d(enc, &maps.wr, d_in[3], 448, 448, 64, 56);
    make2d(enc, &maps.wi, d_in[4], 448, 448, 64, 56);
    make2d(enc, &maps.wg, d_in[6], 1792, 448, 64, 64);
    make2d(enc, &maps.wu, d_in[7], 1792, 448, 64, 64);
    make3d_half(enc, &maps.wd, d_in[8], 1792);
    make2d(enc, &maps.h, p_h, 1792, 2048, 64, 128);
    make3d_half(enc, &maps.ab, p_ab, 4096);
    make2d(enc, &maps.hs, p_h, 1792, 2048, 64, 16);
    make2d(enc, &maps.abs, p_ab, 448, 4096, 112, 16, false);
    for (int i = 0; i < 9; i++) cached[i] = d_in[i];
  }
  if (!attr_done) {
    cudaFuncSetAttribute(k1_kernel, cudaFuncAttributeMaxDynamicSharedMemorySize, K1_SMEM);
    cudaFuncSetAttribute(k2_kernel, cudaFuncAttributeMaxDynamicSharedMemorySize, K2_SMEM);
    attr_done = true;
  }
  PfPtrs pf;
  pf.wr = (const uint8_t*)d_in[3]; pf.wi = (const uint8_t*)d_in[4]; pf.wg = (const uint8_t*)d_in[6]; pf.wu = (const uint8_t*)d_in[7];
  pf.wd = (const uint8_t*)d_in[8]; pf.cr = (const uint8_t*)d_in[1]; pf.ci = (const uint8_t*)d_in[2];
  k1_kernel<<<128, 384, K1_SMEM>>>(maps.wr, maps.wi, maps.wg, maps.wu, maps.hs, maps.abs, (const __nv_bfloat16*)d_in[0], pf);

  cudaLaunchConfig_t cfg = {};
  cfg.gridDim = dim3(128); cfg.blockDim = dim3(384); cfg.dynamicSmemBytes = K2_SMEM; cfg.stream = cudaStreamPerThread;
  cudaLaunchAttribute at[1];
  at[0].id = cudaLaunchAttributeProgrammaticStreamSerialization;
  at[0].val.programmaticStreamSerializationAllowed = 1;
  cfg.attrs = at; cfg.numAttrs = 1;
  cudaLaunchKernelEx(&cfg, k2_kernel, maps.cr, maps.ci, maps.h, maps.ab, maps.wd, (const __nv_bfloat16*)d_in[0], (__nv_bfloat16*)d_out);
}
```

```cpp
#include <cuda_runtime.h>
#include <cuda_bf16.h>
#include <cuda.h>
#include <stdint.h>

namespace {

__device__ __align__(1024) __nv_bfloat16 g_ab[4096 * 448];
__device__ __align__(1024) __nv_bfloat16 g_h[2048 * 1792];
__device__ uint4 g_part[32 * 3 * 14 * 256];
__device__ __align__(1024) __nv_bfloat16 g_s[2048 * 448];
__device__ unsigned int g_flags[64];

#define DBG(k, i) do {} while (0)
#define DBGC(k, i) do {} while (0)

#define TIMEOUT(code) __trap()
#define SPIN_LIMIT (1 << 22)
__device__ __forceinline__ uint32_t s2u(const void* p) { return (uint32_t)__cvta_generic_to_shared(p); }
__device__ __forceinline__ void mbar_init(uint32_t b, int c) { asm volatile("mbarrier.init.shared::cta.b64 [%0], %1;" ::"r"(b), "r"(c)); }
__device__ __forceinline__ void mbar_expect(uint32_t b, uint32_t bytes) {
  asm volatile("mbarrier.arrive.expect_tx.shared::cta.b64 _, [%0], %1;" ::"r"(b), "r"(bytes) : "memory");
}
__device__ __forceinline__ void mbar_wait(uint32_t b, uint32_t ph, int code = 1) {
  uint32_t done = 0;
  int it = 0;
  while (true) {
    asm volatile("{.reg .pred p; mbarrier.try_wait.parity.shared::cta.b64 p, [%1], %2; selp.u32 %0,1,0,p;}" : "=r"(done) : "r"(b), "r"(ph) : "memory");
    if (done) break;
    if (++it > SPIN_LIMIT) { TIMEOUT(code); break; }
  }
}
__device__ __forceinline__ void mbar_arrive_cluster(uint32_t b, uint32_t cta) {
  uint32_t r;
  asm volatile("mapa.shared::cluster.u32 %0, %1, %2;" : "=r"(r) : "r"(b), "r"(cta));
  asm volatile("mbarrier.arrive.shared::cluster.b64 _, [%0];" ::"r"(r) : "memory");
}
__device__ __forceinline__ void tma2d(uint32_t dst, const CUtensorMap* m, int c0, int c1, uint32_t bar) {
  asm volatile("cp.async.bulk.tensor.2d.shared::cluster.global.mbarrier::complete_tx::bytes [%0], [%1, {%3,%4}], [%2];" ::"r"(dst), "l"(m), "r"(bar), "r"(c0), "r"(c1) : "memory");
}
__device__ __forceinline__ void tma2d_mc(uint32_t dst, const CUtensorMap* m, int c0, int c1, uint32_t bar, uint16_t mask) {
  asm volatile("cp.async.bulk.tensor.2d.shared::cluster.global.mbarrier::complete_tx::bytes.multicast::cluster [%0], [%1, {%3,%4}], [%2], %5;" ::"r"(dst), "l"(m), "r"(bar), "r"(c0), "r"(c1), "h"(mask) : "memory");
}
__device__ __forceinline__ void tma3d_mc(uint32_t dst, const CUtensorMap* m, int c0, int c1, int c2, uint32_t bar, uint16_t mask) {
  asm volatile("cp.async.bulk.tensor.3d.shared::cluster.global.mbarrier::complete_tx::bytes.multicast::cluster [%0], [%1, {%3,%4,%5}], [%2], %6;" ::"r"(dst), "l"(m), "r"(bar), "r"(c0), "r"(c1), "r"(c2), "h"(mask) : "memory");
}
__device__ __forceinline__ void tma2d_store(const CUtensorMap* m, uint32_t src, int c0, int c1) {
  asm volatile("cp.async.bulk.tensor.2d.global.shared::cta.bulk_group [%0, {%2,%3}], [%1];" ::"l"(m), "r"(src), "r"(c0), "r"(c1) : "memory");
}
__device__ __forceinline__ void bulk_load(uint32_t dst, const void* src, uint32_t bytes, uint32_t bar) {
  asm volatile("cp.async.bulk.shared::cluster.global.mbarrier::complete_tx::bytes [%0], [%1], %2, [%3];" ::"r"(dst), "l"(src), "r"(bytes), "r"(bar) : "memory");
}
__device__ __forceinline__ void bulk_commit() { asm volatile("cp.async.bulk.commit_group;" ::: "memory"); }
__device__ __forceinline__ void bulk_wait_read0() { asm volatile("cp.async.bulk.wait_group.read 0;" ::: "memory"); }
__device__ __forceinline__ void bulk_wait0() { asm volatile("cp.async.bulk.wait_group 0;" ::: "memory"); }
__device__ __forceinline__ void fence_async_smem() { asm volatile("fence.proxy.async.shared::cta;" ::: "memory"); }
__device__ __forceinline__ void prefetch_tmap(const CUtensorMap* m) { asm volatile("prefetch.tensormap [%0];" ::"l"(m) : "memory"); }
__device__ __forceinline__ void l2_prefetch(const void* p, uint32_t bytes) {
  asm volatile("cp.async.bulk.prefetch.L2.global [%0], %1;" ::"l"(p), "r"(bytes) : "memory");
}
__device__ __forceinline__ void cluster_arrive_relaxed() { asm volatile("barrier.cluster.arrive.relaxed.aligned;" ::: "memory"); }
__device__ __forceinline__ void cluster_wait() { asm volatile("barrier.cluster.wait.aligned;" ::: "memory"); }
__device__ __forceinline__ void wg_fence() { __syncwarp(); asm volatile("wgmma.fence.sync.aligned;" ::: "memory"); }
__device__ __forceinline__ void wg_commit() { asm volatile("wgmma.commit_group.sync.aligned;" ::: "memory"); }
template <int N> __device__ __forceinline__ void wg_wait() { __syncwarp(); asm volatile("wgmma.wait_group.sync.aligned %0;" ::"n"(N) : "memory"); }
__device__ __forceinline__ void named_bar(int id, int n) { asm volatile("bar.sync %0, %1;" ::"r"(id), "r"(n) : "memory"); }
__device__ __forceinline__ void named_arrive(int id, int n) { asm volatile("bar.arrive %0, %1;" ::"r"(id), "r"(n) : "memory"); }
template <int N> __device__ __forceinline__ void reg_inc() { asm volatile("setmaxnreg.inc.sync.aligned.u32 %0;" ::"n"(N)); }
template <int N> __device__ __forceinline__ void reg_dec() { asm volatile("setmaxnreg.dec.sync.aligned.u32 %0;" ::"n"(N)); }
__device__ __forceinline__ void pdl_wait() { asm volatile("griddepcontrol.wait;" ::: "memory"); }
__device__ __forceinline__ void pdl_launch() { asm volatile("griddepcontrol.launch_dependents;" ::: "memory"); }

__device__ __forceinline__ uint32_t make_desc(uint32_t addr, uint32_t lbo, uint32_t  ) {
  return ((addr & 0x3FFFF) >> 4) | ((lbo >> 4) << 16);
}
__device__ __forceinline__ void stmatrix_x4(uint32_t addr, uint32_t r0, uint32_t r1, uint32_t r2, uint32_t r3) {
  asm volatile("stmatrix.sync.aligned.m8n8.x4.shared.b16 [%0], {%1,%2,%3,%4};" ::"r"(addr), "r"(r0), "r"(r1), "r"(r2), "r"(r3) : "memory");
}
__device__ __forceinline__ uint4 lds128(uint32_t a) {
  uint4 v;
  asm volatile("ld.shared.v4.u32 {%0,%1,%2,%3}, [%4];" : "=r"(v.x), "=r"(v.y), "=r"(v.z), "=r"(v.w) : "r"(a) : "memory");
  return v;
}
__device__ __forceinline__ void sts128(uint32_t a, uint4 v) {
  asm volatile("st.shared.v4.u32 [%0], {%1,%2,%3,%4};" ::"r"(a), "r"(v.x), "r"(v.y), "r"(v.z), "r"(v.w) : "memory");
}
__device__ __forceinline__ void stg128(void* p, uint4 v) {
  asm volatile("st.global.v4.u32 [%0], {%1,%2,%3,%4};" ::"l"(p), "r"(v.x), "r"(v.y), "r"(v.z), "r"(v.w) : "memory");
}
__device__ __forceinline__ void cp_async16(uint32_t dst, const void* src) {
  asm volatile("cp.async.cg.shared.global [%0], [%1], 16;" ::"r"(dst), "l"(src) : "memory");
}
__device__ __forceinline__ void cp_async8(uint32_t dst, const void* src) {
  asm volatile("cp.async.ca.shared.global [%0], [%1], 8;" ::"r"(dst), "l"(src) : "memory");
}
__device__ __forceinline__ uint2 lds64(uint32_t a) {
  uint2 v;
  asm volatile("ld.shared.v2.u32 {%0,%1}, [%2];" : "=r"(v.x), "=r"(v.y) : "r"(a) : "memory");
  return v;
}
__device__ __forceinline__ void cp_async_wait_all() { asm volatile("cp.async.wait_all;" ::: "memory"); }
__device__ __forceinline__ uint32_t pack_bf16(float lo, float hi) {
  uint32_t r;
  asm("cvt.rn.bf16x2.f32 %0, %1, %2;" : "=r"(r) : "f"(hi), "f"(lo));
  return r;
}
__device__ __forceinline__ uint32_t hmul2_bf16(uint32_t a, uint32_t b) {
  uint32_t r;
  asm("mul.rn.bf16x2 %0, %1, %2;" : "=r"(r) : "r"(a), "r"(b));
  return r;
}
__device__ __forceinline__ uint32_t hsub2_bf16(uint32_t a, uint32_t b) {
  uint32_t r;
  asm("sub.rn.bf16x2 %0, %1, %2;" : "=r"(r) : "r"(a), "r"(b));
  return r;
}
__device__ __forceinline__ uint32_t hadd2_bf16(uint32_t a, uint32_t b) {
  uint32_t r;
  asm("add.rn.bf16x2 %0, %1, %2;" : "=r"(r) : "r"(a), "r"(b));
  return r;
}
__device__ __forceinline__ uint32_t hfma2_bf16(uint32_t a, uint32_t b, uint32_t c) {
  uint32_t r;
  asm("fma.rn.bf16x2 %0, %1, %2, %3;" : "=r"(r) : "r"(a), "r"(b), "r"(c));
  return r;
}
__device__ __forceinline__ bool mbar_test(uint32_t b, uint32_t ph) {
  uint32_t done;
  asm volatile("{.reg .pred p; mbarrier.test_wait.parity.shared::cta.b64 p, [%1], %2; selp.u32 %0,1,0,p;}" : "=r"(done) : "r"(b), "r"(ph) : "memory");
  return __all_sync(0xffffffffu, done != 0);
}
__device__ __forceinline__ uint4 ldg128_cg(const void* p) {
  uint4 v;
  asm volatile("ld.global.cg.v4.u32 {%0,%1,%2,%3}, [%4];" : "=r"(v.x), "=r"(v.y), "=r"(v.z), "=r"(v.w) : "l"(p) : "memory");
  return v;
}
__device__ __forceinline__ float bf_lo(uint32_t w) { return __uint_as_float(w << 16); }
__device__ __forceinline__ float bf_hi(uint32_t w) { return __uint_as_float(w & 0xffff0000u); }
__device__ __forceinline__ float rbf(float x) { return __bfloat162float(__float2bfloat16_rn(x)); }
__device__ __forceinline__ float ex2f(float x) { float r; asm("ex2.approx.ftz.f32 %0, %1;" : "=f"(r) : "f"(x)); return r; }
__device__ __forceinline__ float rcpf(float x) { float r; asm("rcp.approx.ftz.f32 %0, %1;" : "=f"(r) : "f"(x)); return r; }
__device__ __forceinline__ float tanhf_hw(float x) { float r; asm("tanh.approx.f32 %0, %1;" : "=f"(r) : "f"(x)); return r; }
__device__ __forceinline__ float gelu_tanh(float x) {
  const float c1 = 0.7978845608028654f;
  const float c2 = c1 * 0.044715f;
  const float t = tanhf_hw(x * fmaf(c2, x * x, c1));
  const float hx = 0.5f * x;
  return fmaf(hx, t, hx);
}
__device__ __forceinline__ float silu_f(float x) {
  const float hx = 0.5f * x;
  return fmaf(hx, tanhf_hw(hx), hx);
}

__device__ __forceinline__ void wgmma_n128_tb(float (&d)[64], uint32_t da, uint32_t db, int scale_d) {
  asm volatile(
    "{\n.reg .pred p;\n.reg .b64 da, db;\nsetp.ne.b32 p, %66, 0;\n"
    "mov.b64 da, {%64, 0x40000040};\nmov.b64 db, {%65, 0x40000040};\n"
    "wgmma.mma_async.sync.aligned.m64n128k16.f32.bf16.bf16 {%0, %1, %2, %3, %4, %5, %6, %7, %8, %9, %10, %11, %12, %13, %14, %15, %16, %17, %18, %19, %20, %21, %22, %23, %24, %25, %26, %27, %28, %29, %30, %31, %32, %33, %34, %35, %36, %37, %38, %39, %40, %41, %42, %43, %44, %45, %46, %47, %48, %49, %50, %51, %52, %53, %54, %55, %56, %57, %58, %59, %60, %61, %62, %63}, da, db, p, 1, 1, 0, 1;\n}\n"
    : "+f"(d[0]), "+f"(d[1]), "+f"(d[2]), "+f"(d[3]), "+f"(d[4]), "+f"(d[5]), "+f"(d[6]), "+f"(d[7]), "+f"(d[8]), "+f"(d[9]), "+f"(d[10]), "+f"(d[11]), "+f"(d[12]), "+f"(d[13]), "+f"(d[14]), "+f"(d[15]), "+f"(d[16]), "+f"(d[17]), "+f"(d[18]), "+f"(d[19]), "+f"(d[20]), "+f"(d[21]), "+f"(d[22]), "+f"(d[23]), "+f"(d[24]), "+f"(d[25]), "+f"(d[26]), "+f"(d[27]), "+f"(d[28]), "+f"(d[29]), "+f"(d[30]), "+f"(d[31]), "+f"(d[32]), "+f"(d[33]), "+f"(d[34]), "+f"(d[35]), "+f"(d[36]), "+f"(d[37]), "+f"(d[38]), "+f"(d[39]), "+f"(d[40]), "+f"(d[41]), "+f"(d[42]), "+f"(d[43]), "+f"(d[44]), "+f"(d[45]), "+f"(d[46]), "+f"(d[47]), "+f"(d[48]), "+f"(d[49]), "+f"(d[50]), "+f"(d[51]), "+f"(d[52]), "+f"(d[53]), "+f"(d[54]), "+f"(d[55]), "+f"(d[56]), "+f"(d[57]), "+f"(d[58]), "+f"(d[59]), "+f"(d[60]), "+f"(d[61]), "+f"(d[62]), "+f"(d[63])
    : "r"(da), "r"(db), "r"(scale_d));
}
__device__ __forceinline__ void wgmma_n128_tb_p(float (&d)[64], uint32_t da, uint32_t db, int scale_d, int enable) {
  asm volatile(
    "{\n.reg .pred p;\n.reg .b64 da, db;\nsetp.ne.b32 p, %66, 0;\n.reg .pred q;\nsetp.ne.b32 q, %67, 0;\n"
    "mov.b64 da, {%64, 0x40000040};\nmov.b64 db, {%65, 0x40000040};\n"
    "@q wgmma.mma_async.sync.aligned.m64n128k16.f32.bf16.bf16 {%0, %1, %2, %3, %4, %5, %6, %7, %8, %9, %10, %11, %12, %13, %14, %15, %16, %17, %18, %19, %20, %21, %22, %23, %24, %25, %26, %27, %28, %29, %30, %31, %32, %33, %34, %35, %36, %37, %38, %39, %40, %41, %42, %43, %44, %45, %46, %47, %48, %49, %50, %51, %52, %53, %54, %55, %56, %57, %58, %59, %60, %61, %62, %63}, da, db, p, 1, 1, 0, 1;\n}\n"
    : "+f"(d[0]), "+f"(d[1]), "+f"(d[2]), "+f"(d[3]), "+f"(d[4]), "+f"(d[5]), "+f"(d[6]), "+f"(d[7]), "+f"(d[8]), "+f"(d[9]), "+f"(d[10]), "+f"(d[11]), "+f"(d[12]), "+f"(d[13]), "+f"(d[14]), "+f"(d[15]), "+f"(d[16]), "+f"(d[17]), "+f"(d[18]), "+f"(d[19]), "+f"(d[20]), "+f"(d[21]), "+f"(d[22]), "+f"(d[23]), "+f"(d[24]), "+f"(d[25]), "+f"(d[26]), "+f"(d[27]), "+f"(d[28]), "+f"(d[29]), "+f"(d[30]), "+f"(d[31]), "+f"(d[32]), "+f"(d[33]), "+f"(d[34]), "+f"(d[35]), "+f"(d[36]), "+f"(d[37]), "+f"(d[38]), "+f"(d[39]), "+f"(d[40]), "+f"(d[41]), "+f"(d[42]), "+f"(d[43]), "+f"(d[44]), "+f"(d[45]), "+f"(d[46]), "+f"(d[47]), "+f"(d[48]), "+f"(d[49]), "+f"(d[50]), "+f"(d[51]), "+f"(d[52]), "+f"(d[53]), "+f"(d[54]), "+f"(d[55]), "+f"(d[56]), "+f"(d[57]), "+f"(d[58]), "+f"(d[59]), "+f"(d[60]), "+f"(d[61]), "+f"(d[62]), "+f"(d[63])
    : "r"(da), "r"(db), "r"(scale_d), "r"(enable));
}
__device__ __forceinline__ void wgmma_n112(float (&d)[56], uint32_t da, uint32_t db, int scale_d) {
  asm volatile(
    "{\n.reg .pred p;\n.reg .b64 da, db;\nsetp.ne.b32 p, %58, 0;\n"
    "mov.b64 da, {%56, 0x40000040};\nmov.b64 db, {%57, 0x40000040};\n"
    "wgmma.mma_async.sync.aligned.m64n112k16.f32.bf16.bf16 {%0, %1, %2, %3, %4, %5, %6, %7, %8, %9, %10, %11, %12, %13, %14, %15, %16, %17, %18, %19, %20, %21, %22, %23, %24, %25, %26, %27, %28, %29, %30, %31, %32, %33, %34, %35, %36, %37, %38, %39, %40, %41, %42, %43, %44, %45, %46, %47, %48, %49, %50, %51, %52, %53, %54, %55}, da, db, p, 1, 1, 0, 0;\n}\n"
    : "+f"(d[0]), "+f"(d[1]), "+f"(d[2]), "+f"(d[3]), "+f"(d[4]), "+f"(d[5]), "+f"(d[6]), "+f"(d[7]), "+f"(d[8]), "+f"(d[9]), "+f"(d[10]), "+f"(d[11]), "+f"(d[12]), "+f"(d[13]), "+f"(d[14]), "+f"(d[15]), "+f"(d[16]), "+f"(d[17]), "+f"(d[18]), "+f"(d[19]), "+f"(d[20]), "+f"(d[21]), "+f"(d[22]), "+f"(d[23]), "+f"(d[24]), "+f"(d[25]), "+f"(d[26]), "+f"(d[27]), "+f"(d[28]), "+f"(d[29]), "+f"(d[30]), "+f"(d[31]), "+f"(d[32]), "+f"(d[33]), "+f"(d[34]), "+f"(d[35]), "+f"(d[36]), "+f"(d[37]), "+f"(d[38]), "+f"(d[39]), "+f"(d[40]), "+f"(d[41]), "+f"(d[42]), "+f"(d[43]), "+f"(d[44]), "+f"(d[45]), "+f"(d[46]), "+f"(d[47]), "+f"(d[48]), "+f"(d[49]), "+f"(d[50]), "+f"(d[51]), "+f"(d[52]), "+f"(d[53]), "+f"(d[54]), "+f"(d[55])
    : "r"(da), "r"(db), "r"(scale_d));
}
__device__ __forceinline__ void wgmma_n224_tb(float (&d)[112], uint32_t da, uint32_t db, int scale_d) {
  asm volatile(
    "{\n.reg .pred p;\n.reg .b64 da, db;\nsetp.ne.b32 p, %114, 0;\n"
    "mov.b64 da, {%112, 0x40000040};\nmov.b64 db, {%113, 0x40000040};\n"
    "wgmma.mma_async.sync.aligned.m64n224k16.f32.bf16.bf16 {%0, %1, %2, %3, %4, %5, %6, %7, %8, %9, %10, %11, %12, %13, %14, %15, %16, %17, %18, %19, %20, %21, %22, %23, %24, %25, %26, %27, %28, %29, %30, %31, %32, %33, %34, %35, %36, %37, %38, %39, %40, %41, %42, %43, %44, %45, %46, %47, %48, %49, %50, %51, %52, %53, %54, %55, %56, %57, %58, %59, %60, %61, %62, %63, %64, %65, %66, %67, %68, %69, %70, %71, %72, %73, %74, %75, %76, %77, %78, %79, %80, %81, %82, %83, %84, %85, %86, %87, %88, %89, %90, %91, %92, %93, %94, %95, %96, %97, %98, %99, %100, %101, %102, %103, %104, %105, %106, %107, %108, %109, %110, %111}, da, db, p, 1, 1, 0, 1;\n}\n"
    : "+f"(d[0]), "+f"(d[1]), "+f"(d[2]), "+f"(d[3]), "+f"(d[4]), "+f"(d[5]), "+f"(d[6]), "+f"(d[7]), "+f"(d[8]), "+f"(d[9]), "+f"(d[10]), "+f"(d[11]), "+f"(d[12]), "+f"(d[13]), "+f"(d[14]), "+f"(d[15]), "+f"(d[16]), "+f"(d[17]), "+f"(d[18]), "+f"(d[19]), "+f"(d[20]), "+f"(d[21]), "+f"(d[22]), "+f"(d[23]), "+f"(d[24]), "+f"(d[25]), "+f"(d[26]), "+f"(d[27]), "+f"(d[28]), "+f"(d[29]), "+f"(d[30]), "+f"(d[31]), "+f"(d[32]), "+f"(d[33]), "+f"(d[34]), "+f"(d[35]), "+f"(d[36]), "+f"(d[37]), "+f"(d[38]), "+f"(d[39]), "+f"(d[40]), "+f"(d[41]), "+f"(d[42]), "+f"(d[43]), "+f"(d[44]), "+f"(d[45]), "+f"(d[46]), "+f"(d[47]), "+f"(d[48]), "+f"(d[49]), "+f"(d[50]), "+f"(d[51]), "+f"(d[52]), "+f"(d[53]), "+f"(d[54]), "+f"(d[55]), "+f"(d[56]), "+f"(d[57]), "+f"(d[58]), "+f"(d[59]), "+f"(d[60]), "+f"(d[61]), "+f"(d[62]), "+f"(d[63]), "+f"(d[64]), "+f"(d[65]), "+f"(d[66]), "+f"(d[67]), "+f"(d[68]), "+f"(d[69]), "+f"(d[70]), "+f"(d[71]), "+f"(d[72]), "+f"(d[73]), "+f"(d[74]), "+f"(d[75]), "+f"(d[76]), "+f"(d[77]), "+f"(d[78]), "+f"(d[79]), "+f"(d[80]), "+f"(d[81]), "+f"(d[82]), "+f"(d[83]), "+f"(d[84]), "+f"(d[85]), "+f"(d[86]), "+f"(d[87]), "+f"(d[88]), "+f"(d[89]), "+f"(d[90]), "+f"(d[91]), "+f"(d[92]), "+f"(d[93]), "+f"(d[94]), "+f"(d[95]), "+f"(d[96]), "+f"(d[97]), "+f"(d[98]), "+f"(d[99]), "+f"(d[100]), "+f"(d[101]), "+f"(d[102]), "+f"(d[103]), "+f"(d[104]), "+f"(d[105]), "+f"(d[106]), "+f"(d[107]), "+f"(d[108]), "+f"(d[109]), "+f"(d[110]), "+f"(d[111])
    : "r"(da), "r"(db), "r"(scale_d));
}

constexpr int K1_NS = 5;
constexpr int K1_A_BYTES = 7 * 16384;
constexpr int K1_B_OFF = K1_A_BYTES;
constexpr int K1_STG_OFF = K1_B_OFF + K1_NS * 16384;
constexpr int K1_BAR_OFF = K1_STG_OFF + 8 * 4096;
constexpr int K1_SMEM = K1_BAR_OFF + 256 + 1024;

struct K1Ctx {
  uint32_t sb, bar_full, rel0, rel1;
  uint32_t dA, dBk, dBn;
  bool lane0;
  const CUtensorMap* tm_hs;
  const CUtensorMap* tm_abs;
};
__device__ __forceinline__ void k1_release(const K1Ctx& c, int slot) {
  if (c.lane0) {
    asm volatile("mbarrier.arrive.shared::cluster.b64 _, [%0];" ::"r"(c.rel0 + 8 * slot) : "memory");
    asm volatile("mbarrier.arrive.shared::cluster.b64 _, [%0];" ::"r"(c.rel1 + 8 * slot) : "memory");
  }
}

__device__ __forceinline__ void k1_unit_ab(const K1Ctx& c, int warp, int lane, int mt, int j) {
  const uint32_t stg = c.sb + K1_STG_OFF + warp * 4096;
  const int wq = warp & 3;
  const int st_row = (lane & 7) + 8 * ((lane >> 3) & 1);
  const int st_chunk = lane >> 4;
  float acc[2][56];
  int slot = 0; uint32_t ph = 0;
#pragma unroll 1
  for (int kb = 0; kb < 7; kb++) {
    const int pslot = (slot == 0) ? K1_NS - 1 : slot - 1;
    mbar_wait(c.bar_full + 8 * slot, ph, 3);
    if (kb == 6) named_arrive(2, 256);
    if (kb == 0 && (threadIdx.x & 127) == 0) DBG(0, 4);
    if ((threadIdx.x & 127) == 0) DBGC(1, 46 + kb);
    wg_fence();
    const uint32_t da = c.dA + kb * 1024;
    const uint32_t db = c.dBk + slot * 1024;
#pragma unroll
    for (int k = 0; k < 4; k++) {
      wgmma_n112(acc[0], da + k * 2, db + k * 2, (kb | k) != 0);
      wgmma_n112(acc[1], da + 512 + k * 2, db + k * 2, (kb | k) != 0);
    }
    wg_commit();
    if (kb > 0) { wg_wait<1>(); k1_release(c, pslot); }
    if (++slot == K1_NS) { slot = 0; ph ^= 1; }
  }
  wg_wait<0>();
  k1_release(c, 6 % K1_NS);
  if ((threadIdx.x & 127) == 0) DBG(0, 5);
  const uint32_t sgn = (j < 4) ? 0u : 0x80008000u;
  const uint32_t sa = stg + st_row * 224 + st_chunk * 16;
  const int row0 = (j < 4 ? 0 : 2048) + mt * 128 + wq * 16;
#pragma unroll
  for (int h = 0; h < 2; h++) {
    if (h == 1) { if (c.lane0) bulk_wait_read0(); __syncwarp(); }
#pragma unroll
    for (int g = 0; g < 14; g += 2) {
      const float* a = &acc[h][4 * g];
      stmatrix_x4(sa + g * 16, pack_bf16(a[0], a[1]) ^ sgn, pack_bf16(a[2], a[3]) ^ sgn, pack_bf16(a[4], a[5]) ^ sgn, pack_bf16(a[6], a[7]) ^ sgn);
    }
    fence_async_smem();
    __syncwarp();
    if (c.lane0) { tma2d_store(c.tm_abs, stg, (j & 3) * 112, row0 + h * 64); bulk_commit(); }
  }
}

__device__ __forceinline__ void k1_unit_gu(const K1Ctx& c, int warp, int lane, int mt, int unit, int fb, int hsel) {
  const uint32_t stg = c.sb + K1_STG_OFF + warp * 4096;
  const int wq = warp & 3;
  const int full = (unit < 4);
  float acc[2][64];
  const uint32_t dA0 = c.dA + (full ? 0 : hsel * 512);
  int slot = (unit * 7) % K1_NS; uint32_t ph = ((unit * 7) / K1_NS) & 1;
  named_bar(2 + ((unit - 1) & 1), 256);
  if (full) {
#pragma unroll 1
    for (int kb = 0; kb < 7; kb++) {
      const int pslot = (slot == 0) ? K1_NS - 1 : slot - 1;
      mbar_wait(c.bar_full + 8 * slot, ph, 4);
      if (kb == 6) named_arrive(2 + (unit & 1), 256);
      if (kb == 0 && (threadIdx.x & 127) == 0) DBG(0, 4 + 3 * unit);
      wg_fence();
      const uint32_t da = dA0 + kb * 1024;
      const uint32_t db = c.dBn + slot * 1024;
#pragma unroll
      for (int k = 0; k < 4; k++) {
        wgmma_n128_tb(acc[0], da + k * 2, db + k * 128, (kb | k) != 0);
        wgmma_n128_tb(acc[1], da + 512 + k * 2, db + k * 128, (kb | k) != 0);
      }
      wg_commit();
      if (kb > 0) { wg_wait<1>(); k1_release(c, pslot); }
      if (++slot == K1_NS) { slot = 0; ph ^= 1; }
    }
  } else {
#pragma unroll 1
    for (int kb = 0; kb < 7; kb++) {
      const int pslot = (slot == 0) ? K1_NS - 1 : slot - 1;
      mbar_wait(c.bar_full + 8 * slot, ph, 5);
      if (kb == 0 && (threadIdx.x & 127) == 0) DBG(0, 4 + 3 * unit);
      wg_fence();
      const uint32_t da = dA0 + kb * 1024;
      const uint32_t db = c.dBn + slot * 1024;
#pragma unroll
      for (int k = 0; k < 4; k++) wgmma_n128_tb(acc[0], da + k * 2, db + k * 128, (kb | k) != 0);
      wg_commit();
      if (kb > 0) { wg_wait<1>(); k1_release(c, pslot); }
      if (++slot == K1_NS) { slot = 0; ph ^= 1; }
    }
  }
  wg_wait<0>();
  k1_release(c, (slot == 0) ? K1_NS - 1 : slot - 1);
  if ((threadIdx.x & 127) == 0) DBG(0, 5 + 3 * unit);
  const int st_row = (lane & 7) + 8 * ((lane >> 3) & 1);
  const int st_chunk = lane >> 4;
  const uint32_t sa = stg + st_row * 128;
  const int row0 = mt * 128 + (full ? 0 : hsel * 64) + wq * 16;
  if (c.lane0) bulk_wait_read0();
  __syncwarp();
#pragma unroll
  for (int h = 0; h < 2; h++) {
    if (h == 1 && !full) break;
#pragma unroll
    for (int g = 0; g < 8; g += 2) {
      uint32_t pk[4];
#pragma unroll
      for (int e = 0; e < 4; e++) {
        const int i = 4 * g + 2 * e;
        const uint32_t g2 = pack_bf16(acc[h][i], acc[h][i + 1]);
        const uint32_t u2 = pack_bf16(acc[h][32 + i], acc[h][32 + i + 1]);
        pk[e] = hmul2_bf16(pack_bf16(gelu_tanh(bf_lo(g2)), gelu_tanh(bf_hi(g2))), u2);
      }
      stmatrix_x4(sa + h * 2048 + (((g + st_chunk) ^ (st_row & 7)) * 16), pk[0], pk[1], pk[2], pk[3]);
    }
    fence_async_smem();
    __syncwarp();
    if (c.lane0) { tma2d_store(c.tm_hs, stg + h * 2048, fb * 64, row0 + h * 64); bulk_commit(); }
  }
}

struct PfPtrs { const uint8_t* wr; const uint8_t* wi; const uint8_t* wg; const uint8_t* wu; const uint8_t* wd; const uint8_t* cr; const uint8_t* ci; };

__global__ void __cluster_dims__(2, 1, 1) __launch_bounds__(384, 1)
k1_kernel(const __grid_constant__ CUtensorMap tm_wr, const __grid_constant__ CUtensorMap tm_wi,
          const __grid_constant__ CUtensorMap tm_wg, const __grid_constant__ CUtensorMap tm_wu,
          const __grid_constant__ CUtensorMap tm_hs, const __grid_constant__ CUtensorMap tm_abs,
          const __nv_bfloat16* __restrict__ x, const PfPtrs pf) {
  extern __shared__ uint8_t smem_raw[];
  const uint32_t sb = (s2u(smem_raw) + 1023) & ~1023u;
  const int tid = threadIdx.x, warp = tid >> 5, lane = tid & 31;
  uint32_t rank;
  asm volatile("mov.u32 %0, %%cluster_ctarank;" : "=r"(rank));
  const int cid = blockIdx.x >> 1;
  const int p = cid >> 3, j = cid & 7;
  const int mt = 2 * p + (int)rank;
  const uint32_t bar_full = sb + K1_BAR_OFF;
  const uint32_t bar_empty = bar_full + 8 * K1_NS;
  const int fb_base = 7 * (j >> 1);
  const int fb0 = fb_base + ((j & 1) ? 4 : 0);
  const int fbh = fb_base + 3;
  const CUtensorMap* tw = (j < 4) ? &tm_wr : &tm_wi;
  const CUtensorMap* tgu = rank ? &tm_wu : &tm_wg;

  if (tid == 0) DBG(0, 0);
  if (tid == 256) {
    for (int i = 0; i < K1_NS; i++) { mbar_init(bar_full + 8 * i, 1); mbar_init(bar_empty + 8 * i, 8); }
    asm volatile("fence.mbarrier_init.release.cluster;" ::: "memory");
    prefetch_tmap(tw);
    prefetch_tmap(tgu);
    prefetch_tmap(&tm_abs);
    prefetch_tmap(&tm_hs);
    if (blockIdx.x < 64) g_flags[blockIdx.x] = 0;
  }
  __syncwarp();
  cluster_arrive_relaxed();
  pdl_launch();

  if (warp >= 8) {
    reg_dec<40>();
    cluster_wait();
    if (tid == 256) {
      int slot = 0; uint32_t ph = 0;
      int kb = 0, unit = 0;
#pragma unroll 1
      for (int s = 0; s < 35; s++) {
        if (s >= K1_NS) mbar_wait(bar_empty + 8 * slot, ph ^ 1, 2);
        DBG(0, 20 + s);
        const uint32_t dst = sb + K1_B_OFF + slot * 16384;
        if (unit == 0) {
          mbar_expect(bar_full + 8 * slot, 14336);
          tma2d_mc(dst + rank * 7168, tw, kb * 64, (j & 3) * 112 + rank * 56, bar_full + 8 * slot, 3);
        } else {
          const int fb = (unit == 4) ? fbh : (fb0 + unit - 1);
          mbar_expect(bar_full + 8 * slot, 16384);
          tma2d_mc(dst + rank * 8192, tgu, fb * 64, kb * 64, bar_full + 8 * slot, 3);
        }
        if (++kb == 7) { kb = 0; unit++; }
        if (++slot == K1_NS) { slot = 0; ph ^= 1; }
      }
    } else if (tid == 288) {
      const int b = blockIdx.x;
      l2_prefetch(pf.wg + b * 12544, 12544);
      l2_prefetch(pf.wu + b * 12544, 12544);
    }
  } else {
    reg_inc<232>();
    const int wg = warp >> 2;
    {
      const int c = lane & 7;
      const int r0 = warp * 16 + (lane >> 3);
      const uint4* src = reinterpret_cast<const uint4*>(x + (size_t)(mt * 128 + r0) * 448) + c;
      uint4 nx[7];
#pragma unroll
      for (int b = 0; b < 7; b++)
        asm volatile("ld.global.nc.v4.u32 {%0,%1,%2,%3}, [%4];" : "=r"(nx[b].x), "=r"(nx[b].y), "=r"(nx[b].z), "=r"(nx[b].w) : "l"(src + b * 8) : "memory");
#pragma unroll
      for (int pass = 1; pass < 4; pass++) asm volatile("prefetch.global.L2 [%0];" ::"l"(src + pass * 4 * 56 + c * 7 - c) : "memory");
#pragma unroll 1
      for (int pass = 0; pass < 4; pass++) {
        uint4 v[7];
#pragma unroll
        for (int b = 0; b < 7; b++) v[b] = nx[b];
        if (pass < 3) {
          const uint4* s2 = src + (pass + 1) * 4 * 56;
#pragma unroll
          for (int b = 0; b < 7; b++)
            asm volatile("ld.global.nc.v4.u32 {%0,%1,%2,%3}, [%4];" : "=r"(nx[b].x), "=r"(nx[b].y), "=r"(nx[b].z), "=r"(nx[b].w) : "l"(s2 + b * 8) : "memory");
        }
        float s0 = 0.f, s1 = 0.f, s2v = 0.f, s3 = 0.f;
#pragma unroll
        for (int b = 0; b < 7; b++) {
          s0 += bf_lo(v[b].x) + bf_hi(v[b].x); s1 += bf_lo(v[b].y) + bf_hi(v[b].y);
          s2v += bf_lo(v[b].z) + bf_hi(v[b].z); s3 += bf_lo(v[b].w) + bf_hi(v[b].w);
        }
        float m = (s0 + s1) + (s2v + s3);
        m += __shfl_xor_sync(0xffffffffu, m, 1);
        m += __shfl_xor_sync(0xffffffffu, m, 2);
        m += __shfl_xor_sync(0xffffffffu, m, 4);
        m *= (1.0f / 448.0f);
        float q0 = 0.f, q1 = 0.f, q2 = 0.f, q3 = 0.f;
#pragma unroll
        for (int b = 0; b < 7; b++) {
          float d;
          d = bf_lo(v[b].x) - m; q0 = fmaf(d, d, q0); d = bf_hi(v[b].x) - m; q1 = fmaf(d, d, q1);
          d = bf_lo(v[b].y) - m; q2 = fmaf(d, d, q2); d = bf_hi(v[b].y) - m; q3 = fmaf(d, d, q3);
          d = bf_lo(v[b].z) - m; q0 = fmaf(d, d, q0); d = bf_hi(v[b].z) - m; q1 = fmaf(d, d, q1);
          d = bf_lo(v[b].w) - m; q2 = fmaf(d, d, q2); d = bf_hi(v[b].w) - m; q3 = fmaf(d, d, q3);
        }
        float q = (q0 + q1) + (q2 + q3);
        q += __shfl_xor_sync(0xffffffffu, q, 1);
        q += __shfl_xor_sync(0xffffffffu, q, 2);
        q += __shfl_xor_sync(0xffffffffu, q, 4);
        const float var_b = rbf(q * (1.0f / 448.0f));
        const float den = rbf(sqrtf(rbf(var_b + 1e-5f)));
        const float ri = 1.0f / den;
        const float rih = rbf(ri);
        const uint32_t rhi2 = pack_bf16(rih, rih), rlo2 = pack_bf16(ri - rih, ri - rih);
        const uint32_t m2 = pack_bf16(m, m);
        const int r = r0 + pass * 4;
        const uint32_t a0 = sb + r * 128 + ((c ^ (r & 7)) * 16);
#pragma unroll
        for (int b = 0; b < 7; b++) {
          uint32_t w4[4] = {v[b].x, v[b].y, v[b].z, v[b].w};
#pragma unroll
          for (int qq = 0; qq < 4; qq++) {
            const uint32_t dw = hsub2_bf16(w4[qq], m2);
            w4[qq] = hfma2_bf16(dw, rhi2, hmul2_bf16(dw, rlo2));
          }
          sts128(a0 + b * 16384, make_uint4(w4[0], w4[1], w4[2], w4[3]));
        }
      }
    }
    if (lane == 0) DBG(0, 59 + (warp & 3));
    asm volatile("fence.proxy.async.shared::cta;" ::: "memory");
    named_bar(1, 256);
    cluster_wait();
    if (tid == 0) DBG(0, 3);

    K1Ctx c;
    c.sb = sb; c.bar_full = bar_full; c.lane0 = (lane == 0);
    asm volatile("mapa.shared::cluster.u32 %0, %1, %2;" : "=r"(c.rel0) : "r"(bar_empty), "r"(0));
    asm volatile("mapa.shared::cluster.u32 %0, %1, %2;" : "=r"(c.rel1) : "r"(bar_empty), "r"(1));
    c.tm_hs = &tm_hs; c.tm_abs = &tm_abs;
    c.dA = make_desc(sb, 16, 1024);
    c.dBk = make_desc(sb + K1_B_OFF, 16, 1024);
    c.dBn = make_desc(sb + K1_B_OFF, 8192, 1024);
    if (wg == 0) {
      k1_unit_ab(c, warp, lane, mt, j);
      if (tid == 0) DBG(0, 6);
    }
#pragma unroll 1
    for (int unit = 2 - wg; unit < 5; unit += 2) {
      k1_unit_gu(c, warp, lane, mt, unit, (unit == 4) ? fbh : fb0 + unit - 1, j & 1);
      if ((tid & 127) == 0) DBG(0, 6 + 3 * unit);
    }
    if (lane == 0) bulk_wait0();
  }
  __syncwarp();
  cluster_arrive_relaxed();
  cluster_wait();
}

constexpr int K2_NS = 4;
constexpr int K2_STAGE = 16384 + 32768;
constexpr int K2_BAR_OFF = K2_NS * K2_STAGE;
constexpr int K2_SMEM = K2_BAR_OFF + 256 + 1024;
constexpr int K2_PITCH = 464;

__device__ __forceinline__ void spin_flag(const unsigned int* flag, unsigned int target) {
  int it = 0;
  while (true) {
    unsigned int v;
    asm volatile("ld.acquire.gpu.global.u32 %0, [%1];" : "=r"(v) : "l"(flag) : "memory");
    if (v >= target) break;
    if (++it > SPIN_LIMIT) { TIMEOUT(20); break; }
  }
}

__global__ void __cluster_dims__(2, 1, 1) __launch_bounds__(384, 1)
k2_kernel(const __grid_constant__ CUtensorMap tm_cr, const __grid_constant__ CUtensorMap tm_ci, const __grid_constant__ CUtensorMap tm_h,
          const __grid_constant__ CUtensorMap tm_ab, const __grid_constant__ CUtensorMap tm_wd,
          const __nv_bfloat16* __restrict__ x, __nv_bfloat16* __restrict__ out) {
  extern __shared__ uint8_t smem_raw[];
  const uint32_t sb = (s2u(smem_raw) + 1023) & ~1023u;
  const int tid = threadIdx.x, warp = tid >> 5, lane = tid & 31;
  uint32_t rank;
  asm volatile("mov.u32 %0, %%cluster_ctarank;" : "=r"(rank));
  const int cid = blockIdx.x >> 1;
  const int q = cid & 3, n = (cid >> 2) & 1, p = cid >> 3;
  const int mt = 2 * p + (int)rank;
  const int tile = mt * 2 + n;
  const uint32_t bar_full = sb + K2_BAR_OFF;
  const uint32_t bar_empty = bar_full + 8 * K2_NS;
  const int g0 = (q == 0) ? 0 : (q == 1 ? 22 : (q == 2 ? 43 : 64));
  const int nkb = (q == 0) ? 22 : (q == 3 ? 28 : 21);

  if (tid == 0) DBG(1, 0);
  if (tid == 256) {
    for (int i = 0; i < K2_NS; i++) { mbar_init(bar_full + 8 * i, 1); mbar_init(bar_empty + 8 * i, 16); }
    mbar_init(bar_empty + 8 * K2_NS, 1);
    asm volatile("fence.mbarrier_init.release.cluster;" ::: "memory");
    if (q == 3) { prefetch_tmap(&tm_h); prefetch_tmap(&tm_wd); }
    else { prefetch_tmap(&tm_cr); prefetch_tmap(&tm_ci); prefetch_tmap(&tm_ab); }
  }
  __syncwarp();
  cluster_arrive_relaxed();
  cluster_wait();

  if (warp >= 8) {
    reg_dec<40>();
    if (tid == 256) {
      const CUtensorMap* tb = (q < 3) ? &tm_ab : &tm_wd;
      const int kb0 = (q < 3) ? g0 : 0;
      int slot = 0; uint32_t ph = 0;
#pragma unroll 1
      for (int it = 0; it < nkb + K2_NS; it++) {
        const int s = (it < K2_NS) ? it : it - K2_NS;
        const bool pre = (it < K2_NS), post = (!pre && s < K2_NS);
        if (it == K2_NS) { pdl_wait(); DBG(1, 31); slot = 0; }
        if (!pre && !post) mbar_wait(bar_empty + 8 * slot, ph, 10);
        const uint32_t dst = sb + slot * K2_STAGE;
        const uint32_t fb = bar_full + 8 * slot;
        if (!post) mbar_expect(fb, K2_STAGE);
        const bool doA = pre ? (q < 3) : (post ? (q == 3) : true);
        const bool doB = pre ? (q == 3) : (post ? (q < 3) : true);
        if (doA) {
          const int g = g0 + s;
          const CUtensorMap* ta = (g < 32) ? &tm_cr : (g < 64 ? &tm_ci : &tm_h);
          tma2d(dst, ta, (g & 31) * 64 + ((g >= 96) ? 2048 : 0), mt * 128, fb);
        }
        if (doB) {
          tma3d_mc(dst + 16384 + (2 * rank) * 8192, tb, (2 * rank) * 64, n, (kb0 + s) * 64, fb, 3);
          tma3d_mc(dst + 16384 + (2 * rank + 1) * 8192, tb, (2 * rank + 1) * 64, n, (kb0 + s) * 64, fb, 3);
        }
        if (++slot == K2_NS) { slot = 0; if (!pre && !post) ph ^= 1; }
      }
    }
  } else {
    reg_inc<232>();
    const int wg = warp >> 2;
    float acc[112];
    uint32_t rel0, rel1;
    asm volatile("mapa.shared::cluster.u32 %0, %1, %2;" : "=r"(rel0) : "r"(bar_empty), "r"(0));
    asm volatile("mapa.shared::cluster.u32 %0, %1, %2;" : "=r"(rel1) : "r"(bar_empty), "r"(1));
    const uint32_t dA0 = make_desc(sb + wg * 8192, 16, 1024);
    const uint32_t dB0 = make_desc(sb + 16384, 8192, 1024);
    int slot = 0; uint32_t ph = 0;
#pragma unroll 1
    for (int s = 0; s < nkb; s++) {
      mbar_wait(bar_full + 8 * slot, ph, 11);
      if (tid == 0) DBG(1, 1 + s);
      if (tid == 0 && (s == 5 || s == 15)) DBGC(1, 53 + (s == 15));
      if (tid == 0 && (s == 23 || s == 27)) DBGC(1, 55 + (s == 27));
      wg_fence();
      const uint32_t da = dA0 + slot * (K2_STAGE / 16);
      const uint32_t db = dB0 + slot * (K2_STAGE / 16);
#pragma unroll
      for (int k = 0; k < 4; k++) wgmma_n224_tb(acc, da + k * 2, db + k * 128, (s | k) != 0);
      wg_commit();
      if (s > 0) {
        wg_wait<1>();
        const int ps = (slot == 0) ? K2_NS - 1 : slot - 1;
        if (lane == 0) {
          asm volatile("mbarrier.arrive.shared::cluster.b64 _, [%0];" ::"r"(rel0 + 8 * ps) : "memory");
          asm volatile("mbarrier.arrive.shared::cluster.b64 _, [%0];" ::"r"(rel1 + 8 * ps) : "memory");
        }
      }
      if (++slot == K2_NS) { slot = 0; ph ^= 1; }
    }
    wg_wait<0>();
    pdl_wait();
    if (tid == 0) DBG(1, 29);
    if (q < 3) {
      uint4* part = g_part + (size_t)(tile * 3 + q) * (14 * 256) + tid;
#pragma unroll
      for (int g = 0; g < 14; g++)
        part[g * 256] = make_uint4(pack_bf16(acc[8 * g], acc[8 * g + 1]), pack_bf16(acc[8 * g + 2], acc[8 * g + 3]),
                                   pack_bf16(acc[8 * g + 4], acc[8 * g + 5]), pack_bf16(acc[8 * g + 6], acc[8 * g + 7]));
      __threadfence();
      asm volatile("fence.proxy.async;" ::: "memory");
      named_bar(1, 256);
      if (tid == 0) atomicAdd(&g_flags[tile], 1u);
    } else {
      named_bar(1, 256);
      const uint32_t bar_p = bar_empty + 8 * K2_NS;
      if (tid == 0) {
        spin_flag(&g_flags[tile], 3u);
        asm volatile("fence.proxy.async;" ::: "memory");
        mbar_expect(bar_p, 3 * 57344);
        const uint4* pp = g_part + (size_t)tile * (3 * 14 * 256);
#pragma unroll 1
        for (int i = 0; i < 6; i++) bulk_load(sb + i * 28672, pp + i * 1792, 28672, bar_p);
        DBG(1, 30);
      }
      const int lc = (lane < 28) ? lane : 27;
      const size_t gbase = (size_t)(mt * 128 + warp * 16) * 448 + n * 224 + lc * 8;
      uint32_t gw[56];
#pragma unroll
      for (int i = 0; i < 56; i++) {
        const uint32_t f2 = pack_bf16(acc[2 * i], acc[2 * i + 1]);
        gw[i] = pack_bf16(silu_f(bf_lo(f2)), silu_f(bf_hi(f2)));
      }
      uint4 xv[16];
#pragma unroll
      for (int t = 0; t < 16; t++) xv[t] = ldg128_cg(x + gbase + t * 448);
      if (tid == 0) DBG(1, 62);
      mbar_wait(bar_p, 0, 12);
      const uint32_t tb = sb + tid * 16;
#pragma unroll
      for (int g = 0; g < 14; g++) {
        const uint4 a = lds128(tb + g * 4096), b = lds128(tb + (14 + g) * 4096), cc = lds128(tb + (28 + g) * 4096);
        gw[4 * g] = hmul2_bf16(pack_bf16(bf_lo(a.x) + bf_lo(b.x) + bf_lo(cc.x), bf_hi(a.x) + bf_hi(b.x) + bf_hi(cc.x)), gw[4 * g]);
        gw[4 * g + 1] = hmul2_bf16(pack_bf16(bf_lo(a.y) + bf_lo(b.y) + bf_lo(cc.y), bf_hi(a.y) + bf_hi(b.y) + bf_hi(cc.y)), gw[4 * g + 1]);
        gw[4 * g + 2] = hmul2_bf16(pack_bf16(bf_lo(a.z) + bf_lo(b.z) + bf_lo(cc.z), bf_hi(a.z) + bf_hi(b.z) + bf_hi(cc.z)), gw[4 * g + 2]);
        gw[4 * g + 3] = hmul2_bf16(pack_bf16(bf_lo(a.w) + bf_lo(b.w) + bf_lo(cc.w), bf_hi(a.w) + bf_hi(b.w) + bf_hi(cc.w)), gw[4 * g + 3]);
      }
      named_bar(1, 256);
      const uint32_t wbase = sb + warp * 16 * K2_PITCH;
      const int st_row = (lane & 7) + 8 * ((lane >> 3) & 1);
      const uint32_t sa = wbase + st_row * K2_PITCH + (lane >> 4) * 16;
#pragma unroll
      for (int g = 0; g < 28; g += 2) stmatrix_x4(sa + g * 16, gw[2 * g], gw[2 * g + 1], gw[2 * g + 2], gw[2 * g + 3]);
      __syncwarp();
      const uint32_t lp = wbase + lc * 16;
#pragma unroll
      for (int t = 0; t < 16; t++) {
        const uint4 tv = lds128(lp + t * K2_PITCH);
        uint4 o;
        o.x = hadd2_bf16(xv[t].x, tv.x); o.y = hadd2_bf16(xv[t].y, tv.y); o.z = hadd2_bf16(xv[t].z, tv.z); o.w = hadd2_bf16(xv[t].w, tv.w);
        if (lane < 28) stg128(out + gbase + t * 448, o);
      }
    }
    if (tid == 0) DBG(1, 63);
  }
  __syncwarp();
  cluster_arrive_relaxed();
  cluster_wait();
}

typedef CUresult (*EncFn)(CUtensorMap*, CUtensorMapDataType, cuuint32_t, void*, const cuuint64_t*, const cuuint64_t*, const cuuint32_t*,
                          const cuuint32_t*, CUtensorMapInterleave, CUtensorMapSwizzle, CUtensorMapL2promotion, CUtensorMapFloatOOBfill);

void make2d(EncFn enc, CUtensorMap* tm, const void* ptr, uint64_t cols, uint64_t rows, uint32_t bc, uint32_t br, bool swz = true) {
  cuuint64_t gd[2] = {cols, rows};
  cuuint64_t gs[1] = {cols * 2};
  cuuint32_t bd[2] = {bc, br};
  cuuint32_t es[2] = {1, 1};
  enc(tm, CU_TENSOR_MAP_DATA_TYPE_BFLOAT16, 2, const_cast<void*>(ptr), gd, gs, bd, es, CU_TENSOR_MAP_INTERLEAVE_NONE,
      swz ? CU_TENSOR_MAP_SWIZZLE_128B : CU_TENSOR_MAP_SWIZZLE_NONE, CU_TENSOR_MAP_L2_PROMOTION_L2_128B, CU_TENSOR_MAP_FLOAT_OOB_FILL_NONE);
}
void make3d_half(EncFn enc, CUtensorMap* tm, const void* ptr, uint64_t rows) {
  cuuint64_t gd[3] = {224, 2, rows};
  cuuint64_t gs[2] = {448, 896};
  cuuint32_t bd[3] = {64, 1, 64};
  cuuint32_t es[3] = {1, 1, 1};
  enc(tm, CU_TENSOR_MAP_DATA_TYPE_BFLOAT16, 3, const_cast<void*>(ptr), gd, gs, bd, es, CU_TENSOR_MAP_INTERLEAVE_NONE,
      CU_TENSOR_MAP_SWIZZLE_128B, CU_TENSOR_MAP_L2_PROMOTION_L2_128B, CU_TENSOR_MAP_FLOAT_OOB_FILL_NONE);
}

struct Maps { CUtensorMap wr, wi, wg, wu, cr, ci, h, ab, wd, hs, abs; };

}

extern "C" void kernel_launch(void* const* d_in, const int* in_sizes, int n_in, void* d_out, int out_size) {
  (void)in_sizes; (void)n_in; (void)out_size;
  static Maps maps;
  static const void* cached[9] = {nullptr};
  static bool attr_done = false;
  bool same = true;
  for (int i = 0; i < 9; i++) same = same && (cached[i] == d_in[i]);
  if (!same) {
    void* fn = nullptr;
    cudaDriverEntryPointQueryResult qr;
    cudaGetDriverEntryPoint("cuTensorMapEncodeTiled", &fn, cudaEnableDefault, &qr);
    EncFn enc = (EncFn)fn;
    void *p_ab = nullptr, *p_h = nullptr;
    cudaGetSymbolAddress(&p_ab, g_ab);
    cudaGetSymbolAddress(&p_h, g_h);
    make2d(enc, &maps.cr, d_in[1], 2048, 2048, 64, 128);
    make2d(enc, &maps.ci, d_in[2], 2048, 2048, 64, 128);
    make2d(enc, &maps.wr, d_in[3], 448, 448, 64, 56);
    make2d(enc, &maps.wi, d_in[4], 448, 448, 64, 56);
    make2d(enc, &maps.wg, d_in[6], 1792, 448, 64, 64);
    make2d(enc, &maps.wu, d_in[7], 1792, 448, 64, 64);
    make3d_half(enc, &maps.wd, d_in[8], 1792);
    make2d(enc, &maps.h, p_h, 1792, 2048, 64, 128);
    make3d_half(enc, &maps.ab, p_ab, 4096);
    make2d(enc, &maps.hs, p_h, 1792, 2048, 64, 16);
    make2d(enc, &maps.abs, p_ab, 448, 4096, 112, 16, false);
    for (int i = 0; i < 9; i++) cached[i] = d_in[i];
  }
  if (!attr_done) {
    cudaFuncSetAttribute(k1_kernel, cudaFuncAttributeMaxDynamicSharedMemorySize, K1_SMEM);
    cudaFuncSetAttribute(k2_kernel, cudaFuncAttributeMaxDynamicSharedMemorySize, K2_SMEM);
    attr_done = true;
  }
  PfPtrs pf;
  pf.wr = (const uint8_t*)d_in[3]; pf.wi = (const uint8_t*)d_in[4]; pf.wg = (const uint8_t*)d_in[6]; pf.wu = (const uint8_t*)d_in[7];
  pf.wd = (const uint8_t*)d_in[8]; pf.cr = (const uint8_t*)d_in[1]; pf.ci = (const uint8_t*)d_in[2];
  k1_kernel<<<128, 384, K1_SMEM>>>(maps.wr, maps.wi, maps.wg, maps.wu, maps.hs, maps.abs, (const __nv_bfloat16*)d_in[0], pf);

  cudaLaunchConfig_t cfg = {};
  cfg.gridDim = dim3(128); cfg.blockDim = dim3(384); cfg.dynamicSmemBytes = K2_SMEM; cfg.stream = cudaStreamPerThread;
  cudaLaunchAttribute at[1];
  at[0].id = cudaLaunchAttributeProgrammaticStreamSerialization;
  at[0].val.programmaticStreamSerializationAllowed = 1;
  cfg.attrs = at; cfg.numAttrs = 1;
  cudaLaunchKernelEx(&cfg, k2_kernel, maps.cr, maps.ci, maps.h, maps.ab, maps.wd, (const __nv_bfloat16*)d_in[0], (__nv_bfloat16*)d_out);
}
```

```cpp
#include <cuda_runtime.h>
#include <cuda_bf16.h>
#include <cuda.h>
#include <stdint.h>

namespace {

__device__ __align__(1024) __nv_bfloat16 g_ab[4096 * 448];
__device__ __align__(1024) __nv_bfloat16 g_h[2048 * 1792];
__device__ uint4 g_part[32 * 3 * 14 * 256];
__device__ __align__(1024) __nv_bfloat16 g_s[2048 * 448];
__device__ unsigned int g_flags[64];

#define DBG(k, i) do {} while (0)
#define DBGC(k, i) do {} while (0)

#define TIMEOUT(code) __trap()
#define SPIN_LIMIT (1 << 22)
__device__ __forceinline__ uint32_t s2u(const void* p) { return (uint32_t)__cvta_generic_to_shared(p); }
__device__ __forceinline__ void mbar_init(uint32_t b, int c) { asm volatile("mbarrier.init.shared::cta.b64 [%0], %1;" ::"r"(b), "r"(c)); }
__device__ __forceinline__ void mbar_expect(uint32_t b, uint32_t bytes) {
  asm volatile("mbarrier.arrive.expect_tx.shared::cta.b64 _, [%0], %1;" ::"r"(b), "r"(bytes) : "memory");
}
__device__ __forceinline__ void mbar_wait(uint32_t b, uint32_t ph, int code = 1) {
  uint32_t done = 0;
  int it = 0;
  while (true) {
    asm volatile("{.reg .pred p; mbarrier.try_wait.parity.shared::cta.b64 p, [%1], %2; selp.u32 %0,1,0,p;}" : "=r"(done) : "r"(b), "r"(ph) : "memory");
    if (done) break;
    if (++it > SPIN_LIMIT) { TIMEOUT(code); break; }
  }
}
__device__ __forceinline__ void mbar_arrive_cluster(uint32_t b, uint32_t cta) {
  uint32_t r;
  asm volatile("mapa.shared::cluster.u32 %0, %1, %2;" : "=r"(r) : "r"(b), "r"(cta));
  asm volatile("mbarrier.arrive.shared::cluster.b64 _, [%0];" ::"r"(r) : "memory");
}
__device__ __forceinline__ void tma2d(uint32_t dst, const CUtensorMap* m, int c0, int c1, uint32_t bar) {
  asm volatile("cp.async.bulk.tensor.2d.shared::cluster.global.mbarrier::complete_tx::bytes [%0], [%1, {%3,%4}], [%2];" ::"r"(dst), "l"(m), "r"(bar), "r"(c0), "r"(c1) : "memory");
}
__device__ __forceinline__ void tma2d_mc(uint32_t dst, const CUtensorMap* m, int c0, int c1, uint32_t bar, uint16_t mask) {
  asm volatile("cp.async.bulk.tensor.2d.shared::cluster.global.mbarrier::complete_tx::bytes.multicast::cluster [%0], [%1, {%3,%4}], [%2], %5;" ::"r"(dst), "l"(m), "r"(bar), "r"(c0), "r"(c1), "h"(mask) : "memory");
}
__device__ __forceinline__ void tma3d_mc(uint32_t dst, const CUtensorMap* m, int c0, int c1, int c2, uint32_t bar, uint16_t mask) {
  asm volatile("cp.async.bulk.tensor.3d.shared::cluster.global.mbarrier::complete_tx::bytes.multicast::cluster [%0], [%1, {%3,%4,%5}], [%2], %6;" ::"r"(dst), "l"(m), "r"(bar), "r"(c0), "r"(c1), "r"(c2), "h"(mask) : "memory");
}
__device__ __forceinline__ void tma2d_store(const CUtensorMap* m, uint32_t src, int c0, int c1) {
  asm volatile("cp.async.bulk.tensor.2d.global.shared::cta.bulk_group [%0, {%2,%3}], [%1];" ::"l"(m), "r"(src), "r"(c0), "r"(c1) : "memory");
}
__device__ __forceinline__ void bulk_load(uint32_t dst, const void* src, uint32_t bytes, uint32_t bar) {
  asm volatile("cp.async.bulk.shared::cluster.global.mbarrier::complete_tx::bytes [%0], [%1], %2, [%3];" ::"r"(dst), "l"(src), "r"(bytes), "r"(bar) : "memory");
}
__device__ __forceinline__ void bulk_commit() { asm volatile("cp.async.bulk.commit_group;" ::: "memory"); }
__device__ __forceinline__ void bulk_wait_read0() { asm volatile("cp.async.bulk.wait_group.read 0;" ::: "memory"); }
__device__ __forceinline__ void bulk_wait0() { asm volatile("cp.async.bulk.wait_group 0;" ::: "memory"); }
__device__ __forceinline__ void fence_async_smem() { asm volatile("fence.proxy.async.shared::cta;" ::: "memory"); }
__device__ __forceinline__ void prefetch_tmap(const CUtensorMap* m) { asm volatile("prefetch.tensormap [%0];" ::"l"(m) : "memory"); }
__device__ __forceinline__ void l2_prefetch(const void* p, uint32_t bytes) {
  asm volatile("cp.async.bulk.prefetch.L2.global [%0], %1;" ::"l"(p), "r"(bytes) : "memory");
}
__device__ __forceinline__ void cluster_arrive_relaxed() { asm volatile("barrier.cluster.arrive.relaxed.aligned;" ::: "memory"); }
__device__ __forceinline__ void cluster_wait() { asm volatile("barrier.cluster.wait.aligned;" ::: "memory"); }
__device__ __forceinline__ void wg_fence() { __syncwarp(); asm volatile("wgmma.fence.sync.aligned;" ::: "memory"); }
__device__ __forceinline__ void wg_commit() { asm volatile("wgmma.commit_group.sync.aligned;" ::: "memory"); }
template <int N> __device__ __forceinline__ void wg_wait() { __syncwarp(); asm volatile("wgmma.wait_group.sync.aligned %0;" ::"n"(N) : "memory"); }
__device__ __forceinline__ void named_bar(int id, int n) { asm volatile("bar.sync %0, %1;" ::"r"(id), "r"(n) : "memory"); }
__device__ __forceinline__ void named_arrive(int id, int n) { asm volatile("bar.arrive %0, %1;" ::"r"(id), "r"(n) : "memory"); }
template <int N> __device__ __forceinline__ void reg_inc() { asm volatile("setmaxnreg.inc.sync.aligned.u32 %0;" ::"n"(N)); }
template <int N> __device__ __forceinline__ void reg_dec() { asm volatile("setmaxnreg.dec.sync.aligned.u32 %0;" ::"n"(N)); }
__device__ __forceinline__ void pdl_wait() { asm volatile("griddepcontrol.wait;" ::: "memory"); }
__device__ __forceinline__ void pdl_launch() { asm volatile("griddepcontrol.launch_dependents;" ::: "memory"); }

__device__ __forceinline__ uint32_t make_desc(uint32_t addr, uint32_t lbo, uint32_t  ) {
  return ((addr & 0x3FFFF) >> 4) | ((lbo >> 4) << 16);
}
__device__ __forceinline__ void stmatrix_x4(uint32_t addr, uint32_t r0, uint32_t r1, uint32_t r2, uint32_t r3) {
  asm volatile("stmatrix.sync.aligned.m8n8.x4.shared.b16 [%0], {%1,%2,%3,%4};" ::"r"(addr), "r"(r0), "r"(r1), "r"(r2), "r"(r3) : "memory");
}
__device__ __forceinline__ uint4 lds128(uint32_t a) {
  uint4 v;
  asm volatile("ld.shared.v4.u32 {%0,%1,%2,%3}, [%4];" : "=r"(v.x), "=r"(v.y), "=r"(v.z), "=r"(v.w) : "r"(a) : "memory");
  return v;
}
__device__ __forceinline__ void sts128(uint32_t a, uint4 v) {
  asm volatile("st.shared.v4.u32 [%0], {%1,%2,%3,%4};" ::"r"(a), "r"(v.x), "r"(v.y), "r"(v.z), "r"(v.w) : "memory");
}
__device__ __forceinline__ void stg128(void* p, uint4 v) {
  asm volatile("st.global.v4.u32 [%0], {%1,%2,%3,%4};" ::"l"(p), "r"(v.x), "r"(v.y), "r"(v.z), "r"(v.w) : "memory");
}
__device__ __forceinline__ void cp_async16(uint32_t dst, const void* src) {
  asm volatile("cp.async.cg.shared.global [%0], [%1], 16;" ::"r"(dst), "l"(src) : "memory");
}
__device__ __forceinline__ void cp_async8(uint32_t dst, const void* src) {
  asm volatile("cp.async.ca.shared.global [%0], [%1], 8;" ::"r"(dst), "l"(src) : "memory");
}
__device__ __forceinline__ uint2 lds64(uint32_t a) {
  uint2 v;
  asm volatile("ld.shared.v2.u32 {%0,%1}, [%2];" : "=r"(v.x), "=r"(v.y) : "r"(a) : "memory");
  return v;
}
__device__ __forceinline__ void cp_async_wait_all() { asm volatile("cp.async.wait_all;" ::: "memory"); }
__device__ __forceinline__ uint32_t pack_bf16(float lo, float hi) {
  uint32_t r;
  asm("cvt.rn.bf16x2.f32 %0, %1, %2;" : "=r"(r) : "f"(hi), "f"(lo));
  return r;
}
__device__ __forceinline__ uint32_t hmul2_bf16(uint32_t a, uint32_t b) {
  uint32_t r;
  asm("mul.rn.bf16x2 %0, %1, %2;" : "=r"(r) : "r"(a), "r"(b));
  return r;
}
__device__ __forceinline__ uint32_t hsub2_bf16(uint32_t a, uint32_t b) {
  uint32_t r;
  asm("sub.rn.bf16x2 %0, %1, %2;" : "=r"(r) : "r"(a), "r"(b));
  return r;
}
__device__ __forceinline__ uint32_t hadd2_bf16(uint32_t a, uint32_t b) {
  uint32_t r;
  asm("add.rn.bf16x2 %0, %1, %2;" : "=r"(r) : "r"(a), "r"(b));
  return r;
}
__device__ __forceinline__ uint32_t hfma2_bf16(uint32_t a, uint32_t b, uint32_t c) {
  uint32_t r;
  asm("fma.rn.bf16x2 %0, %1, %2, %3;" : "=r"(r) : "r"(a), "r"(b), "r"(c));
  return r;
}
__device__ __forceinline__ bool mbar_test(uint32_t b, uint32_t ph) {
  uint32_t done;
  asm volatile("{.reg .pred p; mbarrier.test_wait.parity.shared::cta.b64 p, [%1], %2; selp.u32 %0,1,0,p;}" : "=r"(done) : "r"(b), "r"(ph) : "memory");
  return __all_sync(0xffffffffu, done != 0);
}
__device__ __forceinline__ uint4 ldg128_cg(const void* p) {
  uint4 v;
  asm volatile("ld.global.cg.v4.u32 {%0,%1,%2,%3}, [%4];" : "=r"(v.x), "=r"(v.y), "=r"(v.z), "=r"(v.w) : "l"(p) : "memory");
  return v;
}
__device__ __forceinline__ float bf_lo(uint32_t w) { return __uint_as_float(w << 16); }
__device__ __forceinline__ float bf_hi(uint32_t w) { return __uint_as_float(w & 0xffff0000u); }
__device__ __forceinline__ float rbf(float x) { return __bfloat162float(__float2bfloat16_rn(x)); }
__device__ __forceinline__ float ex2f(float x) { float r; asm("ex2.approx.ftz.f32 %0, %1;" : "=f"(r) : "f"(x)); return r; }
__device__ __forceinline__ float rcpf(float x) { float r; asm("rcp.approx.ftz.f32 %0, %1;" : "=f"(r) : "f"(x)); return r; }
__device__ __forceinline__ float tanhf_hw(float x) { float r; asm("tanh.approx.f32 %0, %1;" : "=f"(r) : "f"(x)); return r; }
__device__ __forceinline__ float gelu_tanh(float x) {
  const float c1 = 0.7978845608028654f;
  const float c2 = c1 * 0.044715f;
  const float t = tanhf_hw(x * fmaf(c2, x * x, c1));
  const float hx = 0.5f * x;
  return fmaf(hx, t, hx);
}
__device__ __forceinline__ float silu_f(float x) {
  const float hx = 0.5f * x;
  return fmaf(hx, tanhf_hw(hx), hx);
}

__device__ __forceinline__ void wgmma_n128_tb(float (&d)[64], uint32_t da, uint32_t db, int scale_d) {
  asm volatile(
    "{\n.reg .pred p;\n.reg .b64 da, db;\nsetp.ne.b32 p, %66, 0;\n"
    "mov.b64 da, {%64, 0x40000040};\nmov.b64 db, {%65, 0x40000040};\n"
    "wgmma.mma_async.sync.aligned.m64n128k16.f32.bf16.bf16 {%0, %1, %2, %3, %4, %5, %6, %7, %8, %9, %10, %11, %12, %13, %14, %15, %16, %17, %18, %19, %20, %21, %22, %23, %24, %25, %26, %27, %28, %29, %30, %31, %32, %33, %34, %35, %36, %37, %38, %39, %40, %41, %42, %43, %44, %45, %46, %47, %48, %49, %50, %51, %52, %53, %54, %55, %56, %57, %58, %59, %60, %61, %62, %63}, da, db, p, 1, 1, 0, 1;\n}\n"
    : "+f"(d[0]), "+f"(d[1]), "+f"(d[2]), "+f"(d[3]), "+f"(d[4]), "+f"(d[5]), "+f"(d[6]), "+f"(d[7]), "+f"(d[8]), "+f"(d[9]), "+f"(d[10]), "+f"(d[11]), "+f"(d[12]), "+f"(d[13]), "+f"(d[14]), "+f"(d[15]), "+f"(d[16]), "+f"(d[17]), "+f"(d[18]), "+f"(d[19]), "+f"(d[20]), "+f"(d[21]), "+f"(d[22]), "+f"(d[23]), "+f"(d[24]), "+f"(d[25]), "+f"(d[26]), "+f"(d[27]), "+f"(d[28]), "+f"(d[29]), "+f"(d[30]), "+f"(d[31]), "+f"(d[32]), "+f"(d[33]), "+f"(d[34]), "+f"(d[35]), "+f"(d[36]), "+f"(d[37]), "+f"(d[38]), "+f"(d[39]), "+f"(d[40]), "+f"(d[41]), "+f"(d[42]), "+f"(d[43]), "+f"(d[44]), "+f"(d[45]), "+f"(d[46]), "+f"(d[47]), "+f"(d[48]), "+f"(d[49]), "+f"(d[50]), "+f"(d[51]), "+f"(d[52]), "+f"(d[53]), "+f"(d[54]), "+f"(d[55]), "+f"(d[56]), "+f"(d[57]), "+f"(d[58]), "+f"(d[59]), "+f"(d[60]), "+f"(d[61]), "+f"(d[62]), "+f"(d[63])
    : "r"(da), "r"(db), "r"(scale_d));
}
__device__ __forceinline__ void wgmma_n128_tb_p(float (&d)[64], uint32_t da, uint32_t db, int scale_d, int enable) {
  asm volatile(
    "{\n.reg .pred p;\n.reg .b64 da, db;\nsetp.ne.b32 p, %66, 0;\n.reg .pred q;\nsetp.ne.b32 q, %67, 0;\n"
    "mov.b64 da, {%64, 0x40000040};\nmov.b64 db, {%65, 0x40000040};\n"
    "@q wgmma.mma_async.sync.aligned.m64n128k16.f32.bf16.bf16 {%0, %1, %2, %3, %4, %5, %6, %7, %8, %9, %10, %11, %12, %13, %14, %15, %16, %17, %18, %19, %20, %21, %22, %23, %24, %25, %26, %27, %28, %29, %30, %31, %32, %33, %34, %35, %36, %37, %38, %39, %40, %41, %42, %43, %44, %45, %46, %47, %48, %49, %50, %51, %52, %53, %54, %55, %56, %57, %58, %59, %60, %61, %62, %63}, da, db, p, 1, 1, 0, 1;\n}\n"
    : "+f"(d[0]), "+f"(d[1]), "+f"(d[2]), "+f"(d[3]), "+f"(d[4]), "+f"(d[5]), "+f"(d[6]), "+f"(d[7]), "+f"(d[8]), "+f"(d[9]), "+f"(d[10]), "+f"(d[11]), "+f"(d[12]), "+f"(d[13]), "+f"(d[14]), "+f"(d[15]), "+f"(d[16]), "+f"(d[17]), "+f"(d[18]), "+f"(d[19]), "+f"(d[20]), "+f"(d[21]), "+f"(d[22]), "+f"(d[23]), "+f"(d[24]), "+f"(d[25]), "+f"(d[26]), "+f"(d[27]), "+f"(d[28]), "+f"(d[29]), "+f"(d[30]), "+f"(d[31]), "+f"(d[32]), "+f"(d[33]), "+f"(d[34]), "+f"(d[35]), "+f"(d[36]), "+f"(d[37]), "+f"(d[38]), "+f"(d[39]), "+f"(d[40]), "+f"(d[41]), "+f"(d[42]), "+f"(d[43]), "+f"(d[44]), "+f"(d[45]), "+f"(d[46]), "+f"(d[47]), "+f"(d[48]), "+f"(d[49]), "+f"(d[50]), "+f"(d[51]), "+f"(d[52]), "+f"(d[53]), "+f"(d[54]), "+f"(d[55]), "+f"(d[56]), "+f"(d[57]), "+f"(d[58]), "+f"(d[59]), "+f"(d[60]), "+f"(d[61]), "+f"(d[62]), "+f"(d[63])
    : "r"(da), "r"(db), "r"(scale_d), "r"(enable));
}
__device__ __forceinline__ void wgmma_n112(float (&d)[56], uint32_t da, uint32_t db, int scale_d) {
  asm volatile(
    "{\n.reg .pred p;\n.reg .b64 da, db;\nsetp.ne.b32 p, %58, 0;\n"
    "mov.b64 da, {%56, 0x40000040};\nmov.b64 db, {%57, 0x40000040};\n"
    "wgmma.mma_async.sync.aligned.m64n112k16.f32.bf16.bf16 {%0, %1, %2, %3, %4, %5, %6, %7, %8, %9, %10, %11, %12, %13, %14, %15, %16, %17, %18, %19, %20, %21, %22, %23, %24, %25, %26, %27, %28, %29, %30, %31, %32, %33, %34, %35, %36, %37, %38, %39, %40, %41, %42, %43, %44, %45, %46, %47, %48, %49, %50, %51, %52, %53, %54, %55}, da, db, p, 1, 1, 0, 0;\n}\n"
    : "+f"(d[0]), "+f"(d[1]), "+f"(d[2]), "+f"(d[3]), "+f"(d[4]), "+f"(d[5]), "+f"(d[6]), "+f"(d[7]), "+f"(d[8]), "+f"(d[9]), "+f"(d[10]), "+f"(d[11]), "+f"(d[12]), "+f"(d[13]), "+f"(d[14]), "+f"(d[15]), "+f"(d[16]), "+f"(d[17]), "+f"(d[18]), "+f"(d[19]), "+f"(d[20]), "+f"(d[21]), "+f"(d[22]), "+f"(d[23]), "+f"(d[24]), "+f"(d[25]), "+f"(d[26]), "+f"(d[27]), "+f"(d[28]), "+f"(d[29]), "+f"(d[30]), "+f"(d[31]), "+f"(d[32]), "+f"(d[33]), "+f"(d[34]), "+f"(d[35]), "+f"(d[36]), "+f"(d[37]), "+f"(d[38]), "+f"(d[39]), "+f"(d[40]), "+f"(d[41]), "+f"(d[42]), "+f"(d[43]), "+f"(d[44]), "+f"(d[45]), "+f"(d[46]), "+f"(d[47]), "+f"(d[48]), "+f"(d[49]), "+f"(d[50]), "+f"(d[51]), "+f"(d[52]), "+f"(d[53]), "+f"(d[54]), "+f"(d[55])
    : "r"(da), "r"(db), "r"(scale_d));
}
__device__ __forceinline__ void wgmma_n224_tb(float (&d)[112], uint32_t da, uint32_t db, int scale_d) {
  asm volatile(
    "{\n.reg .pred p;\n.reg .b64 da, db;\nsetp.ne.b32 p, %114, 0;\n"
    "mov.b64 da, {%112, 0x40000040};\nmov.b64 db, {%113, 0x40000040};\n"
    "wgmma.mma_async.sync.aligned.m64n224k16.f32.bf16.bf16 {%0, %1, %2, %3, %4, %5, %6, %7, %8, %9, %10, %11, %12, %13, %14, %15, %16, %17, %18, %19, %20, %21, %22, %23, %24, %25, %26, %27, %28, %29, %30, %31, %32, %33, %34, %35, %36, %37, %38, %39, %40, %41, %42, %43, %44, %45, %46, %47, %48, %49, %50, %51, %52, %53, %54, %55, %56, %57, %58, %59, %60, %61, %62, %63, %64, %65, %66, %67, %68, %69, %70, %71, %72, %73, %74, %75, %76, %77, %78, %79, %80, %81, %82, %83, %84, %85, %86, %87, %88, %89, %90, %91, %92, %93, %94, %95, %96, %97, %98, %99, %100, %101, %102, %103, %104, %105, %106, %107, %108, %109, %110, %111}, da, db, p, 1, 1, 0, 1;\n}\n"
    : "+f"(d[0]), "+f"(d[1]), "+f"(d[2]), "+f"(d[3]), "+f"(d[4]), "+f"(d[5]), "+f"(d[6]), "+f"(d[7]), "+f"(d[8]), "+f"(d[9]), "+f"(d[10]), "+f"(d[11]), "+f"(d[12]), "+f"(d[13]), "+f"(d[14]), "+f"(d[15]), "+f"(d[16]), "+f"(d[17]), "+f"(d[18]), "+f"(d[19]), "+f"(d[20]), "+f"(d[21]), "+f"(d[22]), "+f"(d[23]), "+f"(d[24]), "+f"(d[25]), "+f"(d[26]), "+f"(d[27]), "+f"(d[28]), "+f"(d[29]), "+f"(d[30]), "+f"(d[31]), "+f"(d[32]), "+f"(d[33]), "+f"(d[34]), "+f"(d[35]), "+f"(d[36]), "+f"(d[37]), "+f"(d[38]), "+f"(d[39]), "+f"(d[40]), "+f"(d[41]), "+f"(d[42]), "+f"(d[43]), "+f"(d[44]), "+f"(d[45]), "+f"(d[46]), "+f"(d[47]), "+f"(d[48]), "+f"(d[49]), "+f"(d[50]), "+f"(d[51]), "+f"(d[52]), "+f"(d[53]), "+f"(d[54]), "+f"(d[55]), "+f"(d[56]), "+f"(d[57]), "+f"(d[58]), "+f"(d[59]), "+f"(d[60]), "+f"(d[61]), "+f"(d[62]), "+f"(d[63]), "+f"(d[64]), "+f"(d[65]), "+f"(d[66]), "+f"(d[67]), "+f"(d[68]), "+f"(d[69]), "+f"(d[70]), "+f"(d[71]), "+f"(d[72]), "+f"(d[73]), "+f"(d[74]), "+f"(d[75]), "+f"(d[76]), "+f"(d[77]), "+f"(d[78]), "+f"(d[79]), "+f"(d[80]), "+f"(d[81]), "+f"(d[82]), "+f"(d[83]), "+f"(d[84]), "+f"(d[85]), "+f"(d[86]), "+f"(d[87]), "+f"(d[88]), "+f"(d[89]), "+f"(d[90]), "+f"(d[91]), "+f"(d[92]), "+f"(d[93]), "+f"(d[94]), "+f"(d[95]), "+f"(d[96]), "+f"(d[97]), "+f"(d[98]), "+f"(d[99]), "+f"(d[100]), "+f"(d[101]), "+f"(d[102]), "+f"(d[103]), "+f"(d[104]), "+f"(d[105]), "+f"(d[106]), "+f"(d[107]), "+f"(d[108]), "+f"(d[109]), "+f"(d[110]), "+f"(d[111])
    : "r"(da), "r"(db), "r"(scale_d));
}

constexpr int K1_NS = 5;
constexpr int K1_A_BYTES = 7 * 16384;
constexpr int K1_B_OFF = K1_A_BYTES;
constexpr int K1_STG_OFF = K1_B_OFF + K1_NS * 16384;
constexpr int K1_BAR_OFF = K1_STG_OFF + 8 * 4096;
constexpr int K1_SMEM = K1_BAR_OFF + 256 + 1024;

struct K1Ctx {
  uint32_t sb, bar_full, rel0, rel1;
  uint32_t dA, dBk, dBn;
  bool lane0;
  const CUtensorMap* tm_hs;
  const CUtensorMap* tm_abs;
};
__device__ __forceinline__ void k1_release(const K1Ctx& c, int slot) {
  if (c.lane0) {
    asm volatile("mbarrier.arrive.shared::cluster.b64 _, [%0];" ::"r"(c.rel0 + 8 * slot) : "memory");
    asm volatile("mbarrier.arrive.shared::cluster.b64 _, [%0];" ::"r"(c.rel1 + 8 * slot) : "memory");
  }
}

__device__ __forceinline__ void k1_unit_ab(const K1Ctx& c, int warp, int lane, int mt, int j) {
  const uint32_t stg = c.sb + K1_STG_OFF + warp * 4096;
  const int wq = warp & 3;
  const int st_row = (lane & 7) + 8 * ((lane >> 3) & 1);
  const int st_chunk = lane >> 4;
  float acc[2][56];
  int slot = 0; uint32_t ph = 0;
#pragma unroll 1
  for (int kb = 0; kb < 7; kb++) {
    const int pslot = (slot == 0) ? K1_NS - 1 : slot - 1;
    mbar_wait(c.bar_full + 8 * slot, ph, 3);
    if (kb == 6) named_arrive(2, 256);
    if (kb == 0 && (threadIdx.x & 127) == 0) DBG(0, 4);
    if ((threadIdx.x & 127) == 0) DBGC(1, 46 + kb);
    wg_fence();
    const uint32_t da = c.dA + kb * 1024;
    const uint32_t db = c.dBk + slot * 1024;
#pragma unroll
    for (int k = 0; k < 4; k++) {
      wgmma_n112(acc[0], da + k * 2, db + k * 2, (kb | k) != 0);
      wgmma_n112(acc[1], da + 512 + k * 2, db + k * 2, (kb | k) != 0);
    }
    wg_commit();
    if (kb > 0) { wg_wait<1>(); k1_release(c, pslot); }
    if (++slot == K1_NS) { slot = 0; ph ^= 1; }
  }
  wg_wait<0>();
  k1_release(c, 6 % K1_NS);
  if ((threadIdx.x & 127) == 0) DBG(0, 5);
  const uint32_t sgn = (j < 4) ? 0u : 0x80008000u;
  const uint32_t sa = stg + st_row * 224 + st_chunk * 16;
  const int row0 = (j < 4 ? 0 : 2048) + mt * 128 + wq * 16;
#pragma unroll
  for (int h = 0; h < 2; h++) {
    if (h == 1) { if (c.lane0) bulk_wait_read0(); __syncwarp(); }
#pragma unroll
    for (int g = 0; g < 14; g += 2) {
      const float* a = &acc[h][4 * g];
      stmatrix_x4(sa + g * 16, pack_bf16(a[0], a[1]) ^ sgn, pack_bf16(a[2], a[3]) ^ sgn, pack_bf16(a[4], a[5]) ^ sgn, pack_bf16(a[6], a[7]) ^ sgn);
    }
    fence_async_smem();
    __syncwarp();
    if (c.lane0) { tma2d_store(c.tm_abs, stg, (j & 3) * 112, row0 + h * 64); bulk_commit(); }
  }
}

__device__ __forceinline__ void k1_unit_gu(const K1Ctx& c, int warp, int lane, int mt, int unit, int fb, int hsel) {
  const uint32_t stg = c.sb + K1_STG_OFF + warp * 4096;
  const int wq = warp & 3;
  const int full = (unit < 4);
  float acc[2][64];
  const uint32_t dA0 = c.dA + (full ? 0 : hsel * 512);
  int slot = (unit * 7) % K1_NS; uint32_t ph = ((unit * 7) / K1_NS) & 1;
  named_bar(2 + ((unit - 1) & 1), 256);
  if (full) {
#pragma unroll 1
    for (int kb = 0; kb < 7; kb++) {
      const int pslot = (slot == 0) ? K1_NS - 1 : slot - 1;
      mbar_wait(c.bar_full + 8 * slot, ph, 4);
      if (kb == 6) named_arrive(2 + (unit & 1), 256);
      if (kb == 0 && (threadIdx.x & 127) == 0) DBG(0, 4 + 3 * unit);
      wg_fence();
      const uint32_t da = dA0 + kb * 1024;
      const uint32_t db = c.dBn + slot * 1024;
#pragma unroll
      for (int k = 0; k < 4; k++) {
        wgmma_n128_tb(acc[0], da + k * 2, db + k * 128, (kb | k) != 0);
        wgmma_n128_tb(acc[1], da + 512 + k * 2, db + k * 128, (kb | k) != 0);
      }
      wg_commit();
      if (kb > 0) { wg_wait<1>(); k1_release(c, pslot); }
      if (++slot == K1_NS) { slot = 0; ph ^= 1; }
    }
  } else {
#pragma unroll 1
    for (int kb = 0; kb < 7; kb++) {
      const int pslot = (slot == 0) ? K1_NS - 1 : slot - 1;
      mbar_wait(c.bar_full + 8 * slot, ph, 5);
      if (kb == 0 && (threadIdx.x & 127) == 0) DBG(0, 4 + 3 * unit);
      wg_fence();
      const uint32_t da = dA0 + kb * 1024;
      const uint32_t db = c.dBn + slot * 1024;
#pragma unroll
      for (int k = 0; k < 4; k++) wgmma_n128_tb(acc[0], da + k * 2, db + k * 128, (kb | k) != 0);
      wg_commit();
      if (kb > 0) { wg_wait<1>(); k1_release(c, pslot); }
      if (++slot == K1_NS) { slot = 0; ph ^= 1; }
    }
  }
  wg_wait<0>();
  k1_release(c, (slot == 0) ? K1_NS - 1 : slot - 1);
  if ((threadIdx.x & 127) == 0) DBG(0, 5 + 3 * unit);
  const int st_row = (lane & 7) + 8 * ((lane >> 3) & 1);
  const int st_chunk = lane >> 4;
  const uint32_t sa = stg + st_row * 128;
  const int row0 = mt * 128 + (full ? 0 : hsel * 64) + wq * 16;
  if (c.lane0) bulk_wait_read0();
  __syncwarp();
#pragma unroll
  for (int h = 0; h < 2; h++) {
    if (h == 1 && !full) break;
#pragma unroll
    for (int g = 0; g < 8; g += 2) {
      uint32_t pk[4];
#pragma unroll
      for (int e = 0; e < 4; e++) {
        const int i = 4 * g + 2 * e;
        const uint32_t g2 = pack_bf16(acc[h][i], acc[h][i + 1]);
        const uint32_t u2 = pack_bf16(acc[h][32 + i], acc[h][32 + i + 1]);
        pk[e] = hmul2_bf16(pack_bf16(gelu_tanh(bf_lo(g2)), gelu_tanh(bf_hi(g2))), u2);
      }
      stmatrix_x4(sa + h * 2048 + (((g + st_chunk) ^ (st_row & 7)) * 16), pk[0], pk[1], pk[2], pk[3]);
    }
    fence_async_smem();
    __syncwarp();
    if (c.lane0) { tma2d_store(c.tm_hs, stg + h * 2048, fb * 64, row0 + h * 64); bulk_commit(); }
  }
}

struct PfPtrs { const uint8_t* wr; const uint8_t* wi; const uint8_t* wg; const uint8_t* wu; const uint8_t* wd; const uint8_t* cr; const uint8_t* ci; };

__global__ void __cluster_dims__(2, 1, 1) __launch_bounds__(384, 1)
k1_kernel(const __grid_constant__ CUtensorMap tm_wr, const __grid_constant__ CUtensorMap tm_wi,
          const __grid_constant__ CUtensorMap tm_wg, const __grid_constant__ CUtensorMap tm_wu,
          const __grid_constant__ CUtensorMap tm_hs, const __grid_constant__ CUtensorMap tm_abs,
          const __nv_bfloat16* __restrict__ x, const PfPtrs pf) {
  extern __shared__ uint8_t smem_raw[];
  const uint32_t sb = (s2u(smem_raw) + 1023) & ~1023u;
  const int tid = threadIdx.x, warp = tid >> 5, lane = tid & 31;
  uint32_t rank;
  asm volatile("mov.u32 %0, %%cluster_ctarank;" : "=r"(rank));
  const int cid = blockIdx.x >> 1;
  const int p = cid >> 3, j = cid & 7;
  const int mt = 2 * p + (int)rank;
  const uint32_t bar_full = sb + K1_BAR_OFF;
  const uint32_t bar_empty = bar_full + 8 * K1_NS;
  const int fb_base = 7 * (j >> 1);
  const int fb0 = fb_base + ((j & 1) ? 4 : 0);
  const int fbh = fb_base + 3;
  const CUtensorMap* tw = (j < 4) ? &tm_wr : &tm_wi;
  const CUtensorMap* tgu = rank ? &tm_wu : &tm_wg;

  if (tid == 0) DBG(0, 0);
  if (tid == 256) {
    for (int i = 0; i < K1_NS; i++) { mbar_init(bar_full + 8 * i, 1); mbar_init(bar_empty + 8 * i, 8); }
    asm volatile("fence.mbarrier_init.release.cluster;" ::: "memory");
    prefetch_tmap(tw);
    prefetch_tmap(tgu);
    prefetch_tmap(&tm_abs);
    prefetch_tmap(&tm_hs);
    if (blockIdx.x < 64) g_flags[blockIdx.x] = 0;
  }
  __syncwarp();
  cluster_arrive_relaxed();
  pdl_launch();

  if (warp >= 8) {
    reg_dec<40>();
    cluster_wait();
    if (tid == 256) {
      int slot = 0; uint32_t ph = 0;
      int kb = 0, unit = 0;
#pragma unroll 1
      for (int s = 0; s < 35; s++) {
        if (s >= K1_NS) mbar_wait(bar_empty + 8 * slot, ph ^ 1, 2);
        DBG(0, 20 + s);
        const uint32_t dst = sb + K1_B_OFF + slot * 16384;
        if (unit == 0) {
          mbar_expect(bar_full + 8 * slot, 14336);
          tma2d_mc(dst + rank * 7168, tw, kb * 64, (j & 3) * 112 + rank * 56, bar_full + 8 * slot, 3);
        } else {
          const int fb = (unit == 4) ? fbh : (fb0 + unit - 1);
          mbar_expect(bar_full + 8 * slot, 16384);
          tma2d_mc(dst + rank * 8192, tgu, fb * 64, kb * 64, bar_full + 8 * slot, 3);
        }
        if (++kb == 7) { kb = 0; unit++; }
        if (++slot == K1_NS) { slot = 0; ph ^= 1; }
      }
    } else if (tid == 288) {
      const int b = blockIdx.x;
      l2_prefetch(pf.wg + b * 12544, 12544);
      l2_prefetch(pf.wu + b * 12544, 12544);
    }
  } else {
    reg_inc<232>();
    const int wg = warp >> 2;
    {
      const int c = lane & 7;
      const int r0 = warp * 16 + (lane >> 3);
      const uint4* src = reinterpret_cast<const uint4*>(x + (size_t)(mt * 128 + r0) * 448) + c;
      uint4 nx[7];
#pragma unroll
      for (int b = 0; b < 7; b++)
        asm volatile("ld.global.nc.v4.u32 {%0,%1,%2,%3}, [%4];" : "=r"(nx[b].x), "=r"(nx[b].y), "=r"(nx[b].z), "=r"(nx[b].w) : "l"(src + b * 8) : "memory");
#pragma unroll
      for (int pass = 1; pass < 4; pass++) asm volatile("prefetch.global.L2 [%0];" ::"l"(src + pass * 4 * 56 + c * 7 - c) : "memory");
#pragma unroll 1
      for (int pass = 0; pass < 4; pass++) {
        uint4 v[7];
#pragma unroll
        for (int b = 0; b < 7; b++) v[b] = nx[b];
        if (pass < 3) {
          const uint4* s2 = src + (pass + 1) * 4 * 56;
#pragma unroll
          for (int b = 0; b < 7; b++)
            asm volatile("ld.global.nc.v4.u32 {%0,%1,%2,%3}, [%4];" : "=r"(nx[b].x), "=r"(nx[b].y), "=r"(nx[b].z), "=r"(nx[b].w) : "l"(s2 + b * 8) : "memory");
        }
        float s0 = 0.f, s1 = 0.f, s2v = 0.f, s3 = 0.f;
#pragma unroll
        for (int b = 0; b < 7; b++) {
          s0 += bf_lo(v[b].x) + bf_hi(v[b].x); s1 += bf_lo(v[b].y) + bf_hi(v[b].y);
          s2v += bf_lo(v[b].z) + bf_hi(v[b].z); s3 += bf_lo(v[b].w) + bf_hi(v[b].w);
        }
        float m = (s0 + s1) + (s2v + s3);
        m += __shfl_xor_sync(0xffffffffu, m, 1);
        m += __shfl_xor_sync(0xffffffffu, m, 2);
        m += __shfl_xor_sync(0xffffffffu, m, 4);
        m *= (1.0f / 448.0f);
        float q0 = 0.f, q1 = 0.f, q2 = 0.f, q3 = 0.f;
#pragma unroll
        for (int b = 0; b < 7; b++) {
          float d;
          d = bf_lo(v[b].x) - m; q0 = fmaf(d, d, q0); d = bf_hi(v[b].x) - m; q1 = fmaf(d, d, q1);
          d = bf_lo(v[b].y) - m; q2 = fmaf(d, d, q2); d = bf_hi(v[b].y) - m; q3 = fmaf(d, d, q3);
          d = bf_lo(v[b].z) - m; q0 = fmaf(d, d, q0); d = bf_hi(v[b].z) - m; q1 = fmaf(d, d, q1);
          d = bf_lo(v[b].w) - m; q2 = fmaf(d, d, q2); d = bf_hi(v[b].w) - m; q3 = fmaf(d, d, q3);
        }
        float q = (q0 + q1) + (q2 + q3);
        q += __shfl_xor_sync(0xffffffffu, q, 1);
        q += __shfl_xor_sync(0xffffffffu, q, 2);
        q += __shfl_xor_sync(0xffffffffu, q, 4);
        const float var_b = rbf(q * (1.0f / 448.0f));
        const float den = rbf(sqrtf(rbf(var_b + 1e-5f)));
        const float ri = 1.0f / den;
        const float rih = rbf(ri);
        const uint32_t rhi2 = pack_bf16(rih, rih), rlo2 = pack_bf16(ri - rih, ri - rih);
        const uint32_t m2 = pack_bf16(m, m);
        const int r = r0 + pass * 4;
        const uint32_t a0 = sb + r * 128 + ((c ^ (r & 7)) * 16);
#pragma unroll
        for (int b = 0; b < 7; b++) {
          uint32_t w4[4] = {v[b].x, v[b].y, v[b].z, v[b].w};
#pragma unroll
          for (int qq = 0; qq < 4; qq++) {
            const uint32_t dw = hsub2_bf16(w4[qq], m2);
            w4[qq] = hfma2_bf16(dw, rhi2, hmul2_bf16(dw, rlo2));
          }
          sts128(a0 + b * 16384, make_uint4(w4[0], w4[1], w4[2], w4[3]));
        }
      }
    }
    if (lane == 0) DBG(0, 59 + (warp & 3));
    asm volatile("fence.proxy.async.shared::cta;" ::: "memory");
    named_bar(1, 256);
    cluster_wait();
    if (tid == 0) DBG(0, 3);

    K1Ctx c;
    c.sb = sb; c.bar_full = bar_full; c.lane0 = (lane == 0);
    asm volatile("mapa.shared::cluster.u32 %0, %1, %2;" : "=r"(c.rel0) : "r"(bar_empty), "r"(0));
    asm volatile("mapa.shared::cluster.u32 %0, %1, %2;" : "=r"(c.rel1) : "r"(bar_empty), "r"(1));
    c.tm_hs = &tm_hs; c.tm_abs = &tm_abs;
    c.dA = make_desc(sb, 16, 1024);
    c.dBk = make_desc(sb + K1_B_OFF, 16, 1024);
    c.dBn = make_desc(sb + K1_B_OFF, 8192, 1024);
    if (wg == 0) {
      k1_unit_ab(c, warp, lane, mt, j);
      if (tid == 0) DBG(0, 6);
    }
#pragma unroll 1
    for (int unit = 2 - wg; unit < 5; unit += 2) {
      k1_unit_gu(c, warp, lane, mt, unit, (unit == 4) ? fbh : fb0 + unit - 1, j & 1);
      if ((tid & 127) == 0) DBG(0, 6 + 3 * unit);
    }
    if (lane == 0) bulk_wait0();
  }
  __syncwarp();
  cluster_arrive_relaxed();
  cluster_wait();
}

constexpr int K2_NS = 4;
constexpr int K2_STAGE = 16384 + 32768;
constexpr int K2_BAR_OFF = K2_NS * K2_STAGE;
constexpr int K2_SMEM = K2_BAR_OFF + 256 + 1024;
constexpr int K2_PITCH = 464;

__device__ __forceinline__ void spin_flag(const unsigned int* flag, unsigned int target) {
  int it = 0;
  while (true) {
    unsigned int v;
    asm volatile("ld.acquire.gpu.global.u32 %0, [%1];" : "=r"(v) : "l"(flag) : "memory");
    if (v >= target) break;
    if (++it > SPIN_LIMIT) { TIMEOUT(20); break; }
  }
}

__global__ void __cluster_dims__(2, 1, 1) __launch_bounds__(384, 1)
k2_kernel(const __grid_constant__ CUtensorMap tm_cr, const __grid_constant__ CUtensorMap tm_ci, const __grid_constant__ CUtensorMap tm_h,
          const __grid_constant__ CUtensorMap tm_ab, const __grid_constant__ CUtensorMap tm_wd,
          const __nv_bfloat16* __restrict__ x, __nv_bfloat16* __restrict__ out) {
  extern __shared__ uint8_t smem_raw[];
  const uint32_t sb = (s2u(smem_raw) + 1023) & ~1023u;
  const int tid = threadIdx.x, warp = tid >> 5, lane = tid & 31;
  uint32_t rank;
  asm volatile("mov.u32 %0, %%cluster_ctarank;" : "=r"(rank));
  const int cid = blockIdx.x >> 1;
  const int q = cid & 3, n = (cid >> 2) & 1, p = cid >> 3;
  const int mt = 2 * p + (int)rank;
  const int tile = mt * 2 + n;
  const uint32_t bar_full = sb + K2_BAR_OFF;
  const uint32_t bar_empty = bar_full + 8 * K2_NS;
  const int g0 = (q == 0) ? 0 : (q == 1 ? 22 : (q == 2 ? 43 : 64));
  const int nkb = (q == 0) ? 22 : (q == 3 ? 28 : 21);

  if (tid == 0) DBG(1, 0);
  if (tid == 256) {
    for (int i = 0; i < K2_NS; i++) { mbar_init(bar_full + 8 * i, 1); mbar_init(bar_empty + 8 * i, 16); }
    mbar_init(bar_empty + 8 * K2_NS, 1);
    asm volatile("fence.mbarrier_init.release.cluster;" ::: "memory");
    if (q == 3) { prefetch_tmap(&tm_h); prefetch_tmap(&tm_wd); }
    else { prefetch_tmap(&tm_cr); prefetch_tmap(&tm_ci); prefetch_tmap(&tm_ab); }
  }
  __syncwarp();
  cluster_arrive_relaxed();
  cluster_wait();

  if (warp >= 8) {
    reg_dec<40>();
    if (tid == 256) {
      const CUtensorMap* tb = (q < 3) ? &tm_ab : &tm_wd;
      const int kb0 = (q < 3) ? g0 : 0;
      int slot = 0; uint32_t ph = 0;
#pragma unroll 1
      for (int it = 0; it < nkb + K2_NS; it++) {
        const int s = (it < K2_NS) ? it : it - K2_NS;
        const bool pre = (it < K2_NS), post = (!pre && s < K2_NS);
        if (it == K2_NS) { pdl_wait(); DBG(1, 31); slot = 0; }
        if (!pre && !post) mbar_wait(bar_empty + 8 * slot, ph, 10);
        const uint32_t dst = sb + slot * K2_STAGE;
        const uint32_t fb = bar_full + 8 * slot;
        if (!post) mbar_expect(fb, K2_STAGE);
        const bool doA = pre ? (q < 3) : (post ? (q == 3) : true);
        const bool doB = pre ? (q == 3) : (post ? (q < 3) : true);
        if (doA) {
          const int g = g0 + s;
          const CUtensorMap* ta = (g < 32) ? &tm_cr : (g < 64 ? &tm_ci : &tm_h);
          tma2d(dst, ta, (g & 31) * 64 + ((g >= 96) ? 2048 : 0), mt * 128, fb);
        }
        if (doB) {
          tma3d_mc(dst + 16384 + (2 * rank) * 8192, tb, (2 * rank) * 64, n, (kb0 + s) * 64, fb, 3);
          tma3d_mc(dst + 16384 + (2 * rank + 1) * 8192, tb, (2 * rank + 1) * 64, n, (kb0 + s) * 64, fb, 3);
        }
        if (++slot == K2_NS) { slot = 0; if (!pre && !post) ph ^= 1; }
      }
      if (q == 3) {
        const uint32_t bar_p = bar_empty + 8 * K2_NS;
        spin_flag(&g_flags[tile], 3u);
        asm volatile("fence.proxy.async;" ::: "memory");
        mbar_expect(bar_p, 3 * 57344);
        const uint4* pp = g_part + (size_t)tile * (3 * 14 * 256);
#pragma unroll 1
        for (int c = 0; c < 7; c++) {
          if ((c & 1) == 0) mbar_wait(bar_empty + 8 * (c >> 1), ph, 13);
          bulk_load(sb + c * 24576, pp + c * 1536, 24576, bar_p);
        }
        DBG(1, 30);
      }
    }
  } else {
    reg_inc<232>();
    const int wg = warp >> 2;
    float acc[112];
    uint32_t rel0, rel1;
    asm volatile("mapa.shared::cluster.u32 %0, %1, %2;" : "=r"(rel0) : "r"(bar_empty), "r"(0));
    asm volatile("mapa.shared::cluster.u32 %0, %1, %2;" : "=r"(rel1) : "r"(bar_empty), "r"(1));
    const uint32_t dA0 = make_desc(sb + wg * 8192, 16, 1024);
    const uint32_t dB0 = make_desc(sb + 16384, 8192, 1024);
    int slot = 0; uint32_t ph = 0;
#pragma unroll 1
    for (int s = 0; s < nkb; s++) {
      mbar_wait(bar_full + 8 * slot, ph, 11);
      if (tid == 0) DBG(1, 1 + s);
      if (tid == 0 && (s == 5 || s == 15)) DBGC(1, 53 + (s == 15));
      if (tid == 0 && (s == 23 || s == 27)) DBGC(1, 55 + (s == 27));
      wg_fence();
      const uint32_t da = dA0 + slot * (K2_STAGE / 16);
      const uint32_t db = dB0 + slot * (K2_STAGE / 16);
#pragma unroll
      for (int k = 0; k < 4; k++) wgmma_n224_tb(acc, da + k * 2, db + k * 128, (s | k) != 0);
      wg_commit();
      if (s > 0) {
        wg_wait<1>();
        const int ps = (slot == 0) ? K2_NS - 1 : slot - 1;
        if (lane == 0) {
          asm volatile("mbarrier.arrive.shared::cluster.b64 _, [%0];" ::"r"(rel0 + 8 * ps) : "memory");
          asm volatile("mbarrier.arrive.shared::cluster.b64 _, [%0];" ::"r"(rel1 + 8 * ps) : "memory");
        }
      }
      if (++slot == K2_NS) { slot = 0; ph ^= 1; }
    }
    wg_wait<0>();
    pdl_wait();
    if (tid == 0) DBG(1, 29);
    if (q < 3) {
      uint4* part = g_part + (size_t)(tile * 3 + q) * (14 * 256) + tid;
#pragma unroll
      for (int g = 0; g < 14; g++)
        part[g * 256] = make_uint4(pack_bf16(acc[8 * g], acc[8 * g + 1]), pack_bf16(acc[8 * g + 2], acc[8 * g + 3]),
                                   pack_bf16(acc[8 * g + 4], acc[8 * g + 5]), pack_bf16(acc[8 * g + 6], acc[8 * g + 7]));
      __threadfence();
      asm volatile("fence.proxy.async;" ::: "memory");
      named_bar(1, 256);
      if (tid == 0) atomicAdd(&g_flags[tile], 1u);
    } else {
      if (lane == 0) {
        asm volatile("mbarrier.arrive.shared::cluster.b64 _, [%0];" ::"r"(rel0 + 8 * (K2_NS - 1)) : "memory");
        asm volatile("mbarrier.arrive.shared::cluster.b64 _, [%0];" ::"r"(rel1 + 8 * (K2_NS - 1)) : "memory");
      }
      const uint32_t bar_p = bar_empty + 8 * K2_NS;
      const int lc = (lane < 28) ? lane : 27;
      const size_t gbase = (size_t)(mt * 128 + warp * 16) * 448 + n * 224 + lc * 8;
      uint4 xv[16];
#pragma unroll
      for (int t = 0; t < 16; t++) xv[t] = ldg128_cg(x + gbase + t * 448);
      uint32_t gw[56];
#pragma unroll
      for (int i = 0; i < 56; i++) {
        const uint32_t f2 = pack_bf16(acc[2 * i], acc[2 * i + 1]);
        gw[i] = pack_bf16(silu_f(bf_lo(f2)), silu_f(bf_hi(f2)));
      }
      if (tid == 0) DBG(1, 62);
      mbar_wait(bar_p, 0, 12);
      const uint32_t tb = sb + tid * 16;
#pragma unroll
      for (int g = 0; g < 14; g++) {
        const uint4 a = lds128(tb + g * 4096), b = lds128(tb + (14 + g) * 4096), cc = lds128(tb + (28 + g) * 4096);
        gw[4 * g] = hmul2_bf16(pack_bf16(bf_lo(a.x) + bf_lo(b.x) + bf_lo(cc.x), bf_hi(a.x) + bf_hi(b.x) + bf_hi(cc.x)), gw[4 * g]);
        gw[4 * g + 1] = hmul2_bf16(pack_bf16(bf_lo(a.y) + bf_lo(b.y) + bf_lo(cc.y), bf_hi(a.y) + bf_hi(b.y) + bf_hi(cc.y)), gw[4 * g + 1]);
        gw[4 * g + 2] = hmul2_bf16(pack_bf16(bf_lo(a.z) + bf_lo(b.z) + bf_lo(cc.z), bf_hi(a.z) + bf_hi(b.z) + bf_hi(cc.z)), gw[4 * g + 2]);
        gw[4 * g + 3] = hmul2_bf16(pack_bf16(bf_lo(a.w) + bf_lo(b.w) + bf_lo(cc.w), bf_hi(a.w) + bf_hi(b.w) + bf_hi(cc.w)), gw[4 * g + 3]);
      }
      named_bar(1, 256);
      const uint32_t wbase = sb + warp * 16 * K2_PITCH;
      const int st_row = (lane & 7) + 8 * ((lane >> 3) & 1);
      const uint32_t sa = wbase + st_row * K2_PITCH + (lane >> 4) * 16;
#pragma unroll
      for (int g = 0; g < 28; g += 2) stmatrix_x4(sa + g * 16, gw[2 * g], gw[2 * g + 1], gw[2 * g + 2], gw[2 * g + 3]);
      __syncwarp();
      const uint32_t lp = wbase + lc * 16;
#pragma unroll
      for (int t = 0; t < 16; t++) {
        const uint4 tv = lds128(lp + t * K2_PITCH);
        uint4 o;
        o.x = hadd2_bf16(xv[t].x, tv.x); o.y = hadd2_bf16(xv[t].y, tv.y); o.z = hadd2_bf16(xv[t].z, tv.z); o.w = hadd2_bf16(xv[t].w, tv.w);
        if (lane < 28) stg128(out + gbase + t * 448, o);
      }
    }
    if (tid == 0) DBG(1, 63);
  }
  __syncwarp();
  cluster_arrive_relaxed();
  cluster_wait();
}

typedef CUresult (*EncFn)(CUtensorMap*, CUtensorMapDataType, cuuint32_t, void*, const cuuint64_t*, const cuuint64_t*, const cuuint32_t*,
                          const cuuint32_t*, CUtensorMapInterleave, CUtensorMapSwizzle, CUtensorMapL2promotion, CUtensorMapFloatOOBfill);

void make2d(EncFn enc, CUtensorMap* tm, const void* ptr, uint64_t cols, uint64_t rows, uint32_t bc, uint32_t br, bool swz = true) {
  cuuint64_t gd[2] = {cols, rows};
  cuuint64_t gs[1] = {cols * 2};
  cuuint32_t bd[2] = {bc, br};
  cuuint32_t es[2] = {1, 1};
  enc(tm, CU_TENSOR_MAP_DATA_TYPE_BFLOAT16, 2, const_cast<void*>(ptr), gd, gs, bd, es, CU_TENSOR_MAP_INTERLEAVE_NONE,
      swz ? CU_TENSOR_MAP_SWIZZLE_128B : CU_TENSOR_MAP_SWIZZLE_NONE, CU_TENSOR_MAP_L2_PROMOTION_L2_128B, CU_TENSOR_MAP_FLOAT_OOB_FILL_NONE);
}
void make3d_half(EncFn enc, CUtensorMap* tm, const void* ptr, uint64_t rows) {
  cuuint64_t gd[3] = {224, 2, rows};
  cuuint64_t gs[2] = {448, 896};
  cuuint32_t bd[3] = {64, 1, 64};
  cuuint32_t es[3] = {1, 1, 1};
  enc(tm, CU_TENSOR_MAP_DATA_TYPE_BFLOAT16, 3, const_cast<void*>(ptr), gd, gs, bd, es, CU_TENSOR_MAP_INTERLEAVE_NONE,
      CU_TENSOR_MAP_SWIZZLE_128B, CU_TENSOR_MAP_L2_PROMOTION_L2_128B, CU_TENSOR_MAP_FLOAT_OOB_FILL_NONE);
}

struct Maps { CUtensorMap wr, wi, wg, wu, cr, ci, h, ab, wd, hs, abs; };

}

extern "C" void kernel_launch(void* const* d_in, const int* in_sizes, int n_in, void* d_out, int out_size) {
  (void)in_sizes; (void)n_in; (void)out_size;
  static Maps maps;
  static const void* cached[9] = {nullptr};
  static bool attr_done = false;
  bool same = true;
  for (int i = 0; i < 9; i++) same = same && (cached[i] == d_in[i]);
  if (!same) {
    void* fn = nullptr;
    cudaDriverEntryPointQueryResult qr;
    cudaGetDriverEntryPoint("cuTensorMapEncodeTiled", &fn, cudaEnableDefault, &qr);
    EncFn enc = (EncFn)fn;
    void *p_ab = nullptr, *p_h = nullptr;
    cudaGetSymbolAddress(&p_ab, g_ab);
    cudaGetSymbolAddress(&p_h, g_h);
    make2d(enc, &maps.cr, d_in[1], 2048, 2048, 64, 128);
    make2d(enc, &maps.ci, d_in[2], 2048, 2048, 64, 128);
    make2d(enc, &maps.wr, d_in[3], 448, 448, 64, 56);
    make2d(enc, &maps.wi, d_in[4], 448, 448, 64, 56);
    make2d(enc, &maps.wg, d_in[6], 1792, 448, 64, 64);
    make2d(enc, &maps.wu, d_in[7], 1792, 448, 64, 64);
    make3d_half(enc, &maps.wd, d_in[8], 1792);
    make2d(enc, &maps.h, p_h, 1792, 2048, 64, 128);
    make3d_half(enc, &maps.ab, p_ab, 4096);
    make2d(enc, &maps.hs, p_h, 1792, 2048, 64, 16);
    make2d(enc, &maps.abs, p_ab, 448, 4096, 112, 16, false);
    for (int i = 0; i < 9; i++) cached[i] = d_in[i];
  }
  if (!attr_done) {
    cudaFuncSetAttribute(k1_kernel, cudaFuncAttributeMaxDynamicSharedMemorySize, K1_SMEM);
    cudaFuncSetAttribute(k2_kernel, cudaFuncAttributeMaxDynamicSharedMemorySize, K2_SMEM);
    attr_done = true;
  }
  PfPtrs pf;
  pf.wr = (const uint8_t*)d_in[3]; pf.wi = (const uint8_t*)d_in[4]; pf.wg = (const uint8_t*)d_in[6]; pf.wu = (const uint8_t*)d_in[7];
  pf.wd = (const uint8_t*)d_in[8]; pf.cr = (const uint8_t*)d_in[1]; pf.ci = (const uint8_t*)d_in[2];
  k1_kernel<<<128, 384, K1_SMEM>>>(maps.wr, maps.wi, maps.wg, maps.wu, maps.hs, maps.abs, (const __nv_bfloat16*)d_in[0], pf);

  cudaLaunchConfig_t cfg = {};
  cfg.gridDim = dim3(128); cfg.blockDim = dim3(384); cfg.dynamicSmemBytes = K2_SMEM; cfg.stream = cudaStreamPerThread;
  cudaLaunchAttribute at[1];
  at[0].id = cudaLaunchAttributeProgrammaticStreamSerialization;
  at[0].val.programmaticStreamSerializationAllowed = 1;
  cfg.attrs = at; cfg.numAttrs = 1;
  cudaLaunchKernelEx(&cfg, k2_kernel, maps.cr, maps.ci, maps.h, maps.ab, maps.wd, (const __nv_bfloat16*)d_in[0], (__nv_bfloat16*)d_out);
}
```

```cpp
#include <cuda_runtime.h>
#include <cuda_bf16.h>
#include <cuda.h>
#include <stdint.h>

namespace {

__device__ __align__(1024) __nv_bfloat16 g_ab[4096 * 448];
__device__ __align__(1024) __nv_bfloat16 g_h[2048 * 1792];
__device__ uint4 g_part[32 * 3 * 14 * 256];
__device__ __align__(1024) __nv_bfloat16 g_s[2048 * 448];
__device__ unsigned int g_epoch;
__device__ unsigned int g_ab_cnt;
__device__ unsigned int g_h_cnt[16];
__device__ unsigned int g_flags[64];

#define DBG(k, i) do {} while (0)
#define DBGC(k, i) do {} while (0)

#define TIMEOUT(code) __trap()
#define SPIN_LIMIT (1 << 22)
__device__ __forceinline__ uint32_t s2u(const void* p) { return (uint32_t)__cvta_generic_to_shared(p); }
__device__ __forceinline__ void mbar_init(uint32_t b, int c) { asm volatile("mbarrier.init.shared::cta.b64 [%0], %1;" ::"r"(b), "r"(c)); }
__device__ __forceinline__ void mbar_expect(uint32_t b, uint32_t bytes) {
  asm volatile("mbarrier.arrive.expect_tx.shared::cta.b64 _, [%0], %1;" ::"r"(b), "r"(bytes) : "memory");
}
__device__ __forceinline__ void mbar_wait(uint32_t b, uint32_t ph, int code = 1) {
  uint32_t done = 0;
  int it = 0;
  while (true) {
    asm volatile("{.reg .pred p; mbarrier.try_wait.parity.shared::cta.b64 p, [%1], %2; selp.u32 %0,1,0,p;}" : "=r"(done) : "r"(b), "r"(ph) : "memory");
    if (done) break;
    if (++it > SPIN_LIMIT) { TIMEOUT(code); break; }
  }
}
__device__ __forceinline__ void mbar_arrive_cluster(uint32_t b, uint32_t cta) {
  uint32_t r;
  asm volatile("mapa.shared::cluster.u32 %0, %1, %2;" : "=r"(r) : "r"(b), "r"(cta));
  asm volatile("mbarrier.arrive.shared::cluster.b64 _, [%0];" ::"r"(r) : "memory");
}
__device__ __forceinline__ void tma2d(uint32_t dst, const CUtensorMap* m, int c0, int c1, uint32_t bar) {
  asm volatile("cp.async.bulk.tensor.2d.shared::cluster.global.mbarrier::complete_tx::bytes [%0], [%1, {%3,%4}], [%2];" ::"r"(dst), "l"(m), "r"(bar), "r"(c0), "r"(c1) : "memory");
}
__device__ __forceinline__ void tma2d_mc(uint32_t dst, const CUtensorMap* m, int c0, int c1, uint32_t bar, uint16_t mask) {
  asm volatile("cp.async.bulk.tensor.2d.shared::cluster.global.mbarrier::complete_tx::bytes.multicast::cluster [%0], [%1, {%3,%4}], [%2], %5;" ::"r"(dst), "l"(m), "r"(bar), "r"(c0), "r"(c1), "h"(mask) : "memory");
}
__device__ __forceinline__ void tma3d_mc(uint32_t dst, const CUtensorMap* m, int c0, int c1, int c2, uint32_t bar, uint16_t mask) {
  asm volatile("cp.async.bulk.tensor.3d.shared::cluster.global.mbarrier::complete_tx::bytes.multicast::cluster [%0], [%1, {%3,%4,%5}], [%2], %6;" ::"r"(dst), "l"(m), "r"(bar), "r"(c0), "r"(c1), "r"(c2), "h"(mask) : "memory");
}
__device__ __forceinline__ void tma2d_store(const CUtensorMap* m, uint32_t src, int c0, int c1) {
  asm volatile("cp.async.bulk.tensor.2d.global.shared::cta.bulk_group [%0, {%2,%3}], [%1];" ::"l"(m), "r"(src), "r"(c0), "r"(c1) : "memory");
}
__device__ __forceinline__ void bulk_load(uint32_t dst, const void* src, uint32_t bytes, uint32_t bar) {
  asm volatile("cp.async.bulk.shared::cluster.global.mbarrier::complete_tx::bytes [%0], [%1], %2, [%3];" ::"r"(dst), "l"(src), "r"(bytes), "r"(bar) : "memory");
}
__device__ __forceinline__ void bulk_commit() { asm volatile("cp.async.bulk.commit_group;" ::: "memory"); }
__device__ __forceinline__ void bulk_wait_read0() { asm volatile("cp.async.bulk.wait_group.read 0;" ::: "memory"); }
__device__ __forceinline__ void bulk_wait0() { asm volatile("cp.async.bulk.wait_group 0;" ::: "memory"); }
__device__ __forceinline__ void fence_async_smem() { asm volatile("fence.proxy.async.shared::cta;" ::: "memory"); }
__device__ __forceinline__ void prefetch_tmap(const CUtensorMap* m) { asm volatile("prefetch.tensormap [%0];" ::"l"(m) : "memory"); }
__device__ __forceinline__ void l2_prefetch(const void* p, uint32_t bytes) {
  asm volatile("cp.async.bulk.prefetch.L2.global [%0], %1;" ::"l"(p), "r"(bytes) : "memory");
}
__device__ __forceinline__ void cluster_arrive_relaxed() { asm volatile("barrier.cluster.arrive.relaxed.aligned;" ::: "memory"); }
__device__ __forceinline__ void cluster_wait() { asm volatile("barrier.cluster.wait.aligned;" ::: "memory"); }
__device__ __forceinline__ void wg_fence() { __syncwarp(); asm volatile("wgmma.fence.sync.aligned;" ::: "memory"); }
__device__ __forceinline__ void wg_commit() { asm volatile("wgmma.commit_group.sync.aligned;" ::: "memory"); }
template <int N> __device__ __forceinline__ void wg_wait() { __syncwarp(); asm volatile("wgmma.wait_group.sync.aligned %0;" ::"n"(N) : "memory"); }
__device__ __forceinline__ void named_bar(int id, int n) { asm volatile("bar.sync %0, %1;" ::"r"(id), "r"(n) : "memory"); }
__device__ __forceinline__ void named_arrive(int id, int n) { asm volatile("bar.arrive %0, %1;" ::"r"(id), "r"(n) : "memory"); }
template <int N> __device__ __forceinline__ void reg_inc() { asm volatile("setmaxnreg.inc.sync.aligned.u32 %0;" ::"n"(N)); }
template <int N> __device__ __forceinline__ void reg_dec() { asm volatile("setmaxnreg.dec.sync.aligned.u32 %0;" ::"n"(N)); }
__device__ __forceinline__ void pdl_wait() { asm volatile("griddepcontrol.wait;" ::: "memory"); }
__device__ __forceinline__ void pdl_launch() { asm volatile("griddepcontrol.launch_dependents;" ::: "memory"); }

__device__ __forceinline__ uint32_t make_desc(uint32_t addr, uint32_t lbo, uint32_t  ) {
  return ((addr & 0x3FFFF) >> 4) | ((lbo >> 4) << 16);
}
__device__ __forceinline__ void stmatrix_x4(uint32_t addr, uint32_t r0, uint32_t r1, uint32_t r2, uint32_t r3) {
  asm volatile("stmatrix.sync.aligned.m8n8.x4.shared.b16 [%0], {%1,%2,%3,%4};" ::"r"(addr), "r"(r0), "r"(r1), "r"(r2), "r"(r3) : "memory");
}
__device__ __forceinline__ uint4 lds128(uint32_t a) {
  uint4 v;
  asm volatile("ld.shared.v4.u32 {%0,%1,%2,%3}, [%4];" : "=r"(v.x), "=r"(v.y), "=r"(v.z), "=r"(v.w) : "r"(a) : "memory");
  return v;
}
__device__ __forceinline__ void sts128(uint32_t a, uint4 v) {
  asm volatile("st.shared.v4.u32 [%0], {%1,%2,%3,%4};" ::"r"(a), "r"(v.x), "r"(v.y), "r"(v.z), "r"(v.w) : "memory");
}
__device__ __forceinline__ void stg128(void* p, uint4 v) {
  asm volatile("st.global.v4.u32 [%0], {%1,%2,%3,%4};" ::"l"(p), "r"(v.x), "r"(v.y), "r"(v.z), "r"(v.w) : "memory");
}
__device__ __forceinline__ void cp_async16(uint32_t dst, const void* src) {
  asm volatile("cp.async.cg.shared.global [%0], [%1], 16;" ::"r"(dst), "l"(src) : "memory");
}
__device__ __forceinline__ void cp_async8(uint32_t dst, const void* src) {
  asm volatile("cp.async.ca.shared.global [%0], [%1], 8;" ::"r"(dst), "l"(src) : "memory");
}
__device__ __forceinline__ uint2 lds64(uint32_t a) {
  uint2 v;
  asm volatile("ld.shared.v2.u32 {%0,%1}, [%2];" : "=r"(v.x), "=r"(v.y) : "r"(a) : "memory");
  return v;
}
__device__ __forceinline__ void cp_async_wait_all() { asm volatile("cp.async.wait_all;" ::: "memory"); }
__device__ __forceinline__ uint32_t pack_bf16(float lo, float hi) {
  uint32_t r;
  asm("cvt.rn.bf16x2.f32 %0, %1, %2;" : "=r"(r) : "f"(hi), "f"(lo));
  return r;
}
__device__ __forceinline__ uint32_t hmul2_bf16(uint32_t a, uint32_t b) {
  uint32_t r;
  asm("mul.rn.bf16x2 %0, %1, %2;" : "=r"(r) : "r"(a), "r"(b));
  return r;
}
__device__ __forceinline__ uint32_t hsub2_bf16(uint32_t a, uint32_t b) {
  uint32_t r;
  asm("sub.rn.bf16x2 %0, %1, %2;" : "=r"(r) : "r"(a), "r"(b));
  return r;
}
__device__ __forceinline__ uint32_t hadd2_bf16(uint32_t a, uint32_t b) {
  uint32_t r;
  asm("add.rn.bf16x2 %0, %1, %2;" : "=r"(r) : "r"(a), "r"(b));
  return r;
}
__device__ __forceinline__ uint32_t hfma2_bf16(uint32_t a, uint32_t b, uint32_t c) {
  uint32_t r;
  asm("fma.rn.bf16x2 %0, %1, %2, %3;" : "=r"(r) : "r"(a), "r"(b), "r"(c));
  return r;
}
__device__ __forceinline__ bool mbar_test(uint32_t b, uint32_t ph) {
  uint32_t done;
  asm volatile("{.reg .pred p; mbarrier.test_wait.parity.shared::cta.b64 p, [%1], %2; selp.u32 %0,1,0,p;}" : "=r"(done) : "r"(b), "r"(ph) : "memory");
  return __all_sync(0xffffffffu, done != 0);
}
__device__ __forceinline__ uint4 ldg128_cg(const void* p) {
  uint4 v;
  asm volatile("ld.global.cg.v4.u32 {%0,%1,%2,%3}, [%4];" : "=r"(v.x), "=r"(v.y), "=r"(v.z), "=r"(v.w) : "l"(p) : "memory");
  return v;
}
__device__ __forceinline__ float bf_lo(uint32_t w) { return __uint_as_float(w << 16); }
__device__ __forceinline__ float bf_hi(uint32_t w) { return __uint_as_float(w & 0xffff0000u); }
__device__ __forceinline__ float rbf(float x) { return __bfloat162float(__float2bfloat16_rn(x)); }
__device__ __forceinline__ float ex2f(float x) { float r; asm("ex2.approx.ftz.f32 %0, %1;" : "=f"(r) : "f"(x)); return r; }
__device__ __forceinline__ float rcpf(float x) { float r; asm("rcp.approx.ftz.f32 %0, %1;" : "=f"(r) : "f"(x)); return r; }
__device__ __forceinline__ float tanhf_hw(float x) { float r; asm("tanh.approx.f32 %0, %1;" : "=f"(r) : "f"(x)); return r; }
__device__ __forceinline__ float gelu_tanh(float x) {
  const float c1 = 0.7978845608028654f;
  const float c2 = c1 * 0.044715f;
  const float t = tanhf_hw(x * fmaf(c2, x * x, c1));
  const float hx = 0.5f * x;
  return fmaf(hx, t, hx);
}
__device__ __forceinline__ float silu_f(float x) {
  const float hx = 0.5f * x;
  return fmaf(hx, tanhf_hw(hx), hx);
}

__device__ __forceinline__ void wgmma_n128_tb(float (&d)[64], uint32_t da, uint32_t db, int scale_d) {
  asm volatile(
    "{\n.reg .pred p;\n.reg .b64 da, db;\nsetp.ne.b32 p, %66, 0;\n"
    "mov.b64 da, {%64, 0x40000040};\nmov.b64 db, {%65, 0x40000040};\n"
    "wgmma.mma_async.sync.aligned.m64n128k16.f32.bf16.bf16 {%0, %1, %2, %3, %4, %5, %6, %7, %8, %9, %10, %11, %12, %13, %14, %15, %16, %17, %18, %19, %20, %21, %22, %23, %24, %25, %26, %27, %28, %29, %30, %31, %32, %33, %34, %35, %36, %37, %38, %39, %40, %41, %42, %43, %44, %45, %46, %47, %48, %49, %50, %51, %52, %53, %54, %55, %56, %57, %58, %59, %60, %61, %62, %63}, da, db, p, 1, 1, 0, 1;\n}\n"
    : "+f"(d[0]), "+f"(d[1]), "+f"(d[2]), "+f"(d[3]), "+f"(d[4]), "+f"(d[5]), "+f"(d[6]), "+f"(d[7]), "+f"(d[8]), "+f"(d[9]), "+f"(d[10]), "+f"(d[11]), "+f"(d[12]), "+f"(d[13]), "+f"(d[14]), "+f"(d[15]), "+f"(d[16]), "+f"(d[17]), "+f"(d[18]), "+f"(d[19]), "+f"(d[20]), "+f"(d[21]), "+f"(d[22]), "+f"(d[23]), "+f"(d[24]), "+f"(d[25]), "+f"(d[26]), "+f"(d[27]), "+f"(d[28]), "+f"(d[29]), "+f"(d[30]), "+f"(d[31]), "+f"(d[32]), "+f"(d[33]), "+f"(d[34]), "+f"(d[35]), "+f"(d[36]), "+f"(d[37]), "+f"(d[38]), "+f"(d[39]), "+f"(d[40]), "+f"(d[41]), "+f"(d[42]), "+f"(d[43]), "+f"(d[44]), "+f"(d[45]), "+f"(d[46]), "+f"(d[47]), "+f"(d[48]), "+f"(d[49]), "+f"(d[50]), "+f"(d[51]), "+f"(d[52]), "+f"(d[53]), "+f"(d[54]), "+f"(d[55]), "+f"(d[56]), "+f"(d[57]), "+f"(d[58]), "+f"(d[59]), "+f"(d[60]), "+f"(d[61]), "+f"(d[62]), "+f"(d[63])
    : "r"(da), "r"(db), "r"(scale_d));
}
__device__ __forceinline__ void wgmma_n128_tb_p(float (&d)[64], uint32_t da, uint32_t db, int scale_d, int enable) {
  asm volatile(
    "{\n.reg .pred p;\n.reg .b64 da, db;\nsetp.ne.b32 p, %66, 0;\n.reg .pred q;\nsetp.ne.b32 q, %67, 0;\n"
    "mov.b64 da, {%64, 0x40000040};\nmov.b64 db, {%65, 0x40000040};\n"
    "@q wgmma.mma_async.sync.aligned.m64n128k16.f32.bf16.bf16 {%0, %1, %2, %3, %4, %5, %6, %7, %8, %9, %10, %11, %12, %13, %14, %15, %16, %17, %18, %19, %20, %21, %22, %23, %24, %25, %26, %27, %28, %29, %30, %31, %32, %33, %34, %35, %36, %37, %38, %39, %40, %41, %42, %43, %44, %45, %46, %47, %48, %49, %50, %51, %52, %53, %54, %55, %56, %57, %58, %59, %60, %61, %62, %63}, da, db, p, 1, 1, 0, 1;\n}\n"
    : "+f"(d[0]), "+f"(d[1]), "+f"(d[2]), "+f"(d[3]), "+f"(d[4]), "+f"(d[5]), "+f"(d[6]), "+f"(d[7]), "+f"(d[8]), "+f"(d[9]), "+f"(d[10]), "+f"(d[11]), "+f"(d[12]), "+f"(d[13]), "+f"(d[14]), "+f"(d[15]), "+f"(d[16]), "+f"(d[17]), "+f"(d[18]), "+f"(d[19]), "+f"(d[20]), "+f"(d[21]), "+f"(d[22]), "+f"(d[23]), "+f"(d[24]), "+f"(d[25]), "+f"(d[26]), "+f"(d[27]), "+f"(d[28]), "+f"(d[29]), "+f"(d[30]), "+f"(d[31]), "+f"(d[32]), "+f"(d[33]), "+f"(d[34]), "+f"(d[35]), "+f"(d[36]), "+f"(d[37]), "+f"(d[38]), "+f"(d[39]), "+f"(d[40]), "+f"(d[41]), "+f"(d[42]), "+f"(d[43]), "+f"(d[44]), "+f"(d[45]), "+f"(d[46]), "+f"(d[47]), "+f"(d[48]), "+f"(d[49]), "+f"(d[50]), "+f"(d[51]), "+f"(d[52]), "+f"(d[53]), "+f"(d[54]), "+f"(d[55]), "+f"(d[56]), "+f"(d[57]), "+f"(d[58]), "+f"(d[59]), "+f"(d[60]), "+f"(d[61]), "+f"(d[62]), "+f"(d[63])
    : "r"(da), "r"(db), "r"(scale_d), "r"(enable));
}
__device__ __forceinline__ void wgmma_n112(float (&d)[56], uint32_t da, uint32_t db, int scale_d) {
  asm volatile(
    "{\n.reg .pred p;\n.reg .b64 da, db;\nsetp.ne.b32 p, %58, 0;\n"
    "mov.b64 da, {%56, 0x40000040};\nmov.b64 db, {%57, 0x40000040};\n"
    "wgmma.mma_async.sync.aligned.m64n112k16.f32.bf16.bf16 {%0, %1, %2, %3, %4, %5, %6, %7, %8, %9, %10, %11, %12, %13, %14, %15, %16, %17, %18, %19, %20, %21, %22, %23, %24, %25, %26, %27, %28, %29, %30, %31, %32, %33, %34, %35, %36, %37, %38, %39, %40, %41, %42, %43, %44, %45, %46, %47, %48, %49, %50, %51, %52, %53, %54, %55}, da, db, p, 1, 1, 0, 0;\n}\n"
    : "+f"(d[0]), "+f"(d[1]), "+f"(d[2]), "+f"(d[3]), "+f"(d[4]), "+f"(d[5]), "+f"(d[6]), "+f"(d[7]), "+f"(d[8]), "+f"(d[9]), "+f"(d[10]), "+f"(d[11]), "+f"(d[12]), "+f"(d[13]), "+f"(d[14]), "+f"(d[15]), "+f"(d[16]), "+f"(d[17]), "+f"(d[18]), "+f"(d[19]), "+f"(d[20]), "+f"(d[21]), "+f"(d[22]), "+f"(d[23]), "+f"(d[24]), "+f"(d[25]), "+f"(d[26]), "+f"(d[27]), "+f"(d[28]), "+f"(d[29]), "+f"(d[30]), "+f"(d[31]), "+f"(d[32]), "+f"(d[33]), "+f"(d[34]), "+f"(d[35]), "+f"(d[36]), "+f"(d[37]), "+f"(d[38]), "+f"(d[39]), "+f"(d[40]), "+f"(d[41]), "+f"(d[42]), "+f"(d[43]), "+f"(d[44]), "+f"(d[45]), "+f"(d[46]), "+f"(d[47]), "+f"(d[48]), "+f"(d[49]), "+f"(d[50]), "+f"(d[51]), "+f"(d[52]), "+f"(d[53]), "+f"(d[54]), "+f"(d[55])
    : "r"(da), "r"(db), "r"(scale_d));
}
__device__ __forceinline__ void wgmma_n224_tb(float (&d)[112], uint32_t da, uint32_t db, int scale_d) {
  asm volatile(
    "{\n.reg .pred p;\n.reg .b64 da, db;\nsetp.ne.b32 p, %114, 0;\n"
    "mov.b64 da, {%112, 0x40000040};\nmov.b64 db, {%113, 0x40000040};\n"
    "wgmma.mma_async.sync.aligned.m64n224k16.f32.bf16.bf16 {%0, %1, %2, %3, %4, %5, %6, %7, %8, %9, %10, %11, %12, %13, %14, %15, %16, %17, %18, %19, %20, %21, %22, %23, %24, %25, %26, %27, %28, %29, %30, %31, %32, %33, %34, %35, %36, %37, %38, %39, %40, %41, %42, %43, %44, %45, %46, %47, %48, %49, %50, %51, %52, %53, %54, %55, %56, %57, %58, %59, %60, %61, %62, %63, %64, %65, %66, %67, %68, %69, %70, %71, %72, %73, %74, %75, %76, %77, %78, %79, %80, %81, %82, %83, %84, %85, %86, %87, %88, %89, %90, %91, %92, %93, %94, %95, %96, %97, %98, %99, %100, %101, %102, %103, %104, %105, %106, %107, %108, %109, %110, %111}, da, db, p, 1, 1, 0, 1;\n}\n"
    : "+f"(d[0]), "+f"(d[1]), "+f"(d[2]), "+f"(d[3]), "+f"(d[4]), "+f"(d[5]), "+f"(d[6]), "+f"(d[7]), "+f"(d[8]), "+f"(d[9]), "+f"(d[10]), "+f"(d[11]), "+f"(d[12]), "+f"(d[13]), "+f"(d[14]), "+f"(d[15]), "+f"(d[16]), "+f"(d[17]), "+f"(d[18]), "+f"(d[19]), "+f"(d[20]), "+f"(d[21]), "+f"(d[22]), "+f"(d[23]), "+f"(d[24]), "+f"(d[25]), "+f"(d[26]), "+f"(d[27]), "+f"(d[28]), "+f"(d[29]), "+f"(d[30]), "+f"(d[31]), "+f"(d[32]), "+f"(d[33]), "+f"(d[34]), "+f"(d[35]), "+f"(d[36]), "+f"(d[37]), "+f"(d[38]), "+f"(d[39]), "+f"(d[40]), "+f"(d[41]), "+f"(d[42]), "+f"(d[43]), "+f"(d[44]), "+f"(d[45]), "+f"(d[46]), "+f"(d[47]), "+f"(d[48]), "+f"(d[49]), "+f"(d[50]), "+f"(d[51]), "+f"(d[52]), "+f"(d[53]), "+f"(d[54]), "+f"(d[55]), "+f"(d[56]), "+f"(d[57]), "+f"(d[58]), "+f"(d[59]), "+f"(d[60]), "+f"(d[61]), "+f"(d[62]), "+f"(d[63]), "+f"(d[64]), "+f"(d[65]), "+f"(d[66]), "+f"(d[67]), "+f"(d[68]), "+f"(d[69]), "+f"(d[70]), "+f"(d[71]), "+f"(d[72]), "+f"(d[73]), "+f"(d[74]), "+f"(d[75]), "+f"(d[76]), "+f"(d[77]), "+f"(d[78]), "+f"(d[79]), "+f"(d[80]), "+f"(d[81]), "+f"(d[82]), "+f"(d[83]), "+f"(d[84]), "+f"(d[85]), "+f"(d[86]), "+f"(d[87]), "+f"(d[88]), "+f"(d[89]), "+f"(d[90]), "+f"(d[91]), "+f"(d[92]), "+f"(d[93]), "+f"(d[94]), "+f"(d[95]), "+f"(d[96]), "+f"(d[97]), "+f"(d[98]), "+f"(d[99]), "+f"(d[100]), "+f"(d[101]), "+f"(d[102]), "+f"(d[103]), "+f"(d[104]), "+f"(d[105]), "+f"(d[106]), "+f"(d[107]), "+f"(d[108]), "+f"(d[109]), "+f"(d[110]), "+f"(d[111])
    : "r"(da), "r"(db), "r"(scale_d));
}

constexpr int K1_NS = 5;
constexpr int K1_A_BYTES = 7 * 16384;
constexpr int K1_B_OFF = K1_A_BYTES;
constexpr int K1_STG_OFF = K1_B_OFF + K1_NS * 16384;
constexpr int K1_BAR_OFF = K1_STG_OFF + 8 * 4096;
constexpr int K1_SMEM = K1_BAR_OFF + 256 + 1024;

struct K1Ctx {
  uint32_t sb, bar_full, rel0, rel1;
  uint32_t dA, dBk, dBn;
  bool lane0;
  const CUtensorMap* tm_hs;
  const CUtensorMap* tm_abs;
};
__device__ __forceinline__ void k1_release(const K1Ctx& c, int slot) {
  if (c.lane0) {
    asm volatile("mbarrier.arrive.shared::cluster.b64 _, [%0];" ::"r"(c.rel0 + 8 * slot) : "memory");
    asm volatile("mbarrier.arrive.shared::cluster.b64 _, [%0];" ::"r"(c.rel1 + 8 * slot) : "memory");
  }
}

__device__ __forceinline__ void k1_unit_ab(const K1Ctx& c, int warp, int lane, int mt, int j) {
  const uint32_t stg = c.sb + K1_STG_OFF + warp * 4096;
  const int wq = warp & 3;
  const int st_row = (lane & 7) + 8 * ((lane >> 3) & 1);
  const int st_chunk = lane >> 4;
  float acc[2][56];
  int slot = 0; uint32_t ph = 0;
#pragma unroll 1
  for (int kb = 0; kb < 7; kb++) {
    const int pslot = (slot == 0) ? K1_NS - 1 : slot - 1;
    mbar_wait(c.bar_full + 8 * slot, ph, 3);
    if (kb == 6) named_arrive(2, 256);
    if (kb == 0 && (threadIdx.x & 127) == 0) DBG(0, 4);
    if ((threadIdx.x & 127) == 0) DBGC(1, 46 + kb);
    wg_fence();
    const uint32_t da = c.dA + kb * 1024;
    const uint32_t db = c.dBk + slot * 1024;
#pragma unroll
    for (int k = 0; k < 4; k++) {
      wgmma_n112(acc[0], da + k * 2, db + k * 2, (kb | k) != 0);
      wgmma_n112(acc[1], da + 512 + k * 2, db + k * 2, (kb | k) != 0);
    }
    wg_commit();
    if (kb > 0) { wg_wait<1>(); k1_release(c, pslot); }
    if (++slot == K1_NS) { slot = 0; ph ^= 1; }
  }
  wg_wait<0>();
  k1_release(c, 6 % K1_NS);
  if ((threadIdx.x & 127) == 0) DBG(0, 5);
  const uint32_t sgn = (j < 4) ? 0u : 0x80008000u;
  const uint32_t sa = stg + st_row * 224 + st_chunk * 16;
  const int row0 = (j < 4 ? 0 : 2048) + mt * 128 + wq * 16;
#pragma unroll
  for (int h = 0; h < 2; h++) {
    if (h == 1) { if (c.lane0) bulk_wait_read0(); __syncwarp(); }
#pragma unroll
    for (int g = 0; g < 14; g += 2) {
      const float* a = &acc[h][4 * g];
      stmatrix_x4(sa + g * 16, pack_bf16(a[0], a[1]) ^ sgn, pack_bf16(a[2], a[3]) ^ sgn, pack_bf16(a[4], a[5]) ^ sgn, pack_bf16(a[6], a[7]) ^ sgn);
    }
    fence_async_smem();
    __syncwarp();
    if (c.lane0) { tma2d_store(c.tm_abs, stg, (j & 3) * 112, row0 + h * 64); bulk_commit(); }
  }
}

__device__ __forceinline__ void k1_unit_gu(const K1Ctx& c, int warp, int lane, int mt, int unit, int fb, int hsel) {
  const uint32_t stg = c.sb + K1_STG_OFF + warp * 4096;
  const int wq = warp & 3;
  const int full = (unit < 4);
  float acc[2][64];
  const uint32_t dA0 = c.dA + (full ? 0 : hsel * 512);
  int slot = (unit * 7) % K1_NS; uint32_t ph = ((unit * 7) / K1_NS) & 1;
  named_bar(2 + ((unit - 1) & 1), 256);
  if (full) {
#pragma unroll 1
    for (int kb = 0; kb < 7; kb++) {
      const int pslot = (slot == 0) ? K1_NS - 1 : slot - 1;
      mbar_wait(c.bar_full + 8 * slot, ph, 4);
      if (kb == 6) named_arrive(2 + (unit & 1), 256);
      if (kb == 0 && (threadIdx.x & 127) == 0) DBG(0, 4 + 3 * unit);
      wg_fence();
      const uint32_t da = dA0 + kb * 1024;
      const uint32_t db = c.dBn + slot * 1024;
#pragma unroll
      for (int k = 0; k < 4; k++) {
        wgmma_n128_tb(acc[0], da + k * 2, db + k * 128, (kb | k) != 0);
        wgmma_n128_tb(acc[1], da + 512 + k * 2, db + k * 128, (kb | k) != 0);
      }
      wg_commit();
      if (kb > 0) { wg_wait<1>(); k1_release(c, pslot); }
      if (++slot == K1_NS) { slot = 0; ph ^= 1; }
    }
  } else {
#pragma unroll 1
    for (int kb = 0; kb < 7; kb++) {
      const int pslot = (slot == 0) ? K1_NS - 1 : slot - 1;
      mbar_wait(c.bar_full + 8 * slot, ph, 5);
      if (kb == 0 && (threadIdx.x & 127) == 0) DBG(0, 4 + 3 * unit);
      wg_fence();
      const uint32_t da = dA0 + kb * 1024;
      const uint32_t db = c.dBn + slot * 1024;
#pragma unroll
      for (int k = 0; k < 4; k++) wgmma_n128_tb(acc[0], da + k * 2, db + k * 128, (kb | k) != 0);
      wg_commit();
      if (kb > 0) { wg_wait<1>(); k1_release(c, pslot); }
      if (++slot == K1_NS) { slot = 0; ph ^= 1; }
    }
  }
  wg_wait<0>();
  k1_release(c, (slot == 0) ? K1_NS - 1 : slot - 1);
  if (unit == 2) {
    if (c.lane0) { bulk_wait0(); asm volatile("fence.proxy.async;" ::: "memory"); __threadfence(); }
    named_bar(4, 128);
    if (threadIdx.x == 0) {
      const unsigned int old = atomicAdd(&g_ab_cnt, 1u);
      if ((old & 127u) == 127u) *reinterpret_cast<volatile unsigned int*>(&g_epoch) = (old >> 7) + 1;
    }
  }
  if (unit >= 3 && lane < 4) {
    asm volatile("mbarrier.arrive.shared::cluster.b64 _, [%0];" ::"r"(c.rel0 + 8 * (K1_NS + 4 + lane)) : "memory");
    asm volatile("mbarrier.arrive.shared::cluster.b64 _, [%0];" ::"r"(c.rel1 + 8 * (K1_NS + 4 + lane)) : "memory");
  }
  if ((threadIdx.x & 127) == 0) DBG(0, 5 + 3 * unit);
  const int st_row = (lane & 7) + 8 * ((lane >> 3) & 1);
  const int st_chunk = lane >> 4;
  const uint32_t sa = stg + st_row * 128;
  const int row0 = mt * 128 + (full ? 0 : hsel * 64) + wq * 16;
  if (c.lane0) bulk_wait_read0();
  __syncwarp();
#pragma unroll
  for (int h = 0; h < 2; h++) {
    if (h == 1 && !full) break;
#pragma unroll
    for (int g = 0; g < 8; g += 2) {
      uint32_t pk[4];
#pragma unroll
      for (int e = 0; e < 4; e++) {
        const int i = 4 * g + 2 * e;
        const uint32_t g2 = pack_bf16(acc[h][i], acc[h][i + 1]);
        const uint32_t u2 = pack_bf16(acc[h][32 + i], acc[h][32 + i + 1]);
        pk[e] = hmul2_bf16(pack_bf16(gelu_tanh(bf_lo(g2)), gelu_tanh(bf_hi(g2))), u2);
      }
      stmatrix_x4(sa + h * 2048 + (((g + st_chunk) ^ (st_row & 7)) * 16), pk[0], pk[1], pk[2], pk[3]);
    }
    fence_async_smem();
    __syncwarp();
    if (c.lane0) { tma2d_store(c.tm_hs, stg + h * 2048, fb * 64, row0 + h * 64); bulk_commit(); }
  }
}

constexpr int K2_NS = 4;
constexpr int K2_STAGE = 16384 + 32768;
constexpr int K2_PITCH = 464;

__device__ __forceinline__ void spin_flag(const unsigned int* flag, unsigned int target) {
  int it = 0;
  while (true) {
    unsigned int v;
    asm volatile("ld.acquire.gpu.global.u32 %0, [%1];" : "=r"(v) : "l"(flag) : "memory");
    if ((int)(v - target) >= 0) break;
    if (++it > SPIN_LIMIT) { TIMEOUT(20); break; }
  }
}

struct PfPtrs { const uint8_t* wg; const uint8_t* wu; };

__global__ void __cluster_dims__(2, 1, 1) __launch_bounds__(384, 1)
fused_kernel(const __grid_constant__ CUtensorMap tm_wr, const __grid_constant__ CUtensorMap tm_wi,
             const __grid_constant__ CUtensorMap tm_wg, const __grid_constant__ CUtensorMap tm_wu,
             const __grid_constant__ CUtensorMap tm_hs, const __grid_constant__ CUtensorMap tm_abs,
             const __grid_constant__ CUtensorMap tm_cr, const __grid_constant__ CUtensorMap tm_ci, const __grid_constant__ CUtensorMap tm_h,
             const __grid_constant__ CUtensorMap tm_ab, const __grid_constant__ CUtensorMap tm_wd,
             const __nv_bfloat16* __restrict__ x, __nv_bfloat16* __restrict__ out, const PfPtrs pf) {
  extern __shared__ uint8_t smem_raw[];
  const uint32_t sb = (s2u(smem_raw) + 1023) & ~1023u;
  const int tid = threadIdx.x, warp = tid >> 5, lane = tid & 31;
  uint32_t rank;
  asm volatile("mov.u32 %0, %%cluster_ctarank;" : "=r"(rank));
  const int cid = blockIdx.x >> 1;
  const int p = cid >> 3, j = cid & 7;
  const int mt = 2 * p + (int)rank;
  const uint32_t bar_full = sb + K1_BAR_OFF;
  const uint32_t bar_empty = bar_full + 8 * K1_NS;
  const uint32_t bar_full2 = bar_empty + 8 * K1_NS;
  const uint32_t bar_empty2 = bar_full2 + 8 * K2_NS;
  const int fb_base = 7 * (j >> 1);
  const int fb0 = fb_base + ((j & 1) ? 4 : 0);
  const int fbh = fb_base + 3;
  const int q = j & 3, n = j >> 2;
  const int tile = mt * 2 + n;
  const int nkb = (q == 0) ? 22 : (q == 3 ? 28 : 21);

  if (tid == 0) DBG(0, 0);
  if (tid == 256) {
    for (int i = 0; i < K1_NS; i++) { mbar_init(bar_full + 8 * i, 1); mbar_init(bar_empty + 8 * i, 8); }
    for (int i = 0; i < K2_NS; i++) { mbar_init(bar_full2 + 8 * i, 1); mbar_init(bar_empty2 + 8 * i, 16); }
    mbar_init(bar_empty2 + 8 * K2_NS, 1);
    asm volatile("fence.mbarrier_init.release.cluster;" ::: "memory");
    prefetch_tmap((j < 4) ? &tm_wr : &tm_wi);
    prefetch_tmap(rank ? &tm_wu : &tm_wg);
    prefetch_tmap(&tm_abs);
    prefetch_tmap(&tm_hs);
  }
  __syncwarp();
  cluster_arrive_relaxed();

  if (warp >= 8) {
    reg_dec<40>();
    cluster_wait();
    if (tid == 256) {
      const unsigned int epoch = *reinterpret_cast<volatile unsigned int*>(&g_epoch);
      {
        const CUtensorMap* tw = (j < 4) ? &tm_wr : &tm_wi;
        const CUtensorMap* tgu = rank ? &tm_wu : &tm_wg;
        int slot = 0; uint32_t ph = 0;
        int kb = 0, unit = 0;
#pragma unroll 1
        for (int s = 0; s < 35; s++) {
          if (s >= K1_NS) mbar_wait(bar_empty + 8 * slot, ph ^ 1, 2);
          const uint32_t dst = sb + K1_B_OFF + slot * 16384;
          if (unit == 0) {
            mbar_expect(bar_full + 8 * slot, 14336);
            tma2d_mc(dst + rank * 7168, tw, kb * 64, (j & 3) * 112 + rank * 56, bar_full + 8 * slot, 3);
          } else {
            const int fb = (unit == 4) ? fbh : (fb0 + unit - 1);
            mbar_expect(bar_full + 8 * slot, 16384);
            tma2d_mc(dst + rank * 8192, tgu, fb * 64, kb * 64, bar_full + 8 * slot, 3);
          }
          if (++kb == 7) { kb = 0; unit++; }
          if (++slot == K1_NS) { slot = 0; ph ^= 1; }
        }
      }
      {
        const int g0 = (q == 0) ? 0 : (q == 1 ? 22 : (q == 2 ? 43 : 64));
        const CUtensorMap* tb = (q < 3) ? &tm_ab : &tm_wd;
        prefetch_tmap(tb); prefetch_tmap((q < 3) ? ((g0 < 32) ? &tm_cr : &tm_ci) : &tm_h);
        const int kb0 = (q < 3) ? g0 : 0;
        if (q < 3) spin_flag(&g_ab_cnt, 128u * (epoch + 1)); else spin_flag(&g_h_cnt[mt], 16u * (epoch + 1));
        asm volatile("fence.proxy.async;" ::: "memory");
        DBG(1, 31);
        int slot = 0; uint32_t ph = 0;
#pragma unroll 1
        for (int s = 0; s < nkb; s++) {
          mbar_wait(bar_empty2 + 8 * slot, ph, 10);
          const uint32_t dst = sb + slot * K2_STAGE;
          const uint32_t fb = bar_full2 + 8 * slot;
          mbar_expect(fb, K2_STAGE);
          const int g = g0 + s;
          const CUtensorMap* ta = (g < 32) ? &tm_cr : (g < 64 ? &tm_ci : &tm_h);
          tma2d(dst, ta, (g & 31) * 64, mt * 128, fb);
          tma3d_mc(dst + 16384 + (2 * rank) * 8192, tb, (2 * rank) * 64, n, (kb0 + s) * 64, fb, 3);
          tma3d_mc(dst + 16384 + (2 * rank + 1) * 8192, tb, (2 * rank + 1) * 64, n, (kb0 + s) * 64, fb, 3);
          if (++slot == K2_NS) { slot = 0; ph ^= 1; }
        }
        if (q == 3) {
          const uint32_t bar_p = bar_empty2 + 8 * K2_NS;
          spin_flag(&g_flags[tile], 3u * (epoch + 1));
          asm volatile("fence.proxy.async;" ::: "memory");
          mbar_expect(bar_p, 3 * 57344);
          const uint4* pp = g_part + (size_t)tile * (3 * 14 * 256);
#pragma unroll 1
          for (int c = 0; c < 7; c++) {
            if ((c & 1) == 0) mbar_wait(bar_empty2 + 8 * (c >> 1), ph, 13);
            bulk_load(sb + c * 24576, pp + c * 1536, 24576, bar_p);
          }
          DBG(1, 30);
        }
      }
    } else if (tid == 288) {
      const int b = blockIdx.x;
      l2_prefetch(pf.wg + b * 12544, 12544);
      l2_prefetch(pf.wu + b * 12544, 12544);
    }
  } else {
    reg_inc<232>();
    const int wg = warp >> 2;
    {
      const int c = lane & 7;
      const int r0 = warp * 16 + (lane >> 3);
      const uint4* src = reinterpret_cast<const uint4*>(x + (size_t)(mt * 128 + r0) * 448) + c;
      uint4 nx[7];
#pragma unroll
      for (int b = 0; b < 7; b++)
        asm volatile("ld.global.nc.v4.u32 {%0,%1,%2,%3}, [%4];" : "=r"(nx[b].x), "=r"(nx[b].y), "=r"(nx[b].z), "=r"(nx[b].w) : "l"(src + b * 8) : "memory");
#pragma unroll
      for (int pass = 1; pass < 4; pass++) asm volatile("prefetch.global.L2 [%0];" ::"l"(src + pass * 4 * 56 + c * 7 - c) : "memory");
#pragma unroll 1
      for (int pass = 0; pass < 4; pass++) {
        uint4 v[7];
#pragma unroll
        for (int b = 0; b < 7; b++) v[b] = nx[b];
        if (pass < 3) {
          const uint4* s2 = src + (pass + 1) * 4 * 56;
#pragma unroll
          for (int b = 0; b < 7; b++)
            asm volatile("ld.global.nc.v4.u32 {%0,%1,%2,%3}, [%4];" : "=r"(nx[b].x), "=r"(nx[b].y), "=r"(nx[b].z), "=r"(nx[b].w) : "l"(s2 + b * 8) : "memory");
        }
        float s0 = 0.f, s1 = 0.f, s2v = 0.f, s3 = 0.f;
#pragma unroll
        for (int b = 0; b < 7; b++) {
          s0 += bf_lo(v[b].x) + bf_hi(v[b].x); s1 += bf_lo(v[b].y) + bf_hi(v[b].y);
          s2v += bf_lo(v[b].z) + bf_hi(v[b].z); s3 += bf_lo(v[b].w) + bf_hi(v[b].w);
        }
        float m = (s0 + s1) + (s2v + s3);
        m += __shfl_xor_sync(0xffffffffu, m, 1);
        m += __shfl_xor_sync(0xffffffffu, m, 2);
        m += __shfl_xor_sync(0xffffffffu, m, 4);
        m *= (1.0f / 448.0f);
        float q0 = 0.f, q1 = 0.f, q2 = 0.f, q3 = 0.f;
#pragma unroll
        for (int b = 0; b < 7; b++) {
          float d;
          d = bf_lo(v[b].x) - m; q0 = fmaf(d, d, q0); d = bf_hi(v[b].x) - m; q1 = fmaf(d, d, q1);
          d = bf_lo(v[b].y) - m; q2 = fmaf(d, d, q2); d = bf_hi(v[b].y) - m; q3 = fmaf(d, d, q3);
          d = bf_lo(v[b].z) - m; q0 = fmaf(d, d, q0); d = bf_hi(v[b].z) - m; q1 = fmaf(d, d, q1);
          d = bf_lo(v[b].w) - m; q2 = fmaf(d, d, q2); d = bf_hi(v[b].w) - m; q3 = fmaf(d, d, q3);
        }
        float q = (q0 + q1) + (q2 + q3);
        q += __shfl_xor_sync(0xffffffffu, q, 1);
        q += __shfl_xor_sync(0xffffffffu, q, 2);
        q += __shfl_xor_sync(0xffffffffu, q, 4);
        const float var_b = rbf(q * (1.0f / 448.0f));
        const float den = rbf(sqrtf(rbf(var_b + 1e-5f)));
        const float ri = 1.0f / den;
        const float rih = rbf(ri);
        const uint32_t rhi2 = pack_bf16(rih, rih), rlo2 = pack_bf16(ri - rih, ri - rih);
        const uint32_t m2 = pack_bf16(m, m);
        const int r = r0 + pass * 4;
        const uint32_t a0 = sb + r * 128 + ((c ^ (r & 7)) * 16);
#pragma unroll
        for (int b = 0; b < 7; b++) {
          uint32_t w4[4] = {v[b].x, v[b].y, v[b].z, v[b].w};
#pragma unroll
          for (int qq = 0; qq < 4; qq++) {
            const uint32_t dw = hsub2_bf16(w4[qq], m2);
            w4[qq] = hfma2_bf16(dw, rhi2, hmul2_bf16(dw, rlo2));
          }
          sts128(a0 + b * 16384, make_uint4(w4[0], w4[1], w4[2], w4[3]));
        }
      }
    }
    asm volatile("fence.proxy.async.shared::cta;" ::: "memory");
    named_bar(1, 256);
    cluster_wait();
    if (tid == 0) DBG(0, 3);

    uint32_t rel0, rel1;
    asm volatile("mapa.shared::cluster.u32 %0, %1, %2;" : "=r"(rel0) : "r"(bar_empty2), "r"(0));
    asm volatile("mapa.shared::cluster.u32 %0, %1, %2;" : "=r"(rel1) : "r"(bar_empty2), "r"(1));
    {
      K1Ctx c;
      c.sb = sb; c.bar_full = bar_full; c.lane0 = (lane == 0);
      c.rel0 = rel0 - 8 * (K1_NS + K2_NS); c.rel1 = rel1 - 8 * (K1_NS + K2_NS);
      c.tm_hs = &tm_hs; c.tm_abs = &tm_abs;
      c.dA = make_desc(sb, 16, 1024);
      c.dBk = make_desc(sb + K1_B_OFF, 16, 1024);
      c.dBn = make_desc(sb + K1_B_OFF, 8192, 1024);
      if (wg == 0) {
        k1_unit_ab(c, warp, lane, mt, j);
        if (tid == 0) DBG(0, 6);
      }
#pragma unroll 1
      for (int unit = 2 - wg; unit < 5; unit += 2) {
        k1_unit_gu(c, warp, lane, mt, unit, (unit == 4) ? fbh : fb0 + unit - 1, j & 1);
        if ((tid & 127) == 0) DBG(0, 6 + 3 * unit);
      }
      if (lane == 0) { bulk_wait0(); asm volatile("fence.proxy.async;" ::: "memory"); __threadfence(); }
      named_bar(4 + wg, 128);
      if ((tid & 127) == 0) atomicAdd(&g_h_cnt[mt], 1u);
    }

    float acc[112];
    const uint32_t dA0 = make_desc(sb + wg * 8192, 16, 1024);
    const uint32_t dB0 = make_desc(sb + 16384, 8192, 1024);
    int slot = 0; uint32_t ph = 0;
#pragma unroll 1
    for (int s = 0; s < nkb; s++) {
      mbar_wait(bar_full2 + 8 * slot, ph, 11);
      if (tid == 0) DBG(1, 1 + s);
      wg_fence();
      const uint32_t da = dA0 + slot * (K2_STAGE / 16);
      const uint32_t db = dB0 + slot * (K2_STAGE / 16);
#pragma unroll
      for (int k = 0; k < 4; k++) wgmma_n224_tb(acc, da + k * 2, db + k * 128, (s | k) != 0);
      wg_commit();
      if (s > 0) {
        wg_wait<1>();
        const int ps = (slot == 0) ? K2_NS - 1 : slot - 1;
        if (lane == 0) {
          asm volatile("mbarrier.arrive.shared::cluster.b64 _, [%0];" ::"r"(rel0 + 8 * ps) : "memory");
          asm volatile("mbarrier.arrive.shared::cluster.b64 _, [%0];" ::"r"(rel1 + 8 * ps) : "memory");
        }
      }
      if (++slot == K2_NS) { slot = 0; ph ^= 1; }
    }
    wg_wait<0>();
    if (tid == 0) DBG(1, 29);
    if (q < 3) {
      uint4* part = g_part + (size_t)(tile * 3 + q) * (14 * 256) + tid;
#pragma unroll
      for (int g = 0; g < 14; g++)
        part[g * 256] = make_uint4(pack_bf16(acc[8 * g], acc[8 * g + 1]), pack_bf16(acc[8 * g + 2], acc[8 * g + 3]),
                                   pack_bf16(acc[8 * g + 4], acc[8 * g + 5]), pack_bf16(acc[8 * g + 6], acc[8 * g + 7]));
      __threadfence();
      asm volatile("fence.proxy.async;" ::: "memory");
      named_bar(1, 256);
      if (tid == 0) atomicAdd(&g_flags[tile], 1u);
    } else {
      if (lane == 0) {
        asm volatile("mbarrier.arrive.shared::cluster.b64 _, [%0];" ::"r"(rel0 + 8 * (K2_NS - 1)) : "memory");
        asm volatile("mbarrier.arrive.shared::cluster.b64 _, [%0];" ::"r"(rel1 + 8 * (K2_NS - 1)) : "memory");
      }
      const uint32_t bar_p = bar_empty2 + 8 * K2_NS;
      const int lc = (lane < 28) ? lane : 27;
      const size_t gbase = (size_t)(mt * 128 + warp * 16) * 448 + n * 224 + lc * 8;
      uint4 xv[16];
#pragma unroll
      for (int t = 0; t < 16; t++) xv[t] = ldg128_cg(x + gbase + t * 448);
      uint32_t gw[56];
#pragma unroll
      for (int i = 0; i < 56; i++) {
        const uint32_t f2 = pack_bf16(acc[2 * i], acc[2 * i + 1]);
        gw[i] = pack_bf16(silu_f(bf_lo(f2)), silu_f(bf_hi(f2)));
      }
      if (tid == 0) DBG(1, 62);
      mbar_wait(bar_p, 0, 12);
      const uint32_t tb = sb + tid * 16;
#pragma unroll
      for (int g = 0; g < 14; g++) {
        const uint4 a = lds128(tb + g * 4096), b = lds128(tb + (14 + g) * 4096), cc = lds128(tb + (28 + g) * 4096);
        gw[4 * g] = hmul2_bf16(pack_bf16(bf_lo(a.x) + bf_lo(b.x) + bf_lo(cc.x), bf_hi(a.x) + bf_hi(b.x) + bf_hi(cc.x)), gw[4 * g]);
        gw[4 * g + 1] = hmul2_bf16(pack_bf16(bf_lo(a.y) + bf_lo(b.y) + bf_lo(cc.y), bf_hi(a.y) + bf_hi(b.y) + bf_hi(cc.y)), gw[4 * g + 1]);
        gw[4 * g + 2] = hmul2_bf16(pack_bf16(bf_lo(a.z) + bf_lo(b.z) + bf_lo(cc.z), bf_hi(a.z) + bf_hi(b.z) + bf_hi(cc.z)), gw[4 * g + 2]);
        gw[4 * g + 3] = hmul2_bf16(pack_bf16(bf_lo(a.w) + bf_lo(b.w) + bf_lo(cc.w), bf_hi(a.w) + bf_hi(b.w) + bf_hi(cc.w)), gw[4 * g + 3]);
      }
      named_bar(1, 256);
      const uint32_t wbase = sb + warp * 16 * K2_PITCH;
      const int st_row = (lane & 7) + 8 * ((lane >> 3) & 1);
      const uint32_t sa = wbase + st_row * K2_PITCH + (lane >> 4) * 16;
#pragma unroll
      for (int g = 0; g < 28; g += 2) stmatrix_x4(sa + g * 16, gw[2 * g], gw[2 * g + 1], gw[2 * g + 2], gw[2 * g + 3]);
      __syncwarp();
      const uint32_t lp = wbase + lc * 16;
#pragma unroll
      for (int t = 0; t < 16; t++) {
        const uint4 tv = lds128(lp + t * K2_PITCH);
        uint4 o;
        o.x = hadd2_bf16(xv[t].x, tv.x); o.y = hadd2_bf16(xv[t].y, tv.y); o.z = hadd2_bf16(xv[t].z, tv.z); o.w = hadd2_bf16(xv[t].w, tv.w);
        if (lane < 28) stg128(out + gbase + t * 448, o);
      }
    }
    if (tid == 0) DBG(1, 63);
  }
  __syncwarp();
  cluster_arrive_relaxed();
  cluster_wait();
}

typedef CUresult (*EncFn)(CUtensorMap*, CUtensorMapDataType, cuuint32_t, void*, const cuuint64_t*, const cuuint64_t*, const cuuint32_t*,
                          const cuuint32_t*, CUtensorMapInterleave, CUtensorMapSwizzle, CUtensorMapL2promotion, CUtensorMapFloatOOBfill);

void make2d(EncFn enc, CUtensorMap* tm, const void* ptr, uint64_t cols, uint64_t rows, uint32_t bc, uint32_t br, bool swz = true) {
  cuuint64_t gd[2] = {cols, rows};
  cuuint64_t gs[1] = {cols * 2};
  cuuint32_t bd[2] = {bc, br};
  cuuint32_t es[2] = {1, 1};
  enc(tm, CU_TENSOR_MAP_DATA_TYPE_BFLOAT16, 2, const_cast<void*>(ptr), gd, gs, bd, es, CU_TENSOR_MAP_INTERLEAVE_NONE,
      swz ? CU_TENSOR_MAP_SWIZZLE_128B : CU_TENSOR_MAP_SWIZZLE_NONE, CU_TENSOR_MAP_L2_PROMOTION_L2_128B, CU_TENSOR_MAP_FLOAT_OOB_FILL_NONE);
}
void make3d_half(EncFn enc, CUtensorMap* tm, const void* ptr, uint64_t rows) {
  cuuint64_t gd[3] = {224, 2, rows};
  cuuint64_t gs[2] = {448, 896};
  cuuint32_t bd[3] = {64, 1, 64};
  cuuint32_t es[3] = {1, 1, 1};
  enc(tm, CU_TENSOR_MAP_DATA_TYPE_BFLOAT16, 3, const_cast<void*>(ptr), gd, gs, bd, es, CU_TENSOR_MAP_INTERLEAVE_NONE,
      CU_TENSOR_MAP_SWIZZLE_128B, CU_TENSOR_MAP_L2_PROMOTION_L2_128B, CU_TENSOR_MAP_FLOAT_OOB_FILL_NONE);
}

struct Maps { CUtensorMap wr, wi, wg, wu, cr, ci, h, ab, wd, hs, abs; };

}

extern "C" void kernel_launch(void* const* d_in, const int* in_sizes, int n_in, void* d_out, int out_size) {
  (void)in_sizes; (void)n_in; (void)out_size;
  static Maps maps;
  static const void* cached[9] = {nullptr};
  static bool attr_done = false;
  bool same = true;
  for (int i = 0; i < 9; i++) same = same && (cached[i] == d_in[i]);
  if (!same) {
    void* fn = nullptr;
    cudaDriverEntryPointQueryResult qr;
    cudaGetDriverEntryPoint("cuTensorMapEncodeTiled", &fn, cudaEnableDefault, &qr);
    EncFn enc = (EncFn)fn;
    void *p_ab = nullptr, *p_h = nullptr;
    cudaGetSymbolAddress(&p_ab, g_ab);
    cudaGetSymbolAddress(&p_h, g_h);
    make2d(enc, &maps.cr, d_in[1], 2048, 2048, 64, 128);
    make2d(enc, &maps.ci, d_in[2], 2048, 2048, 64, 128);
    make2d(enc, &maps.wr, d_in[3], 448, 448, 64, 56);
    make2d(enc, &maps.wi, d_in[4], 448, 448, 64, 56);
    make2d(enc, &maps.wg, d_in[6], 1792, 448, 64, 64);
    make2d(enc, &maps.wu, d_in[7], 1792, 448, 64, 64);
    make3d_half(enc, &maps.wd, d_in[8], 1792);
    make2d(enc, &maps.h, p_h, 1792, 2048, 64, 128);
    make3d_half(enc, &maps.ab, p_ab, 4096);
    make2d(enc, &maps.hs, p_h, 1792, 2048, 64, 16);
    make2d(enc, &maps.abs, p_ab, 448, 4096, 112, 16, false);
    for (int i = 0; i < 9; i++) cached[i] = d_in[i];
  }
  if (!attr_done) {
    cudaFuncSetAttribute(fused_kernel, cudaFuncAttributeMaxDynamicSharedMemorySize, K1_SMEM);
    attr_done = true;
  }
  PfPtrs pf;
  pf.wg = (const uint8_t*)d_in[6]; pf.wu = (const uint8_t*)d_in[7];
  fused_kernel<<<128, 384, K1_SMEM>>>(maps.wr, maps.wi, maps.wg, maps.wu, maps.hs, maps.abs, maps.cr, maps.ci, maps.h, maps.ab, maps.wd,
                                      (const __nv_bfloat16*)d_in[0], (__nv_bfloat16*)d_out, pf);
}
```

```cpp
#include <cuda_runtime.h>
#include <cuda_bf16.h>
#include <cuda.h>
#include <stdint.h>

namespace {

__device__ __align__(1024) __nv_bfloat16 g_ab[4096 * 448];
__device__ __align__(1024) __nv_bfloat16 g_h[2048 * 1792];
__device__ uint4 g_part[32 * 3 * 14 * 256];
__device__ __align__(1024) __nv_bfloat16 g_s[2048 * 448];
__device__ unsigned int g_epoch;
__device__ unsigned int g_ab_cnt;
__device__ unsigned int g_h_cnt[16 * 4];
__device__ unsigned int g_flags[64];

#define DBG(k, i) do {} while (0)
#define DBGC(k, i) do {} while (0)

#define TIMEOUT(code) __trap()
#define SPIN_LIMIT (1 << 22)
__device__ __forceinline__ uint32_t s2u(const void* p) { return (uint32_t)__cvta_generic_to_shared(p); }
__device__ __forceinline__ void mbar_init(uint32_t b, int c) { asm volatile("mbarrier.init.shared::cta.b64 [%0], %1;" ::"r"(b), "r"(c)); }
__device__ __forceinline__ void mbar_expect(uint32_t b, uint32_t bytes) {
  asm volatile("mbarrier.arrive.expect_tx.shared::cta.b64 _, [%0], %1;" ::"r"(b), "r"(bytes) : "memory");
}
__device__ __forceinline__ void mbar_wait(uint32_t b, uint32_t ph, int code = 1) {
  uint32_t done = 0;
  int it = 0;
  while (true) {
    asm volatile("{.reg .pred p; mbarrier.try_wait.parity.shared::cta.b64 p, [%1], %2; selp.u32 %0,1,0,p;}" : "=r"(done) : "r"(b), "r"(ph) : "memory");
    if (done) break;
    if (++it > SPIN_LIMIT) { TIMEOUT(code); break; }
  }
}
__device__ __forceinline__ void mbar_arrive_cluster(uint32_t b, uint32_t cta) {
  uint32_t r;
  asm volatile("mapa.shared::cluster.u32 %0, %1, %2;" : "=r"(r) : "r"(b), "r"(cta));
  asm volatile("mbarrier.arrive.shared::cluster.b64 _, [%0];" ::"r"(r) : "memory");
}
__device__ __forceinline__ void tma2d(uint32_t dst, const CUtensorMap* m, int c0, int c1, uint32_t bar) {
  asm volatile("cp.async.bulk.tensor.2d.shared::cluster.global.mbarrier::complete_tx::bytes [%0], [%1, {%3,%4}], [%2];" ::"r"(dst), "l"(m), "r"(bar), "r"(c0), "r"(c1) : "memory");
}
__device__ __forceinline__ void tma2d_mc(uint32_t dst, const CUtensorMap* m, int c0, int c1, uint32_t bar, uint16_t mask) {
  asm volatile("cp.async.bulk.tensor.2d.shared::cluster.global.mbarrier::complete_tx::bytes.multicast::cluster [%0], [%1, {%3,%4}], [%2], %5;" ::"r"(dst), "l"(m), "r"(bar), "r"(c0), "r"(c1), "h"(mask) : "memory");
}
__device__ __forceinline__ void tma3d_mc(uint32_t dst, const CUtensorMap* m, int c0, int c1, int c2, uint32_t bar, uint16_t mask) {
  asm volatile("cp.async.bulk.tensor.3d.shared::cluster.global.mbarrier::complete_tx::bytes.multicast::cluster [%0], [%1, {%3,%4,%5}], [%2], %6;" ::"r"(dst), "l"(m), "r"(bar), "r"(c0), "r"(c1), "r"(c2), "h"(mask) : "memory");
}
__device__ __forceinline__ void tma2d_store(const CUtensorMap* m, uint32_t src, int c0, int c1) {
  asm volatile("cp.async.bulk.tensor.2d.global.shared::cta.bulk_group [%0, {%2,%3}], [%1];" ::"l"(m), "r"(src), "r"(c0), "r"(c1) : "memory");
}
__device__ __forceinline__ void bulk_load(uint32_t dst, const void* src, uint32_t bytes, uint32_t bar) {
  asm volatile("cp.async.bulk.shared::cluster.global.mbarrier::complete_tx::bytes [%0], [%1], %2, [%3];" ::"r"(dst), "l"(src), "r"(bytes), "r"(bar) : "memory");
}
__device__ __forceinline__ void tma2d_prefetch(const CUtensorMap* m, int c0, int c1) {
  asm volatile("cp.async.bulk.prefetch.tensor.2d.L2.global [%0, {%1,%2}];" ::"l"(m), "r"(c0), "r"(c1) : "memory");
}
__device__ __forceinline__ void bulk_commit() { asm volatile("cp.async.bulk.commit_group;" ::: "memory"); }
__device__ __forceinline__ void bulk_wait_read0() { asm volatile("cp.async.bulk.wait_group.read 0;" ::: "memory"); }
__device__ __forceinline__ void bulk_wait0() { asm volatile("cp.async.bulk.wait_group 0;" ::: "memory"); }
__device__ __forceinline__ void fence_async_smem() { asm volatile("fence.proxy.async.shared::cta;" ::: "memory"); }
__device__ __forceinline__ void prefetch_tmap(const CUtensorMap* m) { asm volatile("prefetch.tensormap [%0];" ::"l"(m) : "memory"); }
__device__ __forceinline__ void l2_prefetch(const void* p, uint32_t bytes) {
  asm volatile("cp.async.bulk.prefetch.L2.global [%0], %1;" ::"l"(p), "r"(bytes) : "memory");
}
__device__ __forceinline__ void cluster_arrive_relaxed() { asm volatile("barrier.cluster.arrive.relaxed.aligned;" ::: "memory"); }
__device__ __forceinline__ void cluster_wait() { asm volatile("barrier.cluster.wait.aligned;" ::: "memory"); }
__device__ __forceinline__ void wg_fence() { __syncwarp(); asm volatile("wgmma.fence.sync.aligned;" ::: "memory"); }
__device__ __forceinline__ void wg_commit() { asm volatile("wgmma.commit_group.sync.aligned;" ::: "memory"); }
template <int N> __device__ __forceinline__ void wg_wait() { __syncwarp(); asm volatile("wgmma.wait_group.sync.aligned %0;" ::"n"(N) : "memory"); }
__device__ __forceinline__ void named_bar(int id, int n) { asm volatile("bar.sync %0, %1;" ::"r"(id), "r"(n) : "memory"); }
__device__ __forceinline__ void named_arrive(int id, int n) { asm volatile("bar.arrive %0, %1;" ::"r"(id), "r"(n) : "memory"); }
template <int N> __device__ __forceinline__ void reg_inc() { asm volatile("setmaxnreg.inc.sync.aligned.u32 %0;" ::"n"(N)); }
template <int N> __device__ __forceinline__ void reg_dec() { asm volatile("setmaxnreg.dec.sync.aligned.u32 %0;" ::"n"(N)); }
__device__ __forceinline__ void pdl_wait() { asm volatile("griddepcontrol.wait;" ::: "memory"); }
__device__ __forceinline__ void pdl_launch() { asm volatile("griddepcontrol.launch_dependents;" ::: "memory"); }

__device__ __forceinline__ uint32_t make_desc(uint32_t addr, uint32_t lbo, uint32_t  ) {
  return ((addr & 0x3FFFF) >> 4) | ((lbo >> 4) << 16);
}
__device__ __forceinline__ void stmatrix_x4(uint32_t addr, uint32_t r0, uint32_t r1, uint32_t r2, uint32_t r3) {
  asm volatile("stmatrix.sync.aligned.m8n8.x4.shared.b16 [%0], {%1,%2,%3,%4};" ::"r"(addr), "r"(r0), "r"(r1), "r"(r2), "r"(r3) : "memory");
}
__device__ __forceinline__ uint4 lds128(uint32_t a) {
  uint4 v;
  asm volatile("ld.shared.v4.u32 {%0,%1,%2,%3}, [%4];" : "=r"(v.x), "=r"(v.y), "=r"(v.z), "=r"(v.w) : "r"(a) : "memory");
  return v;
}
__device__ __forceinline__ void sts128(uint32_t a, uint4 v) {
  asm volatile("st.shared.v4.u32 [%0], {%1,%2,%3,%4};" ::"r"(a), "r"(v.x), "r"(v.y), "r"(v.z), "r"(v.w) : "memory");
}
__device__ __forceinline__ void stg128(void* p, uint4 v) {
  asm volatile("st.global.v4.u32 [%0], {%1,%2,%3,%4};" ::"l"(p), "r"(v.x), "r"(v.y), "r"(v.z), "r"(v.w) : "memory");
}
__device__ __forceinline__ void cp_async16(uint32_t dst, const void* src) {
  asm volatile("cp.async.cg.shared.global [%0], [%1], 16;" ::"r"(dst), "l"(src) : "memory");
}
__device__ __forceinline__ void cp_async8(uint32_t dst, const void* src) {
  asm volatile("cp.async.ca.shared.global [%0], [%1], 8;" ::"r"(dst), "l"(src) : "memory");
}
__device__ __forceinline__ uint2 lds64(uint32_t a) {
  uint2 v;
  asm volatile("ld.shared.v2.u32 {%0,%1}, [%2];" : "=r"(v.x), "=r"(v.y) : "r"(a) : "memory");
  return v;
}
__device__ __forceinline__ void cp_async_wait_all() { asm volatile("cp.async.wait_all;" ::: "memory"); }
__device__ __forceinline__ uint32_t pack_bf16(float lo, float hi) {
  uint32_t r;
  asm("cvt.rn.bf16x2.f32 %0, %1, %2;" : "=r"(r) : "f"(hi), "f"(lo));
  return r;
}
__device__ __forceinline__ uint32_t hmul2_bf16(uint32_t a, uint32_t b) {
  uint32_t r;
  asm("mul.rn.bf16x2 %0, %1, %2;" : "=r"(r) : "r"(a), "r"(b));
  return r;
}
__device__ __forceinline__ uint32_t hsub2_bf16(uint32_t a, uint32_t b) {
  uint32_t r;
  asm("sub.rn.bf16x2 %0, %1, %2;" : "=r"(r) : "r"(a), "r"(b));
  return r;
}
__device__ __forceinline__ uint32_t hadd2_bf16(uint32_t a, uint32_t b) {
  uint32_t r;
  asm("add.rn.bf16x2 %0, %1, %2;" : "=r"(r) : "r"(a), "r"(b));
  return r;
}
__device__ __forceinline__ uint32_t hfma2_bf16(uint32_t a, uint32_t b, uint32_t c) {
  uint32_t r;
  asm("fma.rn.bf16x2 %0, %1, %2, %3;" : "=r"(r) : "r"(a), "r"(b), "r"(c));
  return r;
}
__device__ __forceinline__ bool mbar_test(uint32_t b, uint32_t ph) {
  uint32_t done;
  asm volatile("{.reg .pred p; mbarrier.test_wait.parity.shared::cta.b64 p, [%1], %2; selp.u32 %0,1,0,p;}" : "=r"(done) : "r"(b), "r"(ph) : "memory");
  return __all_sync(0xffffffffu, done != 0);
}
__device__ __forceinline__ uint4 ldg128_cg(const void* p) {
  uint4 v;
  asm volatile("ld.global.cg.v4.u32 {%0,%1,%2,%3}, [%4];" : "=r"(v.x), "=r"(v.y), "=r"(v.z), "=r"(v.w) : "l"(p) : "memory");
  return v;
}
__device__ __forceinline__ float bf_lo(uint32_t w) { return __uint_as_float(w << 16); }
__device__ __forceinline__ float bf_hi(uint32_t w) { return __uint_as_float(w & 0xffff0000u); }
__device__ __forceinline__ float rbf(float x) { return __bfloat162float(__float2bfloat16_rn(x)); }
__device__ __forceinline__ float ex2f(float x) { float r; asm("ex2.approx.ftz.f32 %0, %1;" : "=f"(r) : "f"(x)); return r; }
__device__ __forceinline__ float rcpf(float x) { float r; asm("rcp.approx.ftz.f32 %0, %1;" : "=f"(r) : "f"(x)); return r; }
__device__ __forceinline__ float tanhf_hw(float x) { float r; asm("tanh.approx.f32 %0, %1;" : "=f"(r) : "f"(x)); return r; }
__device__ __forceinline__ float gelu_tanh(float x) {
  const float c1 = 0.7978845608028654f;
  const float c2 = c1 * 0.044715f;
  const float t = tanhf_hw(x * fmaf(c2, x * x, c1));
  const float hx = 0.5f * x;
  return fmaf(hx, t, hx);
}
__device__ __forceinline__ float silu_f(float x) {
  const float hx = 0.5f * x;
  return fmaf(hx, tanhf_hw(hx), hx);
}

__device__ __forceinline__ void wgmma_n128_tb(float (&d)[64], uint32_t da, uint32_t db, int scale_d) {
  asm volatile(
    "{\n.reg .pred p;\n.reg .b64 da, db;\nsetp.ne.b32 p, %66, 0;\n"
    "mov.b64 da, {%64, 0x40000040};\nmov.b64 db, {%65, 0x40000040};\n"
    "wgmma.mma_async.sync.aligned.m64n128k16.f32.bf16.bf16 {%0, %1, %2, %3, %4, %5, %6, %7, %8, %9, %10, %11, %12, %13, %14, %15, %16, %17, %18, %19, %20, %21, %22, %23, %24, %25, %26, %27, %28, %29, %30, %31, %32, %33, %34, %35, %36, %37, %38, %39, %40, %41, %42, %43, %44, %45, %46, %47, %48, %49, %50, %51, %52, %53, %54, %55, %56, %57, %58, %59, %60, %61, %62, %63}, da, db, p, 1, 1, 0, 1;\n}\n"
    : "+f"(d[0]), "+f"(d[1]), "+f"(d[2]), "+f"(d[3]), "+f"(d[4]), "+f"(d[5]), "+f"(d[6]), "+f"(d[7]), "+f"(d[8]), "+f"(d[9]), "+f"(d[10]), "+f"(d[11]), "+f"(d[12]), "+f"(d[13]), "+f"(d[14]), "+f"(d[15]), "+f"(d[16]), "+f"(d[17]), "+f"(d[18]), "+f"(d[19]), "+f"(d[20]), "+f"(d[21]), "+f"(d[22]), "+f"(d[23]), "+f"(d[24]), "+f"(d[25]), "+f"(d[26]), "+f"(d[27]), "+f"(d[28]), "+f"(d[29]), "+f"(d[30]), "+f"(d[31]), "+f"(d[32]), "+f"(d[33]), "+f"(d[34]), "+f"(d[35]), "+f"(d[36]), "+f"(d[37]), "+f"(d[38]), "+f"(d[39]), "+f"(d[40]), "+f"(d[41]), "+f"(d[42]), "+f"(d[43]), "+f"(d[44]), "+f"(d[45]), "+f"(d[46]), "+f"(d[47]), "+f"(d[48]), "+f"(d[49]), "+f"(d[50]), "+f"(d[51]), "+f"(d[52]), "+f"(d[53]), "+f"(d[54]), "+f"(d[55]), "+f"(d[56]), "+f"(d[57]), "+f"(d[58]), "+f"(d[59]), "+f"(d[60]), "+f"(d[61]), "+f"(d[62]), "+f"(d[63])
    : "r"(da), "r"(db), "r"(scale_d));
}
__device__ __forceinline__ void wgmma_n128_tb_p(float (&d)[64], uint32_t da, uint32_t db, int scale_d, int enable) {
  asm volatile(
    "{\n.reg .pred p;\n.reg .b64 da, db;\nsetp.ne.b32 p, %66, 0;\n.reg .pred q;\nsetp.ne.b32 q, %67, 0;\n"
    "mov.b64 da, {%64, 0x40000040};\nmov.b64 db, {%65, 0x40000040};\n"
    "@q wgmma.mma_async.sync.aligned.m64n128k16.f32.bf16.bf16 {%0, %1, %2, %3, %4, %5, %6, %7, %8, %9, %10, %11, %12, %13, %14, %15, %16, %17, %18, %19, %20, %21, %22, %23, %24, %25, %26, %27, %28, %29, %30, %31, %32, %33, %34, %35, %36, %37, %38, %39, %40, %41, %42, %43, %44, %45, %46, %47, %48, %49, %50, %51, %52, %53, %54, %55, %56, %57, %58, %59, %60, %61, %62, %63}, da, db, p, 1, 1, 0, 1;\n}\n"
    : "+f"(d[0]), "+f"(d[1]), "+f"(d[2]), "+f"(d[3]), "+f"(d[4]), "+f"(d[5]), "+f"(d[6]), "+f"(d[7]), "+f"(d[8]), "+f"(d[9]), "+f"(d[10]), "+f"(d[11]), "+f"(d[12]), "+f"(d[13]), "+f"(d[14]), "+f"(d[15]), "+f"(d[16]), "+f"(d[17]), "+f"(d[18]), "+f"(d[19]), "+f"(d[20]), "+f"(d[21]), "+f"(d[22]), "+f"(d[23]), "+f"(d[24]), "+f"(d[25]), "+f"(d[26]), "+f"(d[27]), "+f"(d[28]), "+f"(d[29]), "+f"(d[30]), "+f"(d[31]), "+f"(d[32]), "+f"(d[33]), "+f"(d[34]), "+f"(d[35]), "+f"(d[36]), "+f"(d[37]), "+f"(d[38]), "+f"(d[39]), "+f"(d[40]), "+f"(d[41]), "+f"(d[42]), "+f"(d[43]), "+f"(d[44]), "+f"(d[45]), "+f"(d[46]), "+f"(d[47]), "+f"(d[48]), "+f"(d[49]), "+f"(d[50]), "+f"(d[51]), "+f"(d[52]), "+f"(d[53]), "+f"(d[54]), "+f"(d[55]), "+f"(d[56]), "+f"(d[57]), "+f"(d[58]), "+f"(d[59]), "+f"(d[60]), "+f"(d[61]), "+f"(d[62]), "+f"(d[63])
    : "r"(da), "r"(db), "r"(scale_d), "r"(enable));
}
__device__ __forceinline__ void wgmma_n112(float (&d)[56], uint32_t da, uint32_t db, int scale_d) {
  asm volatile(
    "{\n.reg .pred p;\n.reg .b64 da, db;\nsetp.ne.b32 p, %58, 0;\n"
    "mov.b64 da, {%56, 0x40000040};\nmov.b64 db, {%57, 0x40000040};\n"
    "wgmma.mma_async.sync.aligned.m64n112k16.f32.bf16.bf16 {%0, %1, %2, %3, %4, %5, %6, %7, %8, %9, %10, %11, %12, %13, %14, %15, %16, %17, %18, %19, %20, %21, %22, %23, %24, %25, %26, %27, %28, %29, %30, %31, %32, %33, %34, %35, %36, %37, %38, %39, %40, %41, %42, %43, %44, %45, %46, %47, %48, %49, %50, %51, %52, %53, %54, %55}, da, db, p, 1, 1, 0, 0;\n}\n"
    : "+f"(d[0]), "+f"(d[1]), "+f"(d[2]), "+f"(d[3]), "+f"(d[4]), "+f"(d[5]), "+f"(d[6]), "+f"(d[7]), "+f"(d[8]), "+f"(d[9]), "+f"(d[10]), "+f"(d[11]), "+f"(d[12]), "+f"(d[13]), "+f"(d[14]), "+f"(d[15]), "+f"(d[16]), "+f"(d[17]), "+f"(d[18]), "+f"(d[19]), "+f"(d[20]), "+f"(d[21]), "+f"(d[22]), "+f"(d[23]), "+f"(d[24]), "+f"(d[25]), "+f"(d[26]), "+f"(d[27]), "+f"(d[28]), "+f"(d[29]), "+f"(d[30]), "+f"(d[31]), "+f"(d[32]), "+f"(d[33]), "+f"(d[34]), "+f"(d[35]), "+f"(d[36]), "+f"(d[37]), "+f"(d[38]), "+f"(d[39]), "+f"(d[40]), "+f"(d[41]), "+f"(d[42]), "+f"(d[43]), "+f"(d[44]), "+f"(d[45]), "+f"(d[46]), "+f"(d[47]), "+f"(d[48]), "+f"(d[49]), "+f"(d[50]), "+f"(d[51]), "+f"(d[52]), "+f"(d[53]), "+f"(d[54]), "+f"(d[55])
    : "r"(da), "r"(db), "r"(scale_d));
}
__device__ __forceinline__ void wgmma_n224_tb(float (&d)[112], uint32_t da, uint32_t db, int scale_d) {
  asm volatile(
    "{\n.reg .pred p;\n.reg .b64 da, db;\nsetp.ne.b32 p, %114, 0;\n"
    "mov.b64 da, {%112, 0x40000040};\nmov.b64 db, {%113, 0x40000040};\n"
    "wgmma.mma_async.sync.aligned.m64n224k16.f32.bf16.bf16 {%0, %1, %2, %3, %4, %5, %6, %7, %8, %9, %10, %11, %12, %13, %14, %15, %16, %17, %18, %19, %20, %21, %22, %23, %24, %25, %26, %27, %28, %29, %30, %31, %32, %33, %34, %35, %36, %37, %38, %39, %40, %41, %42, %43, %44, %45, %46, %47, %48, %49, %50, %51, %52, %53, %54, %55, %56, %57, %58, %59, %60, %61, %62, %63, %64, %65, %66, %67, %68, %69, %70, %71, %72, %73, %74, %75, %76, %77, %78, %79, %80, %81, %82, %83, %84, %85, %86, %87, %88, %89, %90, %91, %92, %93, %94, %95, %96, %97, %98, %99, %100, %101, %102, %103, %104, %105, %106, %107, %108, %109, %110, %111}, da, db, p, 1, 1, 0, 1;\n}\n"
    : "+f"(d[0]), "+f"(d[1]), "+f"(d[2]), "+f"(d[3]), "+f"(d[4]), "+f"(d[5]), "+f"(d[6]), "+f"(d[7]), "+f"(d[8]), "+f"(d[9]), "+f"(d[10]), "+f"(d[11]), "+f"(d[12]), "+f"(d[13]), "+f"(d[14]), "+f"(d[15]), "+f"(d[16]), "+f"(d[17]), "+f"(d[18]), "+f"(d[19]), "+f"(d[20]), "+f"(d[21]), "+f"(d[22]), "+f"(d[23]), "+f"(d[24]), "+f"(d[25]), "+f"(d[26]), "+f"(d[27]), "+f"(d[28]), "+f"(d[29]), "+f"(d[30]), "+f"(d[31]), "+f"(d[32]), "+f"(d[33]), "+f"(d[34]), "+f"(d[35]), "+f"(d[36]), "+f"(d[37]), "+f"(d[38]), "+f"(d[39]), "+f"(d[40]), "+f"(d[41]), "+f"(d[42]), "+f"(d[43]), "+f"(d[44]), "+f"(d[45]), "+f"(d[46]), "+f"(d[47]), "+f"(d[48]), "+f"(d[49]), "+f"(d[50]), "+f"(d[51]), "+f"(d[52]), "+f"(d[53]), "+f"(d[54]), "+f"(d[55]), "+f"(d[56]), "+f"(d[57]), "+f"(d[58]), "+f"(d[59]), "+f"(d[60]), "+f"(d[61]), "+f"(d[62]), "+f"(d[63]), "+f"(d[64]), "+f"(d[65]), "+f"(d[66]), "+f"(d[67]), "+f"(d[68]), "+f"(d[69]), "+f"(d[70]), "+f"(d[71]), "+f"(d[72]), "+f"(d[73]), "+f"(d[74]), "+f"(d[75]), "+f"(d[76]), "+f"(d[77]), "+f"(d[78]), "+f"(d[79]), "+f"(d[80]), "+f"(d[81]), "+f"(d[82]), "+f"(d[83]), "+f"(d[84]), "+f"(d[85]), "+f"(d[86]), "+f"(d[87]), "+f"(d[88]), "+f"(d[89]), "+f"(d[90]), "+f"(d[91]), "+f"(d[92]), "+f"(d[93]), "+f"(d[94]), "+f"(d[95]), "+f"(d[96]), "+f"(d[97]), "+f"(d[98]), "+f"(d[99]), "+f"(d[100]), "+f"(d[101]), "+f"(d[102]), "+f"(d[103]), "+f"(d[104]), "+f"(d[105]), "+f"(d[106]), "+f"(d[107]), "+f"(d[108]), "+f"(d[109]), "+f"(d[110]), "+f"(d[111])
    : "r"(da), "r"(db), "r"(scale_d));
}

constexpr int K1_NS = 5;
constexpr int K1_A_BYTES = 7 * 16384;
constexpr int K1_B_OFF = K1_A_BYTES;
constexpr int K1_STG_OFF = K1_B_OFF + K1_NS * 16384;
constexpr int K1_BAR_OFF = K1_STG_OFF + 8 * 4096;
constexpr int K1_SMEM = K1_BAR_OFF + 256 + 1024;

struct K1Ctx {
  uint32_t sb, bar_full, rel0, rel1;
  uint32_t dA, dBk, dBn;
  bool lane0;
  const CUtensorMap* tm_hs;
  const CUtensorMap* tm_abs;
};
__device__ __forceinline__ void k1_release(const K1Ctx& c, int slot) {
  if (c.lane0) {
    asm volatile("mbarrier.arrive.shared::cluster.b64 _, [%0];" ::"r"(c.rel0 + 8 * slot) : "memory");
    asm volatile("mbarrier.arrive.shared::cluster.b64 _, [%0];" ::"r"(c.rel1 + 8 * slot) : "memory");
  }
}

__device__ __forceinline__ void k1_unit_ab(const K1Ctx& c, int warp, int lane, int mt, int j) {
  const uint32_t stg = c.sb + K1_STG_OFF + warp * 4096;
  const int wq = warp & 3;
  const int st_row = (lane & 7) + 8 * ((lane >> 3) & 1);
  const int st_chunk = lane >> 4;
  float acc[2][56];
  int slot = 0; uint32_t ph = 0;
#pragma unroll 1
  for (int kb = 0; kb < 7; kb++) {
    const int pslot = (slot == 0) ? K1_NS - 1 : slot - 1;
    mbar_wait(c.bar_full + 8 * slot, ph, 3);
    if (kb == 6) named_arrive(2, 256);
    if (kb == 0 && (threadIdx.x & 127) == 0) DBG(0, 4);
    if ((threadIdx.x & 127) == 0) DBGC(1, 46 + kb);
    wg_fence();
    const uint32_t da = c.dA + kb * 1024;
    const uint32_t db = c.dBk + slot * 1024;
#pragma unroll
    for (int k = 0; k < 4; k++) {
      wgmma_n112(acc[0], da + k * 2, db + k * 2, (kb | k) != 0);
      wgmma_n112(acc[1], da + 512 + k * 2, db + k * 2, (kb | k) != 0);
    }
    wg_commit();
    if (kb > 0) { wg_wait<1>(); k1_release(c, pslot); }
    if (++slot == K1_NS) { slot = 0; ph ^= 1; }
  }
  wg_wait<0>();
  k1_release(c, 6 % K1_NS);
  if ((threadIdx.x & 127) == 0) DBG(0, 5);
  const uint32_t sgn = (j < 4) ? 0u : 0x80008000u;
  const uint32_t sa = stg + st_row * 224 + st_chunk * 16;
  const int row0 = (j < 4 ? 0 : 2048) + mt * 128 + wq * 16;
#pragma unroll
  for (int h = 0; h < 2; h++) {
    if (h == 1) { if (c.lane0) bulk_wait_read0(); __syncwarp(); }
#pragma unroll
    for (int g = 0; g < 14; g += 2) {
      const float* a = &acc[h][4 * g];
      stmatrix_x4(sa + g * 16, pack_bf16(a[0], a[1]) ^ sgn, pack_bf16(a[2], a[3]) ^ sgn, pack_bf16(a[4], a[5]) ^ sgn, pack_bf16(a[6], a[7]) ^ sgn);
    }
    fence_async_smem();
    __syncwarp();
    if (c.lane0) { tma2d_store(c.tm_abs, stg, (j & 3) * 112, row0 + h * 64); bulk_commit(); }
  }
}

__device__ __forceinline__ void k1_unit_gu(const K1Ctx& c, int warp, int lane, int mt, int unit, int fb, int hsel) {
  const uint32_t stg = c.sb + K1_STG_OFF + warp * 4096;
  const int wq = warp & 3;
  const int full = (unit < 4);
  float acc[2][64];
  const uint32_t dA0 = c.dA + (full ? 0 : hsel * 512);
  int slot = (unit * 7) % K1_NS; uint32_t ph = ((unit * 7) / K1_NS) & 1;
  named_bar(2 + ((unit - 1) & 1), 256);
  if (full) {
#pragma unroll 1
    for (int kb = 0; kb < 7; kb++) {
      const int pslot = (slot == 0) ? K1_NS - 1 : slot - 1;
      mbar_wait(c.bar_full + 8 * slot, ph, 4);
      if (kb == 6) named_arrive(2 + (unit & 1), 256);
      if (kb == 0 && (threadIdx.x & 127) == 0) DBG(0, 4 + 3 * unit);
      wg_fence();
      const uint32_t da = dA0 + kb * 1024;
      const uint32_t db = c.dBn + slot * 1024;
#pragma unroll
      for (int k = 0; k < 4; k++) {
        wgmma_n128_tb(acc[0], da + k * 2, db + k * 128, (kb | k) != 0);
        wgmma_n128_tb(acc[1], da + 512 + k * 2, db + k * 128, (kb | k) != 0);
      }
      wg_commit();
      if (kb > 0) { wg_wait<1>(); k1_release(c, pslot); }
      if (++slot == K1_NS) { slot = 0; ph ^= 1; }
    }
  } else {
#pragma unroll 1
    for (int kb = 0; kb < 7; kb++) {
      const int pslot = (slot == 0) ? K1_NS - 1 : slot - 1;
      mbar_wait(c.bar_full + 8 * slot, ph, 5);
      if (kb == 0 && (threadIdx.x & 127) == 0) DBG(0, 4 + 3 * unit);
      wg_fence();
      const uint32_t da = dA0 + kb * 1024;
      const uint32_t db = c.dBn + slot * 1024;
#pragma unroll
      for (int k = 0; k < 4; k++) wgmma_n128_tb(acc[0], da + k * 2, db + k * 128, (kb | k) != 0);
      wg_commit();
      if (kb > 0) { wg_wait<1>(); k1_release(c, pslot); }
      if (++slot == K1_NS) { slot = 0; ph ^= 1; }
    }
  }
  wg_wait<0>();
  k1_release(c, (slot == 0) ? K1_NS - 1 : slot - 1);
  if (unit >= 2) {
    if (c.lane0) { bulk_wait0(); asm volatile("fence.proxy.async;" ::: "memory"); __threadfence(); }
    named_bar(4 + (unit & 1), 128);
    if ((threadIdx.x & 127) == 0) {
      if (unit == 2) {
        const unsigned int old = atomicAdd(&g_ab_cnt, 1u);
        if ((old & 127u) == 127u) *reinterpret_cast<volatile unsigned int*>(&g_epoch) = (old >> 7) + 1;
      } else {
        atomicAdd(&g_h_cnt[mt * 4 + unit - 3], 1u);
      }
    }
  }
  if (unit >= 3 && lane < 4) {
    asm volatile("mbarrier.arrive.shared::cluster.b64 _, [%0];" ::"r"(c.rel0 + 8 * (K1_NS + 4 + lane)) : "memory");
    asm volatile("mbarrier.arrive.shared::cluster.b64 _, [%0];" ::"r"(c.rel1 + 8 * (K1_NS + 4 + lane)) : "memory");
  }
  if ((threadIdx.x & 127) == 0) DBG(0, 5 + 3 * unit);
  const int st_row = (lane & 7) + 8 * ((lane >> 3) & 1);
  const int st_chunk = lane >> 4;
  const uint32_t sa = stg + st_row * 128;
  const int row0 = mt * 128 + (full ? 0 : hsel * 64) + wq * 16;
  if (c.lane0) bulk_wait_read0();
  __syncwarp();
#pragma unroll
  for (int h = 0; h < 2; h++) {
    if (h == 1 && !full) break;
#pragma unroll
    for (int g = 0; g < 8; g += 2) {
      uint32_t pk[4];
#pragma unroll
      for (int e = 0; e < 4; e++) {
        const int i = 4 * g + 2 * e;
        const uint32_t g2 = pack_bf16(acc[h][i], acc[h][i + 1]);
        const uint32_t u2 = pack_bf16(acc[h][32 + i], acc[h][32 + i + 1]);
        pk[e] = hmul2_bf16(pack_bf16(gelu_tanh(bf_lo(g2)), gelu_tanh(bf_hi(g2))), u2);
      }
      stmatrix_x4(sa + h * 2048 + (((g + st_chunk) ^ (st_row & 7)) * 16), pk[0], pk[1], pk[2], pk[3]);
    }
    fence_async_smem();
    __syncwarp();
    if (c.lane0) { tma2d_store(c.tm_hs, stg + h * 2048, fb * 64, row0 + h * 64); bulk_commit(); }
  }
}

constexpr int K2_NS = 4;
constexpr int K2_STAGE = 16384 + 32768;
constexpr int K2_PITCH = 464;

__device__ __forceinline__ void spin_flag(const unsigned int* flag, unsigned int target) {
  int it = 0;
  while (true) {
    unsigned int v;
    asm volatile("ld.acquire.gpu.global.u32 %0, [%1];" : "=r"(v) : "l"(flag) : "memory");
    if ((int)(v - target) >= 0) break;
    if (++it > SPIN_LIMIT) { TIMEOUT(20); break; }
  }
}

struct PfPtrs { const uint8_t* wg; const uint8_t* wu; const uint8_t* wd; };

__global__ void __cluster_dims__(2, 1, 1) __launch_bounds__(384, 1)
fused_kernel(const __grid_constant__ CUtensorMap tm_wr, const __grid_constant__ CUtensorMap tm_wi,
             const __grid_constant__ CUtensorMap tm_wg, const __grid_constant__ CUtensorMap tm_wu,
             const __grid_constant__ CUtensorMap tm_hs, const __grid_constant__ CUtensorMap tm_abs,
             const __grid_constant__ CUtensorMap tm_cr, const __grid_constant__ CUtensorMap tm_ci, const __grid_constant__ CUtensorMap tm_h,
             const __grid_constant__ CUtensorMap tm_ab, const __grid_constant__ CUtensorMap tm_wd,
             const __nv_bfloat16* __restrict__ x, __nv_bfloat16* __restrict__ out, const PfPtrs pf) {
  extern __shared__ uint8_t smem_raw[];
  const uint32_t sb = (s2u(smem_raw) + 1023) & ~1023u;
  const int tid = threadIdx.x, warp = tid >> 5, lane = tid & 31;
  uint32_t rank;
  asm volatile("mov.u32 %0, %%cluster_ctarank;" : "=r"(rank));
  const int cid = blockIdx.x >> 1;
  const int p = cid >> 3, j = cid & 7;
  const int mt = 2 * p + (int)rank;
  const uint32_t bar_full = sb + K1_BAR_OFF;
  const uint32_t bar_empty = bar_full + 8 * K1_NS;
  const uint32_t bar_full2 = bar_empty + 8 * K1_NS;
  const uint32_t bar_empty2 = bar_full2 + 8 * K2_NS;
  const int fb_base = 7 * (j >> 1);
  const int fb0 = fb_base + ((j & 1) ? 4 : 0);
  const int fbh = fb_base + 3;
  const int q = j & 3, n = j >> 2;
  const int tile = mt * 2 + n;
  const int nkb = (q == 0) ? 22 : (q == 3 ? 28 : 21);

  if (tid == 0) DBG(0, 0);
  if (tid == 256) {
    for (int i = 0; i < K1_NS; i++) { mbar_init(bar_full + 8 * i, 1); mbar_init(bar_empty + 8 * i, 8); }
    for (int i = 0; i < K2_NS; i++) { mbar_init(bar_full2 + 8 * i, 1); mbar_init(bar_empty2 + 8 * i, 16); }
    mbar_init(bar_empty2 + 8 * K2_NS, 1);
    asm volatile("fence.mbarrier_init.release.cluster;" ::: "memory");
    prefetch_tmap((j < 4) ? &tm_wr : &tm_wi);
    prefetch_tmap(rank ? &tm_wu : &tm_wg);
    prefetch_tmap(&tm_abs);
    prefetch_tmap(&tm_hs);
  }
  __syncwarp();
  cluster_arrive_relaxed();

  if (warp >= 8) {
    reg_dec<40>();
    cluster_wait();
    if (tid == 256) {
      const unsigned int epoch = *reinterpret_cast<volatile unsigned int*>(&g_epoch);
      {
        const CUtensorMap* tw = (j < 4) ? &tm_wr : &tm_wi;
        const CUtensorMap* tgu = rank ? &tm_wu : &tm_wg;
        int slot = 0; uint32_t ph = 0;
        int kb = 0, unit = 0;
#pragma unroll 1
        for (int s = 0; s < 35; s++) {
          if (s >= K1_NS) mbar_wait(bar_empty + 8 * slot, ph ^ 1, 2);
          const uint32_t dst = sb + K1_B_OFF + slot * 16384;
          if (unit == 0) {
            mbar_expect(bar_full + 8 * slot, 14336);
            tma2d_mc(dst + rank * 7168, tw, kb * 64, (j & 3) * 112 + rank * 56, bar_full + 8 * slot, 3);
          } else {
            const int fb = (unit == 4) ? fbh : (fb0 + unit - 1);
            mbar_expect(bar_full + 8 * slot, 16384);
            tma2d_mc(dst + rank * 8192, tgu, fb * 64, kb * 64, bar_full + 8 * slot, 3);
          }
          if (++kb == 7) { kb = 0; unit++; }
          if (++slot == K1_NS) { slot = 0; ph ^= 1; }
        }
      }
      {
        const int g0 = (q == 0) ? 0 : (q == 1 ? 22 : (q == 2 ? 43 : 64));
        const CUtensorMap* tb = (q < 3) ? &tm_ab : &tm_wd;
        prefetch_tmap(tb); prefetch_tmap((q < 3) ? ((g0 < 32) ? &tm_cr : &tm_ci) : &tm_h);
        const int kb0 = (q < 3) ? g0 : 0;
        if (q < 3) { spin_flag(&g_ab_cnt, 128u * (epoch + 1)); asm volatile("fence.proxy.async;" ::: "memory"); }
        DBG(1, 31);
        int slot = 0; uint32_t ph = 0;
#pragma unroll 1
        for (int s = 0; s < nkb; s++) {
          int kblk = kb0 + s;
          const CUtensorMap* ta = (kblk < 32) ? &tm_cr : &tm_ci;
          if (q == 3) {
            if ((s & 7) == 0) { spin_flag(&g_h_cnt[mt * 4 + (s >> 3)], 8u * (epoch + 1)); asm volatile("fence.proxy.async;" ::: "memory"); }
            const int i = s & 7;
            kblk = (s < 24) ? (7 * (i >> 1) + ((i & 1) ? 4 : 0) + (s >> 3)) : (7 * i + 3);
            ta = &tm_h;
          }
          mbar_wait(bar_empty2 + 8 * slot, ph, 10);
          const uint32_t dst = sb + slot * K2_STAGE;
          const uint32_t fb = bar_full2 + 8 * slot;
          mbar_expect(fb, K2_STAGE);
          tma2d(dst, ta, (kblk & 31) * 64, mt * 128, fb);
          tma3d_mc(dst + 16384 + (2 * rank) * 8192, tb, (2 * rank) * 64, n, kblk * 64, fb, 3);
          tma3d_mc(dst + 16384 + (2 * rank + 1) * 8192, tb, (2 * rank + 1) * 64, n, kblk * 64, fb, 3);
          if (++slot == K2_NS) { slot = 0; ph ^= 1; }
        }
        if (q == 3) {
          const uint32_t bar_p = bar_empty2 + 8 * K2_NS;
          spin_flag(&g_flags[tile], 3u * (epoch + 1));
          asm volatile("fence.proxy.async;" ::: "memory");
          mbar_expect(bar_p, 3 * 57344);
          const uint4* pp = g_part + (size_t)tile * (3 * 14 * 256);
#pragma unroll 1
          for (int c = 0; c < 7; c++) {
            if ((c & 1) == 0) mbar_wait(bar_empty2 + 8 * (c >> 1), ph, 13);
            bulk_load(sb + c * 24576, pp + c * 1536, 24576, bar_p);
          }
          DBG(1, 30);
        }
      }
    } else if (tid == 288) {
      const int b = blockIdx.x;
      l2_prefetch(pf.wg + b * 12544, 12544);
      l2_prefetch(pf.wu + b * 12544, 12544);
      __nanosleep(6000);
      l2_prefetch(pf.wd + b * 12544, 12544);
      if (q < 3) {
        const int g0 = (q == 0) ? 0 : (q == 1 ? 22 : 43);
#pragma unroll 1
        for (int s = 0; s < 6; s++) tma2d_prefetch((g0 + s < 32) ? &tm_cr : &tm_ci, ((g0 + s) & 31) * 64, mt * 128);
      }
    }
  } else {
    reg_inc<232>();
    const int wg = warp >> 2;
    {
      const int c = lane & 7;
      const int r0 = warp * 16 + (lane >> 3);
      const uint4* src = reinterpret_cast<const uint4*>(x + (size_t)(mt * 128 + r0) * 448) + c;
      uint4 nx[7];
#pragma unroll
      for (int b = 0; b < 7; b++)
        asm volatile("ld.global.nc.v4.u32 {%0,%1,%2,%3}, [%4];" : "=r"(nx[b].x), "=r"(nx[b].y), "=r"(nx[b].z), "=r"(nx[b].w) : "l"(src + b * 8) : "memory");
#pragma unroll
      for (int pass = 1; pass < 4; pass++) asm volatile("prefetch.global.L2 [%0];" ::"l"(src + pass * 4 * 56 + c * 7 - c) : "memory");
#pragma unroll 1
      for (int pass = 0; pass < 4; pass++) {
        uint4 v[7];
#pragma unroll
        for (int b = 0; b < 7; b++) v[b] = nx[b];
        if (pass < 3) {
          const uint4* s2 = src + (pass + 1) * 4 * 56;
#pragma unroll
          for (int b = 0; b < 7; b++)
            asm volatile("ld.global.nc.v4.u32 {%0,%1,%2,%3}, [%4];" : "=r"(nx[b].x), "=r"(nx[b].y), "=r"(nx[b].z), "=r"(nx[b].w) : "l"(s2 + b * 8) : "memory");
        }
        float s0 = 0.f, s1 = 0.f, s2v = 0.f, s3 = 0.f;
#pragma unroll
        for (int b = 0; b < 7; b++) {
          s0 += bf_lo(v[b].x) + bf_hi(v[b].x); s1 += bf_lo(v[b].y) + bf_hi(v[b].y);
          s2v += bf_lo(v[b].z) + bf_hi(v[b].z); s3 += bf_lo(v[b].w) + bf_hi(v[b].w);
        }
        float m = (s0 + s1) + (s2v + s3);
        m += __shfl_xor_sync(0xffffffffu, m, 1);
        m += __shfl_xor_sync(0xffffffffu, m, 2);
        m += __shfl_xor_sync(0xffffffffu, m, 4);
        m *= (1.0f / 448.0f);
        float q0 = 0.f, q1 = 0.f, q2 = 0.f, q3 = 0.f;
#pragma unroll
        for (int b = 0; b < 7; b++) {
          float d;
          d = bf_lo(v[b].x) - m; q0 = fmaf(d, d, q0); d = bf_hi(v[b].x) - m; q1 = fmaf(d, d, q1);
          d = bf_lo(v[b].y) - m; q2 = fmaf(d, d, q2); d = bf_hi(v[b].y) - m; q3 = fmaf(d, d, q3);
          d = bf_lo(v[b].z) - m; q0 = fmaf(d, d, q0); d = bf_hi(v[b].z) - m; q1 = fmaf(d, d, q1);
          d = bf_lo(v[b].w) - m; q2 = fmaf(d, d, q2); d = bf_hi(v[b].w) - m; q3 = fmaf(d, d, q3);
        }
        float q = (q0 + q1) + (q2 + q3);
        q += __shfl_xor_sync(0xffffffffu, q, 1);
        q += __shfl_xor_sync(0xffffffffu, q, 2);
        q += __shfl_xor_sync(0xffffffffu, q, 4);
        const float var_b = rbf(q * (1.0f / 448.0f));
        const float den = rbf(sqrtf(rbf(var_b + 1e-5f)));
        const float ri = 1.0f / den;
        const float rih = rbf(ri);
        const uint32_t rhi2 = pack_bf16(rih, rih), rlo2 = pack_bf16(ri - rih, ri - rih);
        const uint32_t m2 = pack_bf16(m, m);
        const int r = r0 + pass * 4;
        const uint32_t a0 = sb + r * 128 + ((c ^ (r & 7)) * 16);
#pragma unroll
        for (int b = 0; b < 7; b++) {
          uint32_t w4[4] = {v[b].x, v[b].y, v[b].z, v[b].w};
#pragma unroll
          for (int qq = 0; qq < 4; qq++) {
            const uint32_t dw = hsub2_bf16(w4[qq], m2);
            w4[qq] = hfma2_bf16(dw, rhi2, hmul2_bf16(dw, rlo2));
          }
          sts128(a0 + b * 16384, make_uint4(w4[0], w4[1], w4[2], w4[3]));
        }
      }
    }
    asm volatile("fence.proxy.async.shared::cta;" ::: "memory");
    named_bar(1, 256);
    cluster_wait();
    if (tid == 0) DBG(0, 3);

    uint32_t rel0, rel1;
    asm volatile("mapa.shared::cluster.u32 %0, %1, %2;" : "=r"(rel0) : "r"(bar_empty2), "r"(0));
    asm volatile("mapa.shared::cluster.u32 %0, %1, %2;" : "=r"(rel1) : "r"(bar_empty2), "r"(1));
    {
      K1Ctx c;
      c.sb = sb; c.bar_full = bar_full; c.lane0 = (lane == 0);
      c.rel0 = rel0 - 8 * (K1_NS + K2_NS); c.rel1 = rel1 - 8 * (K1_NS + K2_NS);
      c.tm_hs = &tm_hs; c.tm_abs = &tm_abs;
      c.dA = make_desc(sb, 16, 1024);
      c.dBk = make_desc(sb + K1_B_OFF, 16, 1024);
      c.dBn = make_desc(sb + K1_B_OFF, 8192, 1024);
      if (wg == 0) {
        k1_unit_ab(c, warp, lane, mt, j);
        if (tid == 0) DBG(0, 6);
      }
#pragma unroll 1
      for (int unit = 2 - wg; unit < 5; unit += 2) {
        k1_unit_gu(c, warp, lane, mt, unit, (unit == 4) ? fbh : fb0 + unit - 1, j & 1);
        if ((tid & 127) == 0) DBG(0, 6 + 3 * unit);
      }
      if (lane == 0) { bulk_wait0(); asm volatile("fence.proxy.async;" ::: "memory"); __threadfence(); }
      named_bar(4 + wg, 128);
      if ((tid & 127) == 0) atomicAdd(&g_h_cnt[mt * 4 + 3 - wg], 1u);
    }

    float acc[112];
    const uint32_t dA0 = make_desc(sb + wg * 8192, 16, 1024);
    const uint32_t dB0 = make_desc(sb + 16384, 8192, 1024);
    int slot = 0; uint32_t ph = 0;
#pragma unroll 1
    for (int s = 0; s < nkb; s++) {
      mbar_wait(bar_full2 + 8 * slot, ph, 11);
      if (tid == 0) DBG(1, 1 + s);
      wg_fence();
      const uint32_t da = dA0 + slot * (K2_STAGE / 16);
      const uint32_t db = dB0 + slot * (K2_STAGE / 16);
#pragma unroll
      for (int k = 0; k < 4; k++) wgmma_n224_tb(acc, da + k * 2, db + k * 128, (s | k) != 0);
      wg_commit();
      if (s > 0) {
        wg_wait<1>();
        const int ps = (slot == 0) ? K2_NS - 1 : slot - 1;
        if (lane == 0) {
          asm volatile("mbarrier.arrive.shared::cluster.b64 _, [%0];" ::"r"(rel0 + 8 * ps) : "memory");
          asm volatile("mbarrier.arrive.shared::cluster.b64 _, [%0];" ::"r"(rel1 + 8 * ps) : "memory");
        }
      }
      if (++slot == K2_NS) { slot = 0; ph ^= 1; }
    }
    wg_wait<0>();
    if (tid == 0) DBG(1, 29);
    if (q < 3) {
      uint4* part = g_part + (size_t)(tile * 3 + q) * (14 * 256) + tid;
#pragma unroll
      for (int g = 0; g < 14; g++)
        part[g * 256] = make_uint4(pack_bf16(acc[8 * g], acc[8 * g + 1]), pack_bf16(acc[8 * g + 2], acc[8 * g + 3]),
                                   pack_bf16(acc[8 * g + 4], acc[8 * g + 5]), pack_bf16(acc[8 * g + 6], acc[8 * g + 7]));
      __threadfence();
      asm volatile("fence.proxy.async;" ::: "memory");
      named_bar(1, 256);
      if (tid == 0) atomicAdd(&g_flags[tile], 1u);
    } else {
      if (lane == 0) {
        asm volatile("mbarrier.arrive.shared::cluster.b64 _, [%0];" ::"r"(rel0 + 8 * (K2_NS - 1)) : "memory");
        asm volatile("mbarrier.arrive.shared::cluster.b64 _, [%0];" ::"r"(rel1 + 8 * (K2_NS - 1)) : "memory");
      }
      const uint32_t bar_p = bar_empty2 + 8 * K2_NS;
      const int lc = (lane < 28) ? lane : 27;
      const size_t gbase = (size_t)(mt * 128 + warp * 16) * 448 + n * 224 + lc * 8;
      uint4 xv[16];
#pragma unroll
      for (int t = 0; t < 16; t++) xv[t] = ldg128_cg(x + gbase + t * 448);
      uint32_t gw[56];
#pragma unroll
      for (int i = 0; i < 56; i++) {
        const uint32_t f2 = pack_bf16(acc[2 * i], acc[2 * i + 1]);
        gw[i] = pack_bf16(silu_f(bf_lo(f2)), silu_f(bf_hi(f2)));
      }
      if (tid == 0) DBG(1, 62);
      mbar_wait(bar_p, 0, 12);
      const uint32_t tb = sb + tid * 16;
#pragma unroll
      for (int g = 0; g < 14; g++) {
        const uint4 a = lds128(tb + g * 4096), b = lds128(tb + (14 + g) * 4096), cc = lds128(tb + (28 + g) * 4096);
        gw[4 * g] = hmul2_bf16(pack_bf16(bf_lo(a.x) + bf_lo(b.x) + bf_lo(cc.x), bf_hi(a.x) + bf_hi(b.x) + bf_hi(cc.x)), gw[4 * g]);
        gw[4 * g + 1] = hmul2_bf16(pack_bf16(bf_lo(a.y) + bf_lo(b.y) + bf_lo(cc.y), bf_hi(a.y) + bf_hi(b.y) + bf_hi(cc.y)), gw[4 * g + 1]);
        gw[4 * g + 2] = hmul2_bf16(pack_bf16(bf_lo(a.z) + bf_lo(b.z) + bf_lo(cc.z), bf_hi(a.z) + bf_hi(b.z) + bf_hi(cc.z)), gw[4 * g + 2]);
        gw[4 * g + 3] = hmul2_bf16(pack_bf16(bf_lo(a.w) + bf_lo(b.w) + bf_lo(cc.w), bf_hi(a.w) + bf_hi(b.w) + bf_hi(cc.w)), gw[4 * g + 3]);
      }
      named_bar(1, 256);
      const uint32_t wbase = sb + warp * 16 * K2_PITCH;
      const int st_row = (lane & 7) + 8 * ((lane >> 3) & 1);
      const uint32_t sa = wbase + st_row * K2_PITCH + (lane >> 4) * 16;
#pragma unroll
      for (int g = 0; g < 28; g += 2) stmatrix_x4(sa + g * 16, gw[2 * g], gw[2 * g + 1], gw[2 * g + 2], gw[2 * g + 3]);
      __syncwarp();
      const uint32_t lp = wbase + lc * 16;
#pragma unroll
      for (int t = 0; t < 16; t++) {
        const uint4 tv = lds128(lp + t * K2_PITCH);
        uint4 o;
        o.x = hadd2_bf16(xv[t].x, tv.x); o.y = hadd2_bf16(xv[t].y, tv.y); o.z = hadd2_bf16(xv[t].z, tv.z); o.w = hadd2_bf16(xv[t].w, tv.w);
        if (lane < 28) stg128(out + gbase + t * 448, o);
      }
    }
    if (tid == 0) DBG(1, 63);
  }
  __syncwarp();
  cluster_arrive_relaxed();
  cluster_wait();
}

typedef CUresult (*EncFn)(CUtensorMap*, CUtensorMapDataType, cuuint32_t, void*, const cuuint64_t*, const cuuint64_t*, const cuuint32_t*,
                          const cuuint32_t*, CUtensorMapInterleave, CUtensorMapSwizzle, CUtensorMapL2promotion, CUtensorMapFloatOOBfill);

void make2d(EncFn enc, CUtensorMap* tm, const void* ptr, uint64_t cols, uint64_t rows, uint32_t bc, uint32_t br, bool swz = true) {
  cuuint64_t gd[2] = {cols, rows};
  cuuint64_t gs[1] = {cols * 2};
  cuuint32_t bd[2] = {bc, br};
  cuuint32_t es[2] = {1, 1};
  enc(tm, CU_TENSOR_MAP_DATA_TYPE_BFLOAT16, 2, const_cast<void*>(ptr), gd, gs, bd, es, CU_TENSOR_MAP_INTERLEAVE_NONE,
      swz ? CU_TENSOR_MAP_SWIZZLE_128B : CU_TENSOR_MAP_SWIZZLE_NONE, CU_TENSOR_MAP_L2_PROMOTION_L2_128B, CU_TENSOR_MAP_FLOAT_OOB_FILL_NONE);
}
void make3d_half(EncFn enc, CUtensorMap* tm, const void* ptr, uint64_t rows) {
  cuuint64_t gd[3] = {224, 2, rows};
  cuuint64_t gs[2] = {448, 896};
  cuuint32_t bd[3] = {64, 1, 64};
  cuuint32_t es[3] = {1, 1, 1};
  enc(tm, CU_TENSOR_MAP_DATA_TYPE_BFLOAT16, 3, const_cast<void*>(ptr), gd, gs, bd, es, CU_TENSOR_MAP_INTERLEAVE_NONE,
      CU_TENSOR_MAP_SWIZZLE_128B, CU_TENSOR_MAP_L2_PROMOTION_L2_128B, CU_TENSOR_MAP_FLOAT_OOB_FILL_NONE);
}

struct Maps { CUtensorMap wr, wi, wg, wu, cr, ci, h, ab, wd, hs, abs; };

}

extern "C" void kernel_launch(void* const* d_in, const int* in_sizes, int n_in, void* d_out, int out_size) {
  (void)in_sizes; (void)n_in; (void)out_size;
  static Maps maps;
  static const void* cached[9] = {nullptr};
  static bool attr_done = false;
  bool same = true;
  for (int i = 0; i < 9; i++) same = same && (cached[i] == d_in[i]);
  if (!same) {
    void* fn = nullptr;
    cudaDriverEntryPointQueryResult qr;
    cudaGetDriverEntryPoint("cuTensorMapEncodeTiled", &fn, cudaEnableDefault, &qr);
    EncFn enc = (EncFn)fn;
    void *p_ab = nullptr, *p_h = nullptr;
    cudaGetSymbolAddress(&p_ab, g_ab);
    cudaGetSymbolAddress(&p_h, g_h);
    make2d(enc, &maps.cr, d_in[1], 2048, 2048, 64, 128);
    make2d(enc, &maps.ci, d_in[2], 2048, 2048, 64, 128);
    make2d(enc, &maps.wr, d_in[3], 448, 448, 64, 56);
    make2d(enc, &maps.wi, d_in[4], 448, 448, 64, 56);
    make2d(enc, &maps.wg, d_in[6], 1792, 448, 64, 64);
    make2d(enc, &maps.wu, d_in[7], 1792, 448, 64, 64);
    make3d_half(enc, &maps.wd, d_in[8], 1792);
    make2d(enc, &maps.h, p_h, 1792, 2048, 64, 128);
    make3d_half(enc, &maps.ab, p_ab, 4096);
    make2d(enc, &maps.hs, p_h, 1792, 2048, 64, 16);
    make2d(enc, &maps.abs, p_ab, 448, 4096, 112, 16, false);
    for (int i = 0; i < 9; i++) cached[i] = d_in[i];
  }
  if (!attr_done) {
    cudaFuncSetAttribute(fused_kernel, cudaFuncAttributeMaxDynamicSharedMemorySize, K1_SMEM);
    attr_done = true;
  }
  PfPtrs pf;
  pf.wg = (const uint8_t*)d_in[6]; pf.wu = (const uint8_t*)d_in[7]; pf.wd = (const uint8_t*)d_in[8];
  fused_kernel<<<128, 384, K1_SMEM>>>(maps.wr, maps.wi, maps.wg, maps.wu, maps.hs, maps.abs, maps.cr, maps.ci, maps.h, maps.ab, maps.wd,
                                      (const __nv_bfloat16*)d_in[0], (__nv_bfloat16*)d_out, pf);
}
```

```cpp
#include <cuda_runtime.h>
#include <cuda_bf16.h>
#include <cuda.h>
#include <stdint.h>

namespace {

__device__ __align__(1024) __nv_bfloat16 g_ab[4096 * 448];
__device__ __align__(1024) __nv_bfloat16 g_h[2048 * 1792];
__device__ uint4 g_part[32 * 3 * 14 * 256];
__device__ __align__(1024) __nv_bfloat16 g_s[2048 * 448];
__device__ unsigned int g_epoch;
__device__ unsigned int g_ab_cnt;
__device__ unsigned int g_h_cnt[16 * 4];
__device__ unsigned int g_flags[64];

#define DBG(k, i) do {} while (0)
#define DBGC(k, i) do {} while (0)

#define TIMEOUT(code) __trap()
#define SPIN_LIMIT (1 << 22)
__device__ __forceinline__ uint32_t s2u(const void* p) { return (uint32_t)__cvta_generic_to_shared(p); }
__device__ __forceinline__ void mbar_init(uint32_t b, int c) { asm volatile("mbarrier.init.shared::cta.b64 [%0], %1;" ::"r"(b), "r"(c)); }
__device__ __forceinline__ void mbar_expect(uint32_t b, uint32_t bytes) {
  asm volatile("mbarrier.arrive.expect_tx.shared::cta.b64 _, [%0], %1;" ::"r"(b), "r"(bytes) : "memory");
}
__device__ __forceinline__ void mbar_wait(uint32_t b, uint32_t ph, int code = 1) {
  uint32_t done = 0;
  int it = 0;
  while (true) {
    asm volatile("{.reg .pred p; mbarrier.try_wait.parity.shared::cta.b64 p, [%1], %2; selp.u32 %0,1,0,p;}" : "=r"(done) : "r"(b), "r"(ph) : "memory");
    if (done) break;
    if (++it > SPIN_LIMIT) { TIMEOUT(code); break; }
  }
}
__device__ __forceinline__ void mbar_arrive_cluster(uint32_t b, uint32_t cta) {
  uint32_t r;
  asm volatile("mapa.shared::cluster.u32 %0, %1, %2;" : "=r"(r) : "r"(b), "r"(cta));
  asm volatile("mbarrier.arrive.shared::cluster.b64 _, [%0];" ::"r"(r) : "memory");
}
__device__ __forceinline__ void tma2d(uint32_t dst, const CUtensorMap* m, int c0, int c1, uint32_t bar) {
  asm volatile("cp.async.bulk.tensor.2d.shared::cluster.global.mbarrier::complete_tx::bytes [%0], [%1, {%3,%4}], [%2];" ::"r"(dst), "l"(m), "r"(bar), "r"(c0), "r"(c1) : "memory");
}
__device__ __forceinline__ void tma2d_mc(uint32_t dst, const CUtensorMap* m, int c0, int c1, uint32_t bar, uint16_t mask) {
  asm volatile("cp.async.bulk.tensor.2d.shared::cluster.global.mbarrier::complete_tx::bytes.multicast::cluster [%0], [%1, {%3,%4}], [%2], %5;" ::"r"(dst), "l"(m), "r"(bar), "r"(c0), "r"(c1), "h"(mask) : "memory");
}
__device__ __forceinline__ void tma3d_mc(uint32_t dst, const CUtensorMap* m, int c0, int c1, int c2, uint32_t bar, uint16_t mask) {
  asm volatile("cp.async.bulk.tensor.3d.shared::cluster.global.mbarrier::complete_tx::bytes.multicast::cluster [%0], [%1, {%3,%4,%5}], [%2], %6;" ::"r"(dst), "l"(m), "r"(bar), "r"(c0), "r"(c1), "r"(c2), "h"(mask) : "memory");
}
__device__ __forceinline__ void tma2d_store(const CUtensorMap* m, uint32_t src, int c0, int c1) {
  asm volatile("cp.async.bulk.tensor.2d.global.shared::cta.bulk_group [%0, {%2,%3}], [%1];" ::"l"(m), "r"(src), "r"(c0), "r"(c1) : "memory");
}
__device__ __forceinline__ void bulk_load(uint32_t dst, const void* src, uint32_t bytes, uint32_t bar) {
  asm volatile("cp.async.bulk.shared::cluster.global.mbarrier::complete_tx::bytes [%0], [%1], %2, [%3];" ::"r"(dst), "l"(src), "r"(bytes), "r"(bar) : "memory");
}
__device__ __forceinline__ void tma2d_prefetch(const CUtensorMap* m, int c0, int c1) {
  asm volatile("cp.async.bulk.prefetch.tensor.2d.L2.global [%0, {%1,%2}];" ::"l"(m), "r"(c0), "r"(c1) : "memory");
}
__device__ __forceinline__ void bulk_commit() { asm volatile("cp.async.bulk.commit_group;" ::: "memory"); }
__device__ __forceinline__ void bulk_wait_read0() { asm volatile("cp.async.bulk.wait_group.read 0;" ::: "memory"); }
__device__ __forceinline__ void bulk_wait0() { asm volatile("cp.async.bulk.wait_group 0;" ::: "memory"); }
__device__ __forceinline__ void fence_async_smem() { asm volatile("fence.proxy.async.shared::cta;" ::: "memory"); }
__device__ __forceinline__ void prefetch_tmap(const CUtensorMap* m) { asm volatile("prefetch.tensormap [%0];" ::"l"(m) : "memory"); }
__device__ __forceinline__ void l2_prefetch(const void* p, uint32_t bytes) {
  asm volatile("cp.async.bulk.prefetch.L2.global [%0], %1;" ::"l"(p), "r"(bytes) : "memory");
}
__device__ __forceinline__ void cluster_arrive_relaxed() { asm volatile("barrier.cluster.arrive.relaxed.aligned;" ::: "memory"); }
__device__ __forceinline__ void cluster_wait() { asm volatile("barrier.cluster.wait.aligned;" ::: "memory"); }
__device__ __forceinline__ void wg_fence() { __syncwarp(); asm volatile("wgmma.fence.sync.aligned;" ::: "memory"); }
__device__ __forceinline__ void wg_commit() { asm volatile("wgmma.commit_group.sync.aligned;" ::: "memory"); }
template <int N> __device__ __forceinline__ void wg_wait() { __syncwarp(); asm volatile("wgmma.wait_group.sync.aligned %0;" ::"n"(N) : "memory"); }
__device__ __forceinline__ void named_bar(int id, int n) { asm volatile("bar.sync %0, %1;" ::"r"(id), "r"(n) : "memory"); }
__device__ __forceinline__ void named_arrive(int id, int n) { asm volatile("bar.arrive %0, %1;" ::"r"(id), "r"(n) : "memory"); }
template <int N> __device__ __forceinline__ void reg_inc() { asm volatile("setmaxnreg.inc.sync.aligned.u32 %0;" ::"n"(N)); }
template <int N> __device__ __forceinline__ void reg_dec() { asm volatile("setmaxnreg.dec.sync.aligned.u32 %0;" ::"n"(N)); }
__device__ __forceinline__ void pdl_wait() { asm volatile("griddepcontrol.wait;" ::: "memory"); }
__device__ __forceinline__ void pdl_launch() { asm volatile("griddepcontrol.launch_dependents;" ::: "memory"); }

__device__ __forceinline__ uint32_t make_desc(uint32_t addr, uint32_t lbo, uint32_t  ) {
  return ((addr & 0x3FFFF) >> 4) | ((lbo >> 4) << 16);
}
__device__ __forceinline__ void stmatrix_x4(uint32_t addr, uint32_t r0, uint32_t r1, uint32_t r2, uint32_t r3) {
  asm volatile("stmatrix.sync.aligned.m8n8.x4.shared.b16 [%0], {%1,%2,%3,%4};" ::"r"(addr), "r"(r0), "r"(r1), "r"(r2), "r"(r3) : "memory");
}
__device__ __forceinline__ uint4 lds128(uint32_t a) {
  uint4 v;
  asm volatile("ld.shared.v4.u32 {%0,%1,%2,%3}, [%4];" : "=r"(v.x), "=r"(v.y), "=r"(v.z), "=r"(v.w) : "r"(a) : "memory");
  return v;
}
__device__ __forceinline__ void sts128(uint32_t a, uint4 v) {
  asm volatile("st.shared.v4.u32 [%0], {%1,%2,%3,%4};" ::"r"(a), "r"(v.x), "r"(v.y), "r"(v.z), "r"(v.w) : "memory");
}
__device__ __forceinline__ void stg128(void* p, uint4 v) {
  asm volatile("st.global.v4.u32 [%0], {%1,%2,%3,%4};" ::"l"(p), "r"(v.x), "r"(v.y), "r"(v.z), "r"(v.w) : "memory");
}
__device__ __forceinline__ void cp_async16(uint32_t dst, const void* src) {
  asm volatile("cp.async.cg.shared.global [%0], [%1], 16;" ::"r"(dst), "l"(src) : "memory");
}
__device__ __forceinline__ void cp_async8(uint32_t dst, const void* src) {
  asm volatile("cp.async.ca.shared.global [%0], [%1], 8;" ::"r"(dst), "l"(src) : "memory");
}
__device__ __forceinline__ uint2 lds64(uint32_t a) {
  uint2 v;
  asm volatile("ld.shared.v2.u32 {%0,%1}, [%2];" : "=r"(v.x), "=r"(v.y) : "r"(a) : "memory");
  return v;
}
__device__ __forceinline__ void cp_async_wait_all() { asm volatile("cp.async.wait_all;" ::: "memory"); }
__device__ __forceinline__ uint32_t pack_bf16(float lo, float hi) {
  uint32_t r;
  asm("cvt.rn.bf16x2.f32 %0, %1, %2;" : "=r"(r) : "f"(hi), "f"(lo));
  return r;
}
__device__ __forceinline__ uint32_t hmul2_bf16(uint32_t a, uint32_t b) {
  uint32_t r;
  asm("mul.rn.bf16x2 %0, %1, %2;" : "=r"(r) : "r"(a), "r"(b));
  return r;
}
__device__ __forceinline__ uint32_t hsub2_bf16(uint32_t a, uint32_t b) {
  uint32_t r;
  asm("sub.rn.bf16x2 %0, %1, %2;" : "=r"(r) : "r"(a), "r"(b));
  return r;
}
__device__ __forceinline__ uint32_t hadd2_bf16(uint32_t a, uint32_t b) {
  uint32_t r;
  asm("add.rn.bf16x2 %0, %1, %2;" : "=r"(r) : "r"(a), "r"(b));
  return r;
}
__device__ __forceinline__ uint32_t hfma2_bf16(uint32_t a, uint32_t b, uint32_t c) {
  uint32_t r;
  asm("fma.rn.bf16x2 %0, %1, %2, %3;" : "=r"(r) : "r"(a), "r"(b), "r"(c));
  return r;
}
__device__ __forceinline__ bool mbar_test(uint32_t b, uint32_t ph) {
  uint32_t done;
  asm volatile("{.reg .pred p; mbarrier.test_wait.parity.shared::cta.b64 p, [%1], %2; selp.u32 %0,1,0,p;}" : "=r"(done) : "r"(b), "r"(ph) : "memory");
  return __all_sync(0xffffffffu, done != 0);
}
__device__ __forceinline__ uint4 ldg128_cg(const void* p) {
  uint4 v;
  asm volatile("ld.global.cg.v4.u32 {%0,%1,%2,%3}, [%4];" : "=r"(v.x), "=r"(v.y), "=r"(v.z), "=r"(v.w) : "l"(p) : "memory");
  return v;
}
__device__ __forceinline__ float bf_lo(uint32_t w) { return __uint_as_float(w << 16); }
__device__ __forceinline__ float bf_hi(uint32_t w) { return __uint_as_float(w & 0xffff0000u); }
__device__ __forceinline__ float rbf(float x) { return __bfloat162float(__float2bfloat16_rn(x)); }
__device__ __forceinline__ float ex2f(float x) { float r; asm("ex2.approx.ftz.f32 %0, %1;" : "=f"(r) : "f"(x)); return r; }
__device__ __forceinline__ float rcpf(float x) { float r; asm("rcp.approx.ftz.f32 %0, %1;" : "=f"(r) : "f"(x)); return r; }
__device__ __forceinline__ float tanhf_hw(float x) { float r; asm("tanh.approx.f32 %0, %1;" : "=f"(r) : "f"(x)); return r; }
__device__ __forceinline__ float gelu_tanh(float x) {
  const float c1 = 0.7978845608028654f;
  const float c2 = c1 * 0.044715f;
  const float t = tanhf_hw(x * fmaf(c2, x * x, c1));
  const float hx = 0.5f * x;
  return fmaf(hx, t, hx);
}
__device__ __forceinline__ float silu_f(float x) {
  const float hx = 0.5f * x;
  return fmaf(hx, tanhf_hw(hx), hx);
}

__device__ __forceinline__ void wgmma_n128_tb(float (&d)[64], uint32_t da, uint32_t db, int scale_d) {
  asm volatile(
    "{\n.reg .pred p;\n.reg .b64 da, db;\nsetp.ne.b32 p, %66, 0;\n"
    "mov.b64 da, {%64, 0x40000040};\nmov.b64 db, {%65, 0x40000040};\n"
    "wgmma.mma_async.sync.aligned.m64n128k16.f32.bf16.bf16 {%0, %1, %2, %3, %4, %5, %6, %7, %8, %9, %10, %11, %12, %13, %14, %15, %16, %17, %18, %19, %20, %21, %22, %23, %24, %25, %26, %27, %28, %29, %30, %31, %32, %33, %34, %35, %36, %37, %38, %39, %40, %41, %42, %43, %44, %45, %46, %47, %48, %49, %50, %51, %52, %53, %54, %55, %56, %57, %58, %59, %60, %61, %62, %63}, da, db, p, 1, 1, 0, 1;\n}\n"
    : "+f"(d[0]), "+f"(d[1]), "+f"(d[2]), "+f"(d[3]), "+f"(d[4]), "+f"(d[5]), "+f"(d[6]), "+f"(d[7]), "+f"(d[8]), "+f"(d[9]), "+f"(d[10]), "+f"(d[11]), "+f"(d[12]), "+f"(d[13]), "+f"(d[14]), "+f"(d[15]), "+f"(d[16]), "+f"(d[17]), "+f"(d[18]), "+f"(d[19]), "+f"(d[20]), "+f"(d[21]), "+f"(d[22]), "+f"(d[23]), "+f"(d[24]), "+f"(d[25]), "+f"(d[26]), "+f"(d[27]), "+f"(d[28]), "+f"(d[29]), "+f"(d[30]), "+f"(d[31]), "+f"(d[32]), "+f"(d[33]), "+f"(d[34]), "+f"(d[35]), "+f"(d[36]), "+f"(d[37]), "+f"(d[38]), "+f"(d[39]), "+f"(d[40]), "+f"(d[41]), "+f"(d[42]), "+f"(d[43]), "+f"(d[44]), "+f"(d[45]), "+f"(d[46]), "+f"(d[47]), "+f"(d[48]), "+f"(d[49]), "+f"(d[50]), "+f"(d[51]), "+f"(d[52]), "+f"(d[53]), "+f"(d[54]), "+f"(d[55]), "+f"(d[56]), "+f"(d[57]), "+f"(d[58]), "+f"(d[59]), "+f"(d[60]), "+f"(d[61]), "+f"(d[62]), "+f"(d[63])
    : "r"(da), "r"(db), "r"(scale_d));
}
__device__ __forceinline__ void wgmma_n128_tb_p(float (&d)[64], uint32_t da, uint32_t db, int scale_d, int enable) {
  asm volatile(
    "{\n.reg .pred p;\n.reg .b64 da, db;\nsetp.ne.b32 p, %66, 0;\n.reg .pred q;\nsetp.ne.b32 q, %67, 0;\n"
    "mov.b64 da, {%64, 0x40000040};\nmov.b64 db, {%65, 0x40000040};\n"
    "@q wgmma.mma_async.sync.aligned.m64n128k16.f32.bf16.bf16 {%0, %1, %2, %3, %4, %5, %6, %7, %8, %9, %10, %11, %12, %13, %14, %15, %16, %17, %18, %19, %20, %21, %22, %23, %24, %25, %26, %27, %28, %29, %30, %31, %32, %33, %34, %35, %36, %37, %38, %39, %40, %41, %42, %43, %44, %45, %46, %47, %48, %49, %50, %51, %52, %53, %54, %55, %56, %57, %58, %59, %60, %61, %62, %63}, da, db, p, 1, 1, 0, 1;\n}\n"
    : "+f"(d[0]), "+f"(d[1]), "+f"(d[2]), "+f"(d[3]), "+f"(d[4]), "+f"(d[5]), "+f"(d[6]), "+f"(d[7]), "+f"(d[8]), "+f"(d[9]), "+f"(d[10]), "+f"(d[11]), "+f"(d[12]), "+f"(d[13]), "+f"(d[14]), "+f"(d[15]), "+f"(d[16]), "+f"(d[17]), "+f"(d[18]), "+f"(d[19]), "+f"(d[20]), "+f"(d[21]), "+f"(d[22]), "+f"(d[23]), "+f"(d[24]), "+f"(d[25]), "+f"(d[26]), "+f"(d[27]), "+f"(d[28]), "+f"(d[29]), "+f"(d[30]), "+f"(d[31]), "+f"(d[32]), "+f"(d[33]), "+f"(d[34]), "+f"(d[35]), "+f"(d[36]), "+f"(d[37]), "+f"(d[38]), "+f"(d[39]), "+f"(d[40]), "+f"(d[41]), "+f"(d[42]), "+f"(d[43]), "+f"(d[44]), "+f"(d[45]), "+f"(d[46]), "+f"(d[47]), "+f"(d[48]), "+f"(d[49]), "+f"(d[50]), "+f"(d[51]), "+f"(d[52]), "+f"(d[53]), "+f"(d[54]), "+f"(d[55]), "+f"(d[56]), "+f"(d[57]), "+f"(d[58]), "+f"(d[59]), "+f"(d[60]), "+f"(d[61]), "+f"(d[62]), "+f"(d[63])
    : "r"(da), "r"(db), "r"(scale_d), "r"(enable));
}
__device__ __forceinline__ void wgmma_n112(float (&d)[56], uint32_t da, uint32_t db, int scale_d) {
  asm volatile(
    "{\n.reg .pred p;\n.reg .b64 da, db;\nsetp.ne.b32 p, %58, 0;\n"
    "mov.b64 da, {%56, 0x40000040};\nmov.b64 db, {%57, 0x40000040};\n"
    "wgmma.mma_async.sync.aligned.m64n112k16.f32.bf16.bf16 {%0, %1, %2, %3, %4, %5, %6, %7, %8, %9, %10, %11, %12, %13, %14, %15, %16, %17, %18, %19, %20, %21, %22, %23, %24, %25, %26, %27, %28, %29, %30, %31, %32, %33, %34, %35, %36, %37, %38, %39, %40, %41, %42, %43, %44, %45, %46, %47, %48, %49, %50, %51, %52, %53, %54, %55}, da, db, p, 1, 1, 0, 0;\n}\n"
    : "+f"(d[0]), "+f"(d[1]), "+f"(d[2]), "+f"(d[3]), "+f"(d[4]), "+f"(d[5]), "+f"(d[6]), "+f"(d[7]), "+f"(d[8]), "+f"(d[9]), "+f"(d[10]), "+f"(d[11]), "+f"(d[12]), "+f"(d[13]), "+f"(d[14]), "+f"(d[15]), "+f"(d[16]), "+f"(d[17]), "+f"(d[18]), "+f"(d[19]), "+f"(d[20]), "+f"(d[21]), "+f"(d[22]), "+f"(d[23]), "+f"(d[24]), "+f"(d[25]), "+f"(d[26]), "+f"(d[27]), "+f"(d[28]), "+f"(d[29]), "+f"(d[30]), "+f"(d[31]), "+f"(d[32]), "+f"(d[33]), "+f"(d[34]), "+f"(d[35]), "+f"(d[36]), "+f"(d[37]), "+f"(d[38]), "+f"(d[39]), "+f"(d[40]), "+f"(d[41]), "+f"(d[42]), "+f"(d[43]), "+f"(d[44]), "+f"(d[45]), "+f"(d[46]), "+f"(d[47]), "+f"(d[48]), "+f"(d[49]), "+f"(d[50]), "+f"(d[51]), "+f"(d[52]), "+f"(d[53]), "+f"(d[54]), "+f"(d[55])
    : "r"(da), "r"(db), "r"(scale_d));
}
__device__ __forceinline__ void wgmma_n224_tb(float (&d)[112], uint32_t da, uint32_t db, int scale_d) {
  asm volatile(
    "{\n.reg .pred p;\n.reg .b64 da, db;\nsetp.ne.b32 p, %114, 0;\n"
    "mov.b64 da, {%112, 0x40000040};\nmov.b64 db, {%113, 0x40000040};\n"
    "wgmma.mma_async.sync.aligned.m64n224k16.f32.bf16.bf16 {%0, %1, %2, %3, %4, %5, %6, %7, %8, %9, %10, %11, %12, %13, %14, %15, %16, %17, %18, %19, %20, %21, %22, %23, %24, %25, %26, %27, %28, %29, %30, %31, %32, %33, %34, %35, %36, %37, %38, %39, %40, %41, %42, %43, %44, %45, %46, %47, %48, %49, %50, %51, %52, %53, %54, %55, %56, %57, %58, %59, %60, %61, %62, %63, %64, %65, %66, %67, %68, %69, %70, %71, %72, %73, %74, %75, %76, %77, %78, %79, %80, %81, %82, %83, %84, %85, %86, %87, %88, %89, %90, %91, %92, %93, %94, %95, %96, %97, %98, %99, %100, %101, %102, %103, %104, %105, %106, %107, %108, %109, %110, %111}, da, db, p, 1, 1, 0, 1;\n}\n"
    : "+f"(d[0]), "+f"(d[1]), "+f"(d[2]), "+f"(d[3]), "+f"(d[4]), "+f"(d[5]), "+f"(d[6]), "+f"(d[7]), "+f"(d[8]), "+f"(d[9]), "+f"(d[10]), "+f"(d[11]), "+f"(d[12]), "+f"(d[13]), "+f"(d[14]), "+f"(d[15]), "+f"(d[16]), "+f"(d[17]), "+f"(d[18]), "+f"(d[19]), "+f"(d[20]), "+f"(d[21]), "+f"(d[22]), "+f"(d[23]), "+f"(d[24]), "+f"(d[25]), "+f"(d[26]), "+f"(d[27]), "+f"(d[28]), "+f"(d[29]), "+f"(d[30]), "+f"(d[31]), "+f"(d[32]), "+f"(d[33]), "+f"(d[34]), "+f"(d[35]), "+f"(d[36]), "+f"(d[37]), "+f"(d[38]), "+f"(d[39]), "+f"(d[40]), "+f"(d[41]), "+f"(d[42]), "+f"(d[43]), "+f"(d[44]), "+f"(d[45]), "+f"(d[46]), "+f"(d[47]), "+f"(d[48]), "+f"(d[49]), "+f"(d[50]), "+f"(d[51]), "+f"(d[52]), "+f"(d[53]), "+f"(d[54]), "+f"(d[55]), "+f"(d[56]), "+f"(d[57]), "+f"(d[58]), "+f"(d[59]), "+f"(d[60]), "+f"(d[61]), "+f"(d[62]), "+f"(d[63]), "+f"(d[64]), "+f"(d[65]), "+f"(d[66]), "+f"(d[67]), "+f"(d[68]), "+f"(d[69]), "+f"(d[70]), "+f"(d[71]), "+f"(d[72]), "+f"(d[73]), "+f"(d[74]), "+f"(d[75]), "+f"(d[76]), "+f"(d[77]), "+f"(d[78]), "+f"(d[79]), "+f"(d[80]), "+f"(d[81]), "+f"(d[82]), "+f"(d[83]), "+f"(d[84]), "+f"(d[85]), "+f"(d[86]), "+f"(d[87]), "+f"(d[88]), "+f"(d[89]), "+f"(d[90]), "+f"(d[91]), "+f"(d[92]), "+f"(d[93]), "+f"(d[94]), "+f"(d[95]), "+f"(d[96]), "+f"(d[97]), "+f"(d[98]), "+f"(d[99]), "+f"(d[100]), "+f"(d[101]), "+f"(d[102]), "+f"(d[103]), "+f"(d[104]), "+f"(d[105]), "+f"(d[106]), "+f"(d[107]), "+f"(d[108]), "+f"(d[109]), "+f"(d[110]), "+f"(d[111])
    : "r"(da), "r"(db), "r"(scale_d));
}

constexpr int K1_NS = 5;
constexpr int K1_A_BYTES = 7 * 16384;
constexpr int K1_B_OFF = K1_A_BYTES;
constexpr int K1_STG_OFF = K1_B_OFF + K1_NS * 16384;
constexpr int K1_BAR_OFF = K1_STG_OFF + 8 * 4096;
constexpr int K1_SMEM = K1_BAR_OFF + 256 + 1024;

struct K1Ctx {
  uint32_t sb, bar_full, rel0, rel1;
  uint32_t dA, dBk, dBn;
  bool lane0;
  uint32_t bar_sfree;
  uint32_t sphase;
};
__device__ __forceinline__ void k1_release(const K1Ctx& c, int slot) {
  if (c.lane0) {
    asm volatile("mbarrier.arrive.shared::cluster.b64 _, [%0];" ::"r"(c.rel0 + 8 * slot) : "memory");
    asm volatile("mbarrier.arrive.shared::cluster.b64 _, [%0];" ::"r"(c.rel1 + 8 * slot) : "memory");
  }
}

__device__ __forceinline__ void k1_unit_ab(K1Ctx& c, int warp, int lane, int mt, int j) {
  const int wq = warp & 3;
  const int st_row = (lane & 7) + 8 * ((lane >> 3) & 1);
  const int st_chunk = lane >> 4;
  float acc[2][56];
  int slot = 0; uint32_t ph = 0;
#pragma unroll 1
  for (int kb = 0; kb < 7; kb++) {
    const int pslot = (slot == 0) ? K1_NS - 1 : slot - 1;
    mbar_wait(c.bar_full + 8 * slot, ph, 3);
    if (kb == 6) named_arrive(2, 256);
    if (kb == 0 && (threadIdx.x & 127) == 0) DBG(0, 4);
    if ((threadIdx.x & 127) == 0) DBGC(1, 46 + kb);
    wg_fence();
    const uint32_t da = c.dA + kb * 1024;
    const uint32_t db = c.dBk + slot * 1024;
#pragma unroll
    for (int k = 0; k < 4; k++) {
      wgmma_n112(acc[0], da + k * 2, db + k * 2, (kb | k) != 0);
      wgmma_n112(acc[1], da + 512 + k * 2, db + k * 2, (kb | k) != 0);
    }
    wg_commit();
    if (kb > 0) { wg_wait<1>(); k1_release(c, pslot); }
    if (++slot == K1_NS) { slot = 0; ph ^= 1; }
  }
  wg_wait<0>();
  k1_release(c, 6 % K1_NS);
  if ((threadIdx.x & 127) == 0) DBG(0, 5);
  const uint32_t sgn = (j < 4) ? 0u : 0x80008000u;
  const uint32_t sa = c.sb + K1_STG_OFF + (wq * 16 + st_row) * 224 + st_chunk * 16;
#pragma unroll
  for (int h = 0; h < 2; h++) {
    if (h == 1) { mbar_wait(c.bar_sfree, c.sphase, 6); c.sphase ^= 1; }
#pragma unroll
    for (int g = 0; g < 14; g += 2) {
      const float* a = &acc[h][4 * g];
      stmatrix_x4(sa + g * 16, pack_bf16(a[0], a[1]) ^ sgn, pack_bf16(a[2], a[3]) ^ sgn, pack_bf16(a[4], a[5]) ^ sgn, pack_bf16(a[6], a[7]) ^ sgn);
    }
    fence_async_smem();
    named_arrive(6, 160);
  }
}

__device__ __forceinline__ void k1_unit_gu(K1Ctx& c, int warp, int lane, int mt, int unit, int fb, int hsel) {
  const int wq = warp & 3;
  const int full = (unit < 4);
  float acc[2][64];
  const uint32_t dA0 = c.dA + (full ? 0 : hsel * 512);
  int slot = (unit * 7) % K1_NS; uint32_t ph = ((unit * 7) / K1_NS) & 1;
  named_bar(2 + ((unit - 1) & 1), 256);
  if (full) {
#pragma unroll 1
    for (int kb = 0; kb < 7; kb++) {
      const int pslot = (slot == 0) ? K1_NS - 1 : slot - 1;
      mbar_wait(c.bar_full + 8 * slot, ph, 4);
      if (kb == 6) named_arrive(2 + (unit & 1), 256);
      if (kb == 0 && (threadIdx.x & 127) == 0) DBG(0, 4 + 3 * unit);
      wg_fence();
      const uint32_t da = dA0 + kb * 1024;
      const uint32_t db = c.dBn + slot * 1024;
#pragma unroll
      for (int k = 0; k < 4; k++) {
        wgmma_n128_tb(acc[0], da + k * 2, db + k * 128, (kb | k) != 0);
        wgmma_n128_tb(acc[1], da + 512 + k * 2, db + k * 128, (kb | k) != 0);
      }
      wg_commit();
      if (kb > 0) { wg_wait<1>(); k1_release(c, pslot); }
      if (++slot == K1_NS) { slot = 0; ph ^= 1; }
    }
  } else {
#pragma unroll 1
    for (int kb = 0; kb < 7; kb++) {
      const int pslot = (slot == 0) ? K1_NS - 1 : slot - 1;
      mbar_wait(c.bar_full + 8 * slot, ph, 5);
      if (kb == 0 && (threadIdx.x & 127) == 0) DBG(0, 4 + 3 * unit);
      wg_fence();
      const uint32_t da = dA0 + kb * 1024;
      const uint32_t db = c.dBn + slot * 1024;
#pragma unroll
      for (int k = 0; k < 4; k++) wgmma_n128_tb(acc[0], da + k * 2, db + k * 128, (kb | k) != 0);
      wg_commit();
      if (kb > 0) { wg_wait<1>(); k1_release(c, pslot); }
      if (++slot == K1_NS) { slot = 0; ph ^= 1; }
    }
  }
  wg_wait<0>();
  k1_release(c, (slot == 0) ? K1_NS - 1 : slot - 1);
  if (unit >= 3 && lane < 4) {
    asm volatile("mbarrier.arrive.shared::cluster.b64 _, [%0];" ::"r"(c.rel0 + 8 * (K1_NS + 4 + lane)) : "memory");
    asm volatile("mbarrier.arrive.shared::cluster.b64 _, [%0];" ::"r"(c.rel1 + 8 * (K1_NS + 4 + lane)) : "memory");
  }
  if ((threadIdx.x & 127) == 0) DBG(0, 5 + 3 * unit);
  const int st_row = (lane & 7) + 8 * ((lane >> 3) & 1);
  const int st_chunk = lane >> 4;
  const uint32_t sa = c.sb + K1_STG_OFF + (warp >> 2) * 16384 + (wq * 16 + st_row) * 128;
  if (unit >= 2) { mbar_wait(c.bar_sfree, c.sphase, 7); c.sphase ^= 1; }
#pragma unroll
  for (int h = 0; h < 2; h++) {
    if (h == 1 && !full) break;
#pragma unroll
    for (int g = 0; g < 8; g += 2) {
      uint32_t pk[4];
#pragma unroll
      for (int e = 0; e < 4; e++) {
        const int i = 4 * g + 2 * e;
        const uint32_t g2 = pack_bf16(acc[h][i], acc[h][i + 1]);
        const uint32_t u2 = pack_bf16(acc[h][32 + i], acc[h][32 + i + 1]);
        pk[e] = hmul2_bf16(pack_bf16(gelu_tanh(bf_lo(g2)), gelu_tanh(bf_hi(g2))), u2);
      }
      stmatrix_x4(sa + h * 8192 + (((g + st_chunk) ^ (st_row & 7)) * 16), pk[0], pk[1], pk[2], pk[3]);
    }
  }
  fence_async_smem();
  named_arrive(6 + (warp >> 2), 160);
}

constexpr int K2_NS = 4;
constexpr int K2_STAGE = 16384 + 32768;
constexpr int K2_PITCH = 464;

__device__ __forceinline__ void spin_flag(const unsigned int* flag, unsigned int target) {
  int it = 0;
  while (true) {
    unsigned int v;
    asm volatile("ld.acquire.gpu.global.u32 %0, [%1];" : "=r"(v) : "l"(flag) : "memory");
    if ((int)(v - target) >= 0) break;
    if (++it > SPIN_LIMIT) { TIMEOUT(20); break; }
  }
}

struct PfPtrs { const uint8_t* wg; const uint8_t* wu; const uint8_t* wd; };

__global__ void __cluster_dims__(2, 1, 1) __launch_bounds__(384, 1)
fused_kernel(const __grid_constant__ CUtensorMap tm_wr, const __grid_constant__ CUtensorMap tm_wi,
             const __grid_constant__ CUtensorMap tm_wg, const __grid_constant__ CUtensorMap tm_wu,
             const __grid_constant__ CUtensorMap tm_hs, const __grid_constant__ CUtensorMap tm_abs,
             const __grid_constant__ CUtensorMap tm_cr, const __grid_constant__ CUtensorMap tm_ci, const __grid_constant__ CUtensorMap tm_h,
             const __grid_constant__ CUtensorMap tm_ab, const __grid_constant__ CUtensorMap tm_wd,
             const __nv_bfloat16* __restrict__ x, __nv_bfloat16* __restrict__ out, const PfPtrs pf) {
  extern __shared__ uint8_t smem_raw[];
  const uint32_t sb = (s2u(smem_raw) + 1023) & ~1023u;
  const int tid = threadIdx.x, warp = tid >> 5, lane = tid & 31;
  uint32_t rank;
  asm volatile("mov.u32 %0, %%cluster_ctarank;" : "=r"(rank));
  const int cid = blockIdx.x >> 1;
  const int p = cid >> 3, j = cid & 7;
  const int mt = 2 * p + (int)rank;
  const uint32_t bar_full = sb + K1_BAR_OFF;
  const uint32_t bar_empty = bar_full + 8 * K1_NS;
  const uint32_t bar_full2 = bar_empty + 8 * K1_NS;
  const uint32_t bar_empty2 = bar_full2 + 8 * K2_NS;
  const int fb_base = 7 * (j >> 1);
  const int fb0 = fb_base + ((j & 1) ? 4 : 0);
  const int fbh = fb_base + 3;
  const int q = j & 3, n = j >> 2;
  const int tile = mt * 2 + n;
  const int nkb = (q == 0) ? 22 : (q == 3 ? 28 : 21);

  if (tid == 0) DBG(0, 0);
  if (tid == 256) {
    for (int i = 0; i < K1_NS; i++) { mbar_init(bar_full + 8 * i, 1); mbar_init(bar_empty + 8 * i, 8); }
    for (int i = 0; i < K2_NS; i++) { mbar_init(bar_full2 + 8 * i, 1); mbar_init(bar_empty2 + 8 * i, 16); }
    mbar_init(bar_empty2 + 8 * K2_NS, 1);
    mbar_init(bar_empty2 + 8 * K2_NS + 8, 1);
    mbar_init(bar_empty2 + 8 * K2_NS + 16, 1);
    asm volatile("fence.mbarrier_init.release.cluster;" ::: "memory");
    prefetch_tmap((j < 4) ? &tm_wr : &tm_wi);
    prefetch_tmap(rank ? &tm_wu : &tm_wg);
    prefetch_tmap(&tm_abs);
    prefetch_tmap(&tm_hs);
  }
  __syncwarp();
  cluster_arrive_relaxed();

  if (warp >= 8) {
    reg_dec<40>();
    cluster_wait();
    if (tid == 256) {
      const unsigned int epoch = *reinterpret_cast<volatile unsigned int*>(&g_epoch);
      {
        const CUtensorMap* tw = (j < 4) ? &tm_wr : &tm_wi;
        const CUtensorMap* tgu = rank ? &tm_wu : &tm_wg;
        int slot = 0; uint32_t ph = 0;
        int kb = 0, unit = 0;
#pragma unroll 1
        for (int s = 0; s < 35; s++) {
          if (s >= K1_NS) mbar_wait(bar_empty + 8 * slot, ph ^ 1, 2);
          const uint32_t dst = sb + K1_B_OFF + slot * 16384;
          if (unit == 0) {
            mbar_expect(bar_full + 8 * slot, 14336);
            tma2d_mc(dst + rank * 7168, tw, kb * 64, (j & 3) * 112 + rank * 56, bar_full + 8 * slot, 3);
          } else {
            const int fb = (unit == 4) ? fbh : (fb0 + unit - 1);
            mbar_expect(bar_full + 8 * slot, 16384);
            tma2d_mc(dst + rank * 8192, tgu, fb * 64, kb * 64, bar_full + 8 * slot, 3);
          }
          if (s == 21) {
            l2_prefetch(pf.wd + blockIdx.x * 12544, 12544);
            if (q < 3) {
              const int g0 = (q == 0) ? 0 : (q == 1 ? 22 : 43);
#pragma unroll 1
              for (int i = 0; i < 6; i++) tma2d_prefetch((g0 + i < 32) ? &tm_cr : &tm_ci, ((g0 + i) & 31) * 64, mt * 128);
            }
          }
          if (++kb == 7) { kb = 0; unit++; }
          if (++slot == K1_NS) { slot = 0; ph ^= 1; }
        }
      }
      {
        const int g0 = (q == 0) ? 0 : (q == 1 ? 22 : (q == 2 ? 43 : 64));
        const CUtensorMap* tb = (q < 3) ? &tm_ab : &tm_wd;
        prefetch_tmap(tb); prefetch_tmap((q < 3) ? ((g0 < 32) ? &tm_cr : &tm_ci) : &tm_h);
        const int kb0 = (q < 3) ? g0 : 0;
        if (q < 3) { spin_flag(&g_ab_cnt, 128u * (epoch + 1)); asm volatile("fence.proxy.async;" ::: "memory"); }
        DBG(1, 31);
        int slot = 0; uint32_t ph = 0;
#pragma unroll 1
        for (int s = 0; s < nkb; s++) {
          int kblk = kb0 + s;
          const CUtensorMap* ta = (kblk < 32) ? &tm_cr : &tm_ci;
          if (q == 3) {
            if ((s & 7) == 0) { spin_flag(&g_h_cnt[mt * 4 + (s >> 3)], 8u * (epoch + 1)); asm volatile("fence.proxy.async;" ::: "memory"); }
            const int i = s & 7;
            kblk = (s < 24) ? (7 * (i >> 1) + ((i & 1) ? 4 : 0) + (s >> 3)) : (7 * i + 3);
            ta = &tm_h;
          }
          mbar_wait(bar_empty2 + 8 * slot, ph, 10);
          const uint32_t dst = sb + slot * K2_STAGE;
          const uint32_t fb = bar_full2 + 8 * slot;
          mbar_expect(fb, K2_STAGE);
          tma2d(dst, ta, (kblk & 31) * 64, mt * 128, fb);
          tma3d_mc(dst + 16384 + (2 * rank) * 8192, tb, (2 * rank) * 64, n, kblk * 64, fb, 3);
          tma3d_mc(dst + 16384 + (2 * rank + 1) * 8192, tb, (2 * rank + 1) * 64, n, kblk * 64, fb, 3);
          if (++slot == K2_NS) { slot = 0; ph ^= 1; }
        }
        if (q == 3) {
          const uint32_t bar_p = bar_empty2 + 8 * K2_NS;
          spin_flag(&g_flags[tile], 3u * (epoch + 1));
          asm volatile("fence.proxy.async;" ::: "memory");
          mbar_expect(bar_p, 3 * 57344);
          const uint4* pp = g_part + (size_t)tile * (3 * 14 * 256);
#pragma unroll 1
          for (int c = 0; c < 7; c++) {
            if ((c & 1) == 0) mbar_wait(bar_empty2 + 8 * (c >> 1), ph, 13);
            bulk_load(sb + c * 24576, pp + c * 1536, 24576, bar_p);
          }
          DBG(1, 30);
        }
      }
    } else if (warp == 9 || warp == 10) {
      const int hw = warp - 9;
      const uint32_t stg = sb + K1_STG_OFF + hw * 16384;
      const uint32_t bar_sfree = bar_empty2 + 8 * K2_NS + 8 + 8 * hw;
      if (lane == 0) {
        const int b = blockIdx.x;
        l2_prefetch((hw ? pf.wu : pf.wg) + b * 12544, 12544);
      }
#pragma unroll 1
      for (int job = 0; job < (hw ? 2 : 4); job++) {
        named_bar(6 + hw, 160);
        if (lane == 0) {
          const int unit = hw ? (1 + 2 * job) : (job < 2 ? 0 : 2 * job - 2);
          if (unit == 0) {
            tma2d_store(&tm_abs, stg, (j & 3) * 112, (j < 4 ? 0 : 2048) + mt * 128 + job * 64);
          } else {
            const int fb = (unit == 4) ? fbh : fb0 + unit - 1;
            tma2d_store(&tm_hs, stg, fb * 64, mt * 128 + ((unit == 4) ? (j & 1) * 64 : 0));
            if (unit < 4) tma2d_store(&tm_hs, stg + 8192, fb * 64, mt * 128 + 64);
          }
          bulk_commit();
          bulk_wait_read0();
          asm volatile("mbarrier.arrive.shared::cta.b64 _, [%0];" ::"r"(bar_sfree) : "memory");
          if (unit != 0 || job == 1) {
            bulk_wait0();
            asm volatile("fence.proxy.async;" ::: "memory");
            __threadfence();
            if (unit == 0) {
              const unsigned int old = atomicAdd(&g_ab_cnt, 1u);
              if ((old & 127u) == 127u) *reinterpret_cast<volatile unsigned int*>(&g_epoch) = (old >> 7) + 1;
            } else {
              atomicAdd(&g_h_cnt[mt * 4 + unit - 1], 1u);
            }
          }
        }
        __syncwarp();
      }
    }
  } else {
    reg_inc<232>();
    const int wg = warp >> 2;
    {
      const int c = lane & 7;
      const int r0 = warp * 16 + (lane >> 3);
      const uint4* src = reinterpret_cast<const uint4*>(x + (size_t)(mt * 128 + r0) * 448) + c;
      uint4 nx[7];
#pragma unroll
      for (int b = 0; b < 7; b++)
        asm volatile("ld.global.nc.v4.u32 {%0,%1,%2,%3}, [%4];" : "=r"(nx[b].x), "=r"(nx[b].y), "=r"(nx[b].z), "=r"(nx[b].w) : "l"(src + b * 8) : "memory");
#pragma unroll
      for (int pass = 1; pass < 4; pass++) asm volatile("prefetch.global.L2 [%0];" ::"l"(src + pass * 4 * 56 + c * 7 - c) : "memory");
#pragma unroll 1
      for (int pass = 0; pass < 4; pass++) {
        uint4 v[7];
#pragma unroll
        for (int b = 0; b < 7; b++) v[b] = nx[b];
        if (pass < 3) {
          const uint4* s2 = src + (pass + 1) * 4 * 56;
#pragma unroll
          for (int b = 0; b < 7; b++)
            asm volatile("ld.global.nc.v4.u32 {%0,%1,%2,%3}, [%4];" : "=r"(nx[b].x), "=r"(nx[b].y), "=r"(nx[b].z), "=r"(nx[b].w) : "l"(s2 + b * 8) : "memory");
        }
        float s0 = 0.f, s1 = 0.f, s2v = 0.f, s3 = 0.f;
#pragma unroll
        for (int b = 0; b < 7; b++) {
          s0 += bf_lo(v[b].x) + bf_hi(v[b].x); s1 += bf_lo(v[b].y) + bf_hi(v[b].y);
          s2v += bf_lo(v[b].z) + bf_hi(v[b].z); s3 += bf_lo(v[b].w) + bf_hi(v[b].w);
        }
        float m = (s0 + s1) + (s2v + s3);
        m += __shfl_xor_sync(0xffffffffu, m, 1);
        m += __shfl_xor_sync(0xffffffffu, m, 2);
        m += __shfl_xor_sync(0xffffffffu, m, 4);
        m *= (1.0f / 448.0f);
        float q0 = 0.f, q1 = 0.f, q2 = 0.f, q3 = 0.f;
#pragma unroll
        for (int b = 0; b < 7; b++) {
          float d;
          d = bf_lo(v[b].x) - m; q0 = fmaf(d, d, q0); d = bf_hi(v[b].x) - m; q1 = fmaf(d, d, q1);
          d = bf_lo(v[b].y) - m; q2 = fmaf(d, d, q2); d = bf_hi(v[b].y) - m; q3 = fmaf(d, d, q3);
          d = bf_lo(v[b].z) - m; q0 = fmaf(d, d, q0); d = bf_hi(v[b].z) - m; q1 = fmaf(d, d, q1);
          d = bf_lo(v[b].w) - m; q2 = fmaf(d, d, q2); d = bf_hi(v[b].w) - m; q3 = fmaf(d, d, q3);
        }
        float q = (q0 + q1) + (q2 + q3);
        q += __shfl_xor_sync(0xffffffffu, q, 1);
        q += __shfl_xor_sync(0xffffffffu, q, 2);
        q += __shfl_xor_sync(0xffffffffu, q, 4);
        const float var_b = rbf(q * (1.0f / 448.0f));
        const float den = rbf(sqrtf(rbf(var_b + 1e-5f)));
        const float ri = 1.0f / den;
        const float rih = rbf(ri);
        const uint32_t rhi2 = pack_bf16(rih, rih), rlo2 = pack_bf16(ri - rih, ri - rih);
        const uint32_t m2 = pack_bf16(m, m);
        const int r = r0 + pass * 4;
        const uint32_t a0 = sb + r * 128 + ((c ^ (r & 7)) * 16);
#pragma unroll
        for (int b = 0; b < 7; b++) {
          uint32_t w4[4] = {v[b].x, v[b].y, v[b].z, v[b].w};
#pragma unroll
          for (int qq = 0; qq < 4; qq++) {
            const uint32_t dw = hsub2_bf16(w4[qq], m2);
            w4[qq] = hfma2_bf16(dw, rhi2, hmul2_bf16(dw, rlo2));
          }
          sts128(a0 + b * 16384, make_uint4(w4[0], w4[1], w4[2], w4[3]));
        }
      }
    }
    asm volatile("fence.proxy.async.shared::cta;" ::: "memory");
    named_bar(1, 256);
    cluster_wait();
    if (tid == 0) DBG(0, 3);

    uint32_t rel0, rel1;
    asm volatile("mapa.shared::cluster.u32 %0, %1, %2;" : "=r"(rel0) : "r"(bar_empty2), "r"(0));
    asm volatile("mapa.shared::cluster.u32 %0, %1, %2;" : "=r"(rel1) : "r"(bar_empty2), "r"(1));
    {
      K1Ctx c;
      c.sb = sb; c.bar_full = bar_full; c.lane0 = (lane == 0);
      c.rel0 = rel0 - 8 * (K1_NS + K2_NS); c.rel1 = rel1 - 8 * (K1_NS + K2_NS);
      c.bar_sfree = bar_empty2 + 8 * K2_NS + 8 + 8 * wg; c.sphase = 0;
      c.dA = make_desc(sb, 16, 1024);
      c.dBk = make_desc(sb + K1_B_OFF, 16, 1024);
      c.dBn = make_desc(sb + K1_B_OFF, 8192, 1024);
      if (wg == 0) {
        k1_unit_ab(c, warp, lane, mt, j);
        if (tid == 0) DBG(0, 6);
      }
#pragma unroll 1
      for (int unit = 2 - wg; unit < 5; unit += 2) {
        k1_unit_gu(c, warp, lane, mt, unit, (unit == 4) ? fbh : fb0 + unit - 1, j & 1);
        if ((tid & 127) == 0) DBG(0, 6 + 3 * unit);
      }
    }

    float acc[112];
    const uint32_t dA0 = make_desc(sb + wg * 8192, 16, 1024);
    const uint32_t dB0 = make_desc(sb + 16384, 8192, 1024);
    int slot = 0; uint32_t ph = 0;
#pragma unroll 1
    for (int s = 0; s < nkb; s++) {
      mbar_wait(bar_full2 + 8 * slot, ph, 11);
      if (tid == 0) DBG(1, 1 + s);
      wg_fence();
      const uint32_t da = dA0 + slot * (K2_STAGE / 16);
      const uint32_t db = dB0 + slot * (K2_STAGE / 16);
#pragma unroll
      for (int k = 0; k < 4; k++) wgmma_n224_tb(acc, da + k * 2, db + k * 128, (s | k) != 0);
      wg_commit();
      if (s > 0) {
        wg_wait<1>();
        const int ps = (slot == 0) ? K2_NS - 1 : slot - 1;
        if (lane == 0) {
          asm volatile("mbarrier.arrive.shared::cluster.b64 _, [%0];" ::"r"(rel0 + 8 * ps) : "memory");
          asm volatile("mbarrier.arrive.shared::cluster.b64 _, [%0];" ::"r"(rel1 + 8 * ps) : "memory");
        }
      }
      if (++slot == K2_NS) { slot = 0; ph ^= 1; }
    }
    wg_wait<0>();
    if (tid == 0) DBG(1, 29);
    if (q < 3) {
      uint4* part = g_part + (size_t)(tile * 3 + q) * (14 * 256) + tid;
#pragma unroll
      for (int g = 0; g < 14; g++)
        part[g * 256] = make_uint4(pack_bf16(acc[8 * g], acc[8 * g + 1]), pack_bf16(acc[8 * g + 2], acc[8 * g + 3]),
                                   pack_bf16(acc[8 * g + 4], acc[8 * g + 5]), pack_bf16(acc[8 * g + 6], acc[8 * g + 7]));
      __threadfence();
      asm volatile("fence.proxy.async;" ::: "memory");
      named_bar(1, 256);
      if (tid == 0) atomicAdd(&g_flags[tile], 1u);
    } else {
      if (lane == 0) {
        asm volatile("mbarrier.arrive.shared::cluster.b64 _, [%0];" ::"r"(rel0 + 8 * (K2_NS - 1)) : "memory");
        asm volatile("mbarrier.arrive.shared::cluster.b64 _, [%0];" ::"r"(rel1 + 8 * (K2_NS - 1)) : "memory");
      }
      const uint32_t bar_p = bar_empty2 + 8 * K2_NS;
      const int lc = (lane < 28) ? lane : 27;
      const size_t gbase = (size_t)(mt * 128 + warp * 16) * 448 + n * 224 + lc * 8;
      uint4 xv[16];
#pragma unroll
      for (int t = 0; t < 16; t++) xv[t] = ldg128_cg(x + gbase + t * 448);
      uint32_t gw[56];
#pragma unroll
      for (int i = 0; i < 56; i++) {
        const uint32_t f2 = pack_bf16(acc[2 * i], acc[2 * i + 1]);
        gw[i] = pack_bf16(silu_f(bf_lo(f2)), silu_f(bf_hi(f2)));
      }
      if (tid == 0) DBG(1, 62);
      mbar_wait(bar_p, 0, 12);
      const uint32_t tb = sb + tid * 16;
#pragma unroll
      for (int g = 0; g < 14; g++) {
        const uint4 a = lds128(tb + g * 4096), b = lds128(tb + (14 + g) * 4096), cc = lds128(tb + (28 + g) * 4096);
        gw[4 * g] = hmul2_bf16(pack_bf16(bf_lo(a.x) + bf_lo(b.x) + bf_lo(cc.x), bf_hi(a.x) + bf_hi(b.x) + bf_hi(cc.x)), gw[4 * g]);
        gw[4 * g + 1] = hmul2_bf16(pack_bf16(bf_lo(a.y) + bf_lo(b.y) + bf_lo(cc.y), bf_hi(a.y) + bf_hi(b.y) + bf_hi(cc.y)), gw[4 * g + 1]);
        gw[4 * g + 2] = hmul2_bf16(pack_bf16(bf_lo(a.z) + bf_lo(b.z) + bf_lo(cc.z), bf_hi(a.z) + bf_hi(b.z) + bf_hi(cc.z)), gw[4 * g + 2]);
        gw[4 * g + 3] = hmul2_bf16(pack_bf16(bf_lo(a.w) + bf_lo(b.w) + bf_lo(cc.w), bf_hi(a.w) + bf_hi(b.w) + bf_hi(cc.w)), gw[4 * g + 3]);
      }
      named_bar(1, 256);
      const uint32_t wbase = sb + warp * 16 * K2_PITCH;
      const int st_row = (lane & 7) + 8 * ((lane >> 3) & 1);
      const uint32_t sa = wbase + st_row * K2_PITCH + (lane >> 4) * 16;
#pragma unroll
      for (int g = 0; g < 28; g += 2) stmatrix_x4(sa + g * 16, gw[2 * g], gw[2 * g + 1], gw[2 * g + 2], gw[2 * g + 3]);
      __syncwarp();
      const uint32_t lp = wbase + lc * 16;
#pragma unroll
      for (int t = 0; t < 16; t++) {
        const uint4 tv = lds128(lp + t * K2_PITCH);
        uint4 o;
        o.x = hadd2_bf16(xv[t].x, tv.x); o.y = hadd2_bf16(xv[t].y, tv.y); o.z = hadd2_bf16(xv[t].z, tv.z); o.w = hadd2_bf16(xv[t].w, tv.w);
        if (lane < 28) stg128(out + gbase + t * 448, o);
      }
    }
    if (tid == 0) DBG(1, 63);
  }
  __syncwarp();
  cluster_arrive_relaxed();
  cluster_wait();
}

typedef CUresult (*EncFn)(CUtensorMap*, CUtensorMapDataType, cuuint32_t, void*, const cuuint64_t*, const cuuint64_t*, const cuuint32_t*,
                          const cuuint32_t*, CUtensorMapInterleave, CUtensorMapSwizzle, CUtensorMapL2promotion, CUtensorMapFloatOOBfill);

void make2d(EncFn enc, CUtensorMap* tm, const void* ptr, uint64_t cols, uint64_t rows, uint32_t bc, uint32_t br, bool swz = true) {
  cuuint64_t gd[2] = {cols, rows};
  cuuint64_t gs[1] = {cols * 2};
  cuuint32_t bd[2] = {bc, br};
  cuuint32_t es[2] = {1, 1};
  enc(tm, CU_TENSOR_MAP_DATA_TYPE_BFLOAT16, 2, const_cast<void*>(ptr), gd, gs, bd, es, CU_TENSOR_MAP_INTERLEAVE_NONE,
      swz ? CU_TENSOR_MAP_SWIZZLE_128B : CU_TENSOR_MAP_SWIZZLE_NONE, CU_TENSOR_MAP_L2_PROMOTION_L2_128B, CU_TENSOR_MAP_FLOAT_OOB_FILL_NONE);
}
void make3d_half(EncFn enc, CUtensorMap* tm, const void* ptr, uint64_t rows) {
  cuuint64_t gd[3] = {224, 2, rows};
  cuuint64_t gs[2] = {448, 896};
  cuuint32_t bd[3] = {64, 1, 64};
  cuuint32_t es[3] = {1, 1, 1};
  enc(tm, CU_TENSOR_MAP_DATA_TYPE_BFLOAT16, 3, const_cast<void*>(ptr), gd, gs, bd, es, CU_TENSOR_MAP_INTERLEAVE_NONE,
      CU_TENSOR_MAP_SWIZZLE_128B, CU_TENSOR_MAP_L2_PROMOTION_L2_128B, CU_TENSOR_MAP_FLOAT_OOB_FILL_NONE);
}

struct Maps { CUtensorMap wr, wi, wg, wu, cr, ci, h, ab, wd, hs, abs; };

}

extern "C" void kernel_launch(void* const* d_in, const int* in_sizes, int n_in, void* d_out, int out_size) {
  (void)in_sizes; (void)n_in; (void)out_size;
  static Maps maps;
  static const void* cached[9] = {nullptr};
  static bool attr_done = false;
  bool same = true;
  for (int i = 0; i < 9; i++) same = same && (cached[i] == d_in[i]);
  if (!same) {
    void* fn = nullptr;
    cudaDriverEntryPointQueryResult qr;
    cudaGetDriverEntryPoint("cuTensorMapEncodeTiled", &fn, cudaEnableDefault, &qr);
    EncFn enc = (EncFn)fn;
    void *p_ab = nullptr, *p_h = nullptr;
    cudaGetSymbolAddress(&p_ab, g_ab);
    cudaGetSymbolAddress(&p_h, g_h);
    make2d(enc, &maps.cr, d_in[1], 2048, 2048, 64, 128);
    make2d(enc, &maps.ci, d_in[2], 2048, 2048, 64, 128);
    make2d(enc, &maps.wr, d_in[3], 448, 448, 64, 56);
    make2d(enc, &maps.wi, d_in[4], 448, 448, 64, 56);
    make2d(enc, &maps.wg, d_in[6], 1792, 448, 64, 64);
    make2d(enc, &maps.wu, d_in[7], 1792, 448, 64, 64);
    make3d_half(enc, &maps.wd, d_in[8], 1792);
    make2d(enc, &maps.h, p_h, 1792, 2048, 64, 128);
    make3d_half(enc, &maps.ab, p_ab, 4096);
    make2d(enc, &maps.hs, p_h, 1792, 2048, 64, 64);
    make2d(enc, &maps.abs, p_ab, 448, 4096, 112, 64, false);
    for (int i = 0; i < 9; i++) cached[i] = d_in[i];
  }
  if (!attr_done) {
    cudaFuncSetAttribute(fused_kernel, cudaFuncAttributeMaxDynamicSharedMemorySize, K1_SMEM);
    attr_done = true;
  }
  PfPtrs pf;
  pf.wg = (const uint8_t*)d_in[6]; pf.wu = (const uint8_t*)d_in[7]; pf.wd = (const uint8_t*)d_in[8];
  fused_kernel<<<128, 384, K1_SMEM>>>(maps.wr, maps.wi, maps.wg, maps.wu, maps.hs, maps.abs, maps.cr, maps.ci, maps.h, maps.ab, maps.wd,
                                      (const __nv_bfloat16*)d_in[0], (__nv_bfloat16*)d_out, pf);
}
```

```cpp
#include <cuda_runtime.h>
#include <cuda_bf16.h>
#include <cuda.h>
#include <stdint.h>

namespace {

__device__ __align__(1024) __nv_bfloat16 g_ab[4096 * 448];
__device__ __align__(1024) __nv_bfloat16 g_h[2048 * 1792];
__device__ uint4 g_part[32 * 3 * 14 * 256];
__device__ __align__(1024) __nv_bfloat16 g_s[2048 * 448];
__device__ unsigned int g_epoch;
__device__ unsigned int g_ab_cnt;
__device__ unsigned int g_h_cnt[16 * 4];
__device__ unsigned int g_flags[64];

#define DBG(k, i) do {} while (0)
#define DBGC(k, i) do {} while (0)

#define TIMEOUT(code) __trap()
#define SPIN_LIMIT (1 << 22)
__device__ __forceinline__ uint32_t s2u(const void* p) { return (uint32_t)__cvta_generic_to_shared(p); }
__device__ __forceinline__ void mbar_init(uint32_t b, int c) { asm volatile("mbarrier.init.shared::cta.b64 [%0], %1;" ::"r"(b), "r"(c)); }
__device__ __forceinline__ void mbar_expect(uint32_t b, uint32_t bytes) {
  asm volatile("mbarrier.arrive.expect_tx.shared::cta.b64 _, [%0], %1;" ::"r"(b), "r"(bytes) : "memory");
}
__device__ __forceinline__ void mbar_wait(uint32_t b, uint32_t ph, int code = 1) {
  uint32_t done = 0;
  int it = 0;
  while (true) {
    asm volatile("{.reg .pred p; mbarrier.try_wait.parity.shared::cta.b64 p, [%1], %2; selp.u32 %0,1,0,p;}" : "=r"(done) : "r"(b), "r"(ph) : "memory");
    if (done) break;
    if (++it > SPIN_LIMIT) { TIMEOUT(code); break; }
  }
}
__device__ __forceinline__ void mbar_arrive_cluster(uint32_t b, uint32_t cta) {
  uint32_t r;
  asm volatile("mapa.shared::cluster.u32 %0, %1, %2;" : "=r"(r) : "r"(b), "r"(cta));
  asm volatile("mbarrier.arrive.shared::cluster.b64 _, [%0];" ::"r"(r) : "memory");
}
__device__ __forceinline__ void tma2d(uint32_t dst, const CUtensorMap* m, int c0, int c1, uint32_t bar) {
  asm volatile("cp.async.bulk.tensor.2d.shared::cluster.global.mbarrier::complete_tx::bytes [%0], [%1, {%3,%4}], [%2];" ::"r"(dst), "l"(m), "r"(bar), "r"(c0), "r"(c1) : "memory");
}
__device__ __forceinline__ void tma2d_mc(uint32_t dst, const CUtensorMap* m, int c0, int c1, uint32_t bar, uint16_t mask) {
  asm volatile("cp.async.bulk.tensor.2d.shared::cluster.global.mbarrier::complete_tx::bytes.multicast::cluster [%0], [%1, {%3,%4}], [%2], %5;" ::"r"(dst), "l"(m), "r"(bar), "r"(c0), "r"(c1), "h"(mask) : "memory");
}
__device__ __forceinline__ void tma3d_mc(uint32_t dst, const CUtensorMap* m, int c0, int c1, int c2, uint32_t bar, uint16_t mask) {
  asm volatile("cp.async.bulk.tensor.3d.shared::cluster.global.mbarrier::complete_tx::bytes.multicast::cluster [%0], [%1, {%3,%4,%5}], [%2], %6;" ::"r"(dst), "l"(m), "r"(bar), "r"(c0), "r"(c1), "r"(c2), "h"(mask) : "memory");
}
__device__ __forceinline__ void tma2d_store(const CUtensorMap* m, uint32_t src, int c0, int c1) {
  asm volatile("cp.async.bulk.tensor.2d.global.shared::cta.bulk_group [%0, {%2,%3}], [%1];" ::"l"(m), "r"(src), "r"(c0), "r"(c1) : "memory");
}
__device__ __forceinline__ void bulk_load(uint32_t dst, const void* src, uint32_t bytes, uint32_t bar) {
  asm volatile("cp.async.bulk.shared::cluster.global.mbarrier::complete_tx::bytes [%0], [%1], %2, [%3];" ::"r"(dst), "l"(src), "r"(bytes), "r"(bar) : "memory");
}
__device__ __forceinline__ void tma2d_prefetch(const CUtensorMap* m, int c0, int c1) {
  asm volatile("cp.async.bulk.prefetch.tensor.2d.L2.global [%0, {%1,%2}];" ::"l"(m), "r"(c0), "r"(c1) : "memory");
}
__device__ __forceinline__ void bulk_commit() { asm volatile("cp.async.bulk.commit_group;" ::: "memory"); }
__device__ __forceinline__ void bulk_wait_read0() { asm volatile("cp.async.bulk.wait_group.read 0;" ::: "memory"); }
__device__ __forceinline__ void bulk_wait0() { asm volatile("cp.async.bulk.wait_group 0;" ::: "memory"); }
__device__ __forceinline__ void fence_async_smem() { asm volatile("fence.proxy.async.shared::cta;" ::: "memory"); }
__device__ __forceinline__ void prefetch_tmap(const CUtensorMap* m) { asm volatile("prefetch.tensormap [%0];" ::"l"(m) : "memory"); }
__device__ __forceinline__ void l2_prefetch(const void* p, uint32_t bytes) {
  asm volatile("cp.async.bulk.prefetch.L2.global [%0], %1;" ::"l"(p), "r"(bytes) : "memory");
}
__device__ __forceinline__ void cluster_arrive_relaxed() { asm volatile("barrier.cluster.arrive.relaxed.aligned;" ::: "memory"); }
__device__ __forceinline__ void cluster_wait() { asm volatile("barrier.cluster.wait.aligned;" ::: "memory"); }
__device__ __forceinline__ void wg_fence() { __syncwarp(); asm volatile("wgmma.fence.sync.aligned;" ::: "memory"); }
__device__ __forceinline__ void wg_commit() { asm volatile("wgmma.commit_group.sync.aligned;" ::: "memory"); }
template <int N> __device__ __forceinline__ void wg_wait() { __syncwarp(); asm volatile("wgmma.wait_group.sync.aligned %0;" ::"n"(N) : "memory"); }
__device__ __forceinline__ void named_bar(int id, int n) { asm volatile("bar.sync %0, %1;" ::"r"(id), "r"(n) : "memory"); }
__device__ __forceinline__ void named_arrive(int id, int n) { asm volatile("bar.arrive %0, %1;" ::"r"(id), "r"(n) : "memory"); }
template <int N> __device__ __forceinline__ void reg_inc() { asm volatile("setmaxnreg.inc.sync.aligned.u32 %0;" ::"n"(N)); }
template <int N> __device__ __forceinline__ void reg_dec() { asm volatile("setmaxnreg.dec.sync.aligned.u32 %0;" ::"n"(N)); }
__device__ __forceinline__ void pdl_wait() { asm volatile("griddepcontrol.wait;" ::: "memory"); }
__device__ __forceinline__ void pdl_launch() { asm volatile("griddepcontrol.launch_dependents;" ::: "memory"); }

__device__ __forceinline__ uint32_t make_desc(uint32_t addr, uint32_t lbo, uint32_t  ) {
  return ((addr & 0x3FFFF) >> 4) | ((lbo >> 4) << 16);
}
__device__ __forceinline__ void stmatrix_x4(uint32_t addr, uint32_t r0, uint32_t r1, uint32_t r2, uint32_t r3) {
  asm volatile("stmatrix.sync.aligned.m8n8.x4.shared.b16 [%0], {%1,%2,%3,%4};" ::"r"(addr), "r"(r0), "r"(r1), "r"(r2), "r"(r3) : "memory");
}
__device__ __forceinline__ uint4 lds128(uint32_t a) {
  uint4 v;
  asm volatile("ld.shared.v4.u32 {%0,%1,%2,%3}, [%4];" : "=r"(v.x), "=r"(v.y), "=r"(v.z), "=r"(v.w) : "r"(a) : "memory");
  return v;
}
__device__ __forceinline__ void sts128(uint32_t a, uint4 v) {
  asm volatile("st.shared.v4.u32 [%0], {%1,%2,%3,%4};" ::"r"(a), "r"(v.x), "r"(v.y), "r"(v.z), "r"(v.w) : "memory");
}
__device__ __forceinline__ void stg128(void* p, uint4 v) {
  asm volatile("st.global.v4.u32 [%0], {%1,%2,%3,%4};" ::"l"(p), "r"(v.x), "r"(v.y), "r"(v.z), "r"(v.w) : "memory");
}
__device__ __forceinline__ void cp_async16(uint32_t dst, const void* src) {
  asm volatile("cp.async.cg.shared.global [%0], [%1], 16;" ::"r"(dst), "l"(src) : "memory");
}
__device__ __forceinline__ void cp_async8(uint32_t dst, const void* src) {
  asm volatile("cp.async.ca.shared.global [%0], [%1], 8;" ::"r"(dst), "l"(src) : "memory");
}
__device__ __forceinline__ uint2 lds64(uint32_t a) {
  uint2 v;
  asm volatile("ld.shared.v2.u32 {%0,%1}, [%2];" : "=r"(v.x), "=r"(v.y) : "r"(a) : "memory");
  return v;
}
__device__ __forceinline__ void cp_async_wait_all() { asm volatile("cp.async.wait_all;" ::: "memory"); }
__device__ __forceinline__ uint32_t pack_bf16(float lo, float hi) {
  uint32_t r;
  asm("cvt.rn.bf16x2.f32 %0, %1, %2;" : "=r"(r) : "f"(hi), "f"(lo));
  return r;
}
__device__ __forceinline__ uint32_t hmul2_bf16(uint32_t a, uint32_t b) {
  uint32_t r;
  asm("mul.rn.bf16x2 %0, %1, %2;" : "=r"(r) : "r"(a), "r"(b));
  return r;
}
__device__ __forceinline__ uint32_t hsub2_bf16(uint32_t a, uint32_t b) {
  uint32_t r;
  asm("sub.rn.bf16x2 %0, %1, %2;" : "=r"(r) : "r"(a), "r"(b));
  return r;
}
__device__ __forceinline__ uint32_t hadd2_bf16(uint32_t a, uint32_t b) {
  uint32_t r;
  asm("add.rn.bf16x2 %0, %1, %2;" : "=r"(r) : "r"(a), "r"(b));
  return r;
}
__device__ __forceinline__ uint32_t hfma2_bf16(uint32_t a, uint32_t b, uint32_t c) {
  uint32_t r;
  asm("fma.rn.bf16x2 %0, %1, %2, %3;" : "=r"(r) : "r"(a), "r"(b), "r"(c));
  return r;
}
__device__ __forceinline__ bool mbar_test(uint32_t b, uint32_t ph) {
  uint32_t done;
  asm volatile("{.reg .pred p; mbarrier.test_wait.parity.shared::cta.b64 p, [%1], %2; selp.u32 %0,1,0,p;}" : "=r"(done) : "r"(b), "r"(ph) : "memory");
  return __all_sync(0xffffffffu, done != 0);
}
__device__ __forceinline__ uint4 ldg128_cg(const void* p) {
  uint4 v;
  asm volatile("ld.global.cg.v4.u32 {%0,%1,%2,%3}, [%4];" : "=r"(v.x), "=r"(v.y), "=r"(v.z), "=r"(v.w) : "l"(p) : "memory");
  return v;
}
__device__ __forceinline__ float bf_lo(uint32_t w) { return __uint_as_float(w << 16); }
__device__ __forceinline__ float bf_hi(uint32_t w) { return __uint_as_float(w & 0xffff0000u); }
__device__ __forceinline__ float rbf(float x) { return __bfloat162float(__float2bfloat16_rn(x)); }
__device__ __forceinline__ float ex2f(float x) { float r; asm("ex2.approx.ftz.f32 %0, %1;" : "=f"(r) : "f"(x)); return r; }
__device__ __forceinline__ float rcpf(float x) { float r; asm("rcp.approx.ftz.f32 %0, %1;" : "=f"(r) : "f"(x)); return r; }
__device__ __forceinline__ float tanhf_hw(float x) { float r; asm("tanh.approx.f32 %0, %1;" : "=f"(r) : "f"(x)); return r; }
__device__ __forceinline__ float gelu_tanh(float x) {
  const float c1 = 0.7978845608028654f;
  const float c2 = c1 * 0.044715f;
  const float t = tanhf_hw(x * fmaf(c2, x * x, c1));
  const float hx = 0.5f * x;
  return fmaf(hx, t, hx);
}
__device__ __forceinline__ float silu_f(float x) {
  const float hx = 0.5f * x;
  return fmaf(hx, tanhf_hw(hx), hx);
}

__device__ __forceinline__ void wgmma_n128_tb(float (&d)[64], uint32_t da, uint32_t db, int scale_d) {
  asm volatile(
    "{\n.reg .pred p;\n.reg .b64 da, db;\nsetp.ne.b32 p, %66, 0;\n"
    "mov.b64 da, {%64, 0x40000040};\nmov.b64 db, {%65, 0x40000040};\n"
    "wgmma.mma_async.sync.aligned.m64n128k16.f32.bf16.bf16 {%0, %1, %2, %3, %4, %5, %6, %7, %8, %9, %10, %11, %12, %13, %14, %15, %16, %17, %18, %19, %20, %21, %22, %23, %24, %25, %26, %27, %28, %29, %30, %31, %32, %33, %34, %35, %36, %37, %38, %39, %40, %41, %42, %43, %44, %45, %46, %47, %48, %49, %50, %51, %52, %53, %54, %55, %56, %57, %58, %59, %60, %61, %62, %63}, da, db, p, 1, 1, 0, 1;\n}\n"
    : "+f"(d[0]), "+f"(d[1]), "+f"(d[2]), "+f"(d[3]), "+f"(d[4]), "+f"(d[5]), "+f"(d[6]), "+f"(d[7]), "+f"(d[8]), "+f"(d[9]), "+f"(d[10]), "+f"(d[11]), "+f"(d[12]), "+f"(d[13]), "+f"(d[14]), "+f"(d[15]), "+f"(d[16]), "+f"(d[17]), "+f"(d[18]), "+f"(d[19]), "+f"(d[20]), "+f"(d[21]), "+f"(d[22]), "+f"(d[23]), "+f"(d[24]), "+f"(d[25]), "+f"(d[26]), "+f"(d[27]), "+f"(d[28]), "+f"(d[29]), "+f"(d[30]), "+f"(d[31]), "+f"(d[32]), "+f"(d[33]), "+f"(d[34]), "+f"(d[35]), "+f"(d[36]), "+f"(d[37]), "+f"(d[38]), "+f"(d[39]), "+f"(d[40]), "+f"(d[41]), "+f"(d[42]), "+f"(d[43]), "+f"(d[44]), "+f"(d[45]), "+f"(d[46]), "+f"(d[47]), "+f"(d[48]), "+f"(d[49]), "+f"(d[50]), "+f"(d[51]), "+f"(d[52]), "+f"(d[53]), "+f"(d[54]), "+f"(d[55]), "+f"(d[56]), "+f"(d[57]), "+f"(d[58]), "+f"(d[59]), "+f"(d[60]), "+f"(d[61]), "+f"(d[62]), "+f"(d[63])
    : "r"(da), "r"(db), "r"(scale_d));
}
__device__ __forceinline__ void wgmma_n128_tb_p(float (&d)[64], uint32_t da, uint32_t db, int scale_d, int enable) {
  asm volatile(
    "{\n.reg .pred p;\n.reg .b64 da, db;\nsetp.ne.b32 p, %66, 0;\n.reg .pred q;\nsetp.ne.b32 q, %67, 0;\n"
    "mov.b64 da, {%64, 0x40000040};\nmov.b64 db, {%65, 0x40000040};\n"
    "@q wgmma.mma_async.sync.aligned.m64n128k16.f32.bf16.bf16 {%0, %1, %2, %3, %4, %5, %6, %7, %8, %9, %10, %11, %12, %13, %14, %15, %16, %17, %18, %19, %20, %21, %22, %23, %24, %25, %26, %27, %28, %29, %30, %31, %32, %33, %34, %35, %36, %37, %38, %39, %40, %41, %42, %43, %44, %45, %46, %47, %48, %49, %50, %51, %52, %53, %54, %55, %56, %57, %58, %59, %60, %61, %62, %63}, da, db, p, 1, 1, 0, 1;\n}\n"
    : "+f"(d[0]), "+f"(d[1]), "+f"(d[2]), "+f"(d[3]), "+f"(d[4]), "+f"(d[5]), "+f"(d[6]), "+f"(d[7]), "+f"(d[8]), "+f"(d[9]), "+f"(d[10]), "+f"(d[11]), "+f"(d[12]), "+f"(d[13]), "+f"(d[14]), "+f"(d[15]), "+f"(d[16]), "+f"(d[17]), "+f"(d[18]), "+f"(d[19]), "+f"(d[20]), "+f"(d[21]), "+f"(d[22]), "+f"(d[23]), "+f"(d[24]), "+f"(d[25]), "+f"(d[26]), "+f"(d[27]), "+f"(d[28]), "+f"(d[29]), "+f"(d[30]), "+f"(d[31]), "+f"(d[32]), "+f"(d[33]), "+f"(d[34]), "+f"(d[35]), "+f"(d[36]), "+f"(d[37]), "+f"(d[38]), "+f"(d[39]), "+f"(d[40]), "+f"(d[41]), "+f"(d[42]), "+f"(d[43]), "+f"(d[44]), "+f"(d[45]), "+f"(d[46]), "+f"(d[47]), "+f"(d[48]), "+f"(d[49]), "+f"(d[50]), "+f"(d[51]), "+f"(d[52]), "+f"(d[53]), "+f"(d[54]), "+f"(d[55]), "+f"(d[56]), "+f"(d[57]), "+f"(d[58]), "+f"(d[59]), "+f"(d[60]), "+f"(d[61]), "+f"(d[62]), "+f"(d[63])
    : "r"(da), "r"(db), "r"(scale_d), "r"(enable));
}
__device__ __forceinline__ void wgmma_n112(float (&d)[56], uint32_t da, uint32_t db, int scale_d) {
  asm volatile(
    "{\n.reg .pred p;\n.reg .b64 da, db;\nsetp.ne.b32 p, %58, 0;\n"
    "mov.b64 da, {%56, 0x40000040};\nmov.b64 db, {%57, 0x40000040};\n"
    "wgmma.mma_async.sync.aligned.m64n112k16.f32.bf16.bf16 {%0, %1, %2, %3, %4, %5, %6, %7, %8, %9, %10, %11, %12, %13, %14, %15, %16, %17, %18, %19, %20, %21, %22, %23, %24, %25, %26, %27, %28, %29, %30, %31, %32, %33, %34, %35, %36, %37, %38, %39, %40, %41, %42, %43, %44, %45, %46, %47, %48, %49, %50, %51, %52, %53, %54, %55}, da, db, p, 1, 1, 0, 0;\n}\n"
    : "+f"(d[0]), "+f"(d[1]), "+f"(d[2]), "+f"(d[3]), "+f"(d[4]), "+f"(d[5]), "+f"(d[6]), "+f"(d[7]), "+f"(d[8]), "+f"(d[9]), "+f"(d[10]), "+f"(d[11]), "+f"(d[12]), "+f"(d[13]), "+f"(d[14]), "+f"(d[15]), "+f"(d[16]), "+f"(d[17]), "+f"(d[18]), "+f"(d[19]), "+f"(d[20]), "+f"(d[21]), "+f"(d[22]), "+f"(d[23]), "+f"(d[24]), "+f"(d[25]), "+f"(d[26]), "+f"(d[27]), "+f"(d[28]), "+f"(d[29]), "+f"(d[30]), "+f"(d[31]), "+f"(d[32]), "+f"(d[33]), "+f"(d[34]), "+f"(d[35]), "+f"(d[36]), "+f"(d[37]), "+f"(d[38]), "+f"(d[39]), "+f"(d[40]), "+f"(d[41]), "+f"(d[42]), "+f"(d[43]), "+f"(d[44]), "+f"(d[45]), "+f"(d[46]), "+f"(d[47]), "+f"(d[48]), "+f"(d[49]), "+f"(d[50]), "+f"(d[51]), "+f"(d[52]), "+f"(d[53]), "+f"(d[54]), "+f"(d[55])
    : "r"(da), "r"(db), "r"(scale_d));
}
__device__ __forceinline__ void wgmma_n224_tb(float (&d)[112], uint32_t da, uint32_t db, int scale_d) {
  asm volatile(
    "{\n.reg .pred p;\n.reg .b64 da, db;\nsetp.ne.b32 p, %114, 0;\n"
    "mov.b64 da, {%112, 0x40000040};\nmov.b64 db, {%113, 0x40000040};\n"
    "wgmma.mma_async.sync.aligned.m64n224k16.f32.bf16.bf16 {%0, %1, %2, %3, %4, %5, %6, %7, %8, %9, %10, %11, %12, %13, %14, %15, %16, %17, %18, %19, %20, %21, %22, %23, %24, %25, %26, %27, %28, %29, %30, %31, %32, %33, %34, %35, %36, %37, %38, %39, %40, %41, %42, %43, %44, %45, %46, %47, %48, %49, %50, %51, %52, %53, %54, %55, %56, %57, %58, %59, %60, %61, %62, %63, %64, %65, %66, %67, %68, %69, %70, %71, %72, %73, %74, %75, %76, %77, %78, %79, %80, %81, %82, %83, %84, %85, %86, %87, %88, %89, %90, %91, %92, %93, %94, %95, %96, %97, %98, %99, %100, %101, %102, %103, %104, %105, %106, %107, %108, %109, %110, %111}, da, db, p, 1, 1, 0, 1;\n}\n"
    : "+f"(d[0]), "+f"(d[1]), "+f"(d[2]), "+f"(d[3]), "+f"(d[4]), "+f"(d[5]), "+f"(d[6]), "+f"(d[7]), "+f"(d[8]), "+f"(d[9]), "+f"(d[10]), "+f"(d[11]), "+f"(d[12]), "+f"(d[13]), "+f"(d[14]), "+f"(d[15]), "+f"(d[16]), "+f"(d[17]), "+f"(d[18]), "+f"(d[19]), "+f"(d[20]), "+f"(d[21]), "+f"(d[22]), "+f"(d[23]), "+f"(d[24]), "+f"(d[25]), "+f"(d[26]), "+f"(d[27]), "+f"(d[28]), "+f"(d[29]), "+f"(d[30]), "+f"(d[31]), "+f"(d[32]), "+f"(d[33]), "+f"(d[34]), "+f"(d[35]), "+f"(d[36]), "+f"(d[37]), "+f"(d[38]), "+f"(d[39]), "+f"(d[40]), "+f"(d[41]), "+f"(d[42]), "+f"(d[43]), "+f"(d[44]), "+f"(d[45]), "+f"(d[46]), "+f"(d[47]), "+f"(d[48]), "+f"(d[49]), "+f"(d[50]), "+f"(d[51]), "+f"(d[52]), "+f"(d[53]), "+f"(d[54]), "+f"(d[55]), "+f"(d[56]), "+f"(d[57]), "+f"(d[58]), "+f"(d[59]), "+f"(d[60]), "+f"(d[61]), "+f"(d[62]), "+f"(d[63]), "+f"(d[64]), "+f"(d[65]), "+f"(d[66]), "+f"(d[67]), "+f"(d[68]), "+f"(d[69]), "+f"(d[70]), "+f"(d[71]), "+f"(d[72]), "+f"(d[73]), "+f"(d[74]), "+f"(d[75]), "+f"(d[76]), "+f"(d[77]), "+f"(d[78]), "+f"(d[79]), "+f"(d[80]), "+f"(d[81]), "+f"(d[82]), "+f"(d[83]), "+f"(d[84]), "+f"(d[85]), "+f"(d[86]), "+f"(d[87]), "+f"(d[88]), "+f"(d[89]), "+f"(d[90]), "+f"(d[91]), "+f"(d[92]), "+f"(d[93]), "+f"(d[94]), "+f"(d[95]), "+f"(d[96]), "+f"(d[97]), "+f"(d[98]), "+f"(d[99]), "+f"(d[100]), "+f"(d[101]), "+f"(d[102]), "+f"(d[103]), "+f"(d[104]), "+f"(d[105]), "+f"(d[106]), "+f"(d[107]), "+f"(d[108]), "+f"(d[109]), "+f"(d[110]), "+f"(d[111])
    : "r"(da), "r"(db), "r"(scale_d));
}

constexpr int K1_NS = 5;
constexpr int K1_A_BYTES = 7 * 16384;
constexpr int K1_B_OFF = K1_A_BYTES;
constexpr int K1_STG_OFF = K1_B_OFF + K1_NS * 16384;
constexpr int K1_BAR_OFF = K1_STG_OFF + 8 * 4096;
constexpr int K1_SMEM = K1_BAR_OFF + 256 + 1024;

struct K1Ctx {
  uint32_t sb, bar_full, rel0, rel1;
  uint32_t dA, dBk, dBn;
  bool lane0;
  uint32_t bar_sfree;
  uint32_t sphase;
};
__device__ __forceinline__ void k1_release(const K1Ctx& c, int slot) {
  if (c.lane0) {
    asm volatile("mbarrier.arrive.shared::cluster.b64 _, [%0];" ::"r"(c.rel0 + 8 * slot) : "memory");
    asm volatile("mbarrier.arrive.shared::cluster.b64 _, [%0];" ::"r"(c.rel1 + 8 * slot) : "memory");
  }
}

__device__ __forceinline__ void k1_unit_ab(K1Ctx& c, int warp, int lane, int mt, int j) {
  const int wq = warp & 3;
  const int st_row = (lane & 7) + 8 * ((lane >> 3) & 1);
  const int st_chunk = lane >> 4;
  float acc[2][56];
  int slot = 0; uint32_t ph = 0;
#pragma unroll 1
  for (int kb = 0; kb < 7; kb++) {
    const int pslot = (slot == 0) ? K1_NS - 1 : slot - 1;
    mbar_wait(c.bar_full + 8 * slot, ph, 3);
    if (kb == 6) named_arrive(2, 256);
    if (kb == 0 && (threadIdx.x & 127) == 0) DBG(0, 4);
    if ((threadIdx.x & 127) == 0) DBGC(1, 46 + kb);
    wg_fence();
    const uint32_t da = c.dA + kb * 1024;
    const uint32_t db = c.dBk + slot * 1024;
#pragma unroll
    for (int k = 0; k < 4; k++) {
      wgmma_n112(acc[0], da + k * 2, db + k * 2, (kb | k) != 0);
      wgmma_n112(acc[1], da + 512 + k * 2, db + k * 2, (kb | k) != 0);
    }
    wg_commit();
    if (kb > 0) { wg_wait<1>(); k1_release(c, pslot); }
    if (++slot == K1_NS) { slot = 0; ph ^= 1; }
  }
  wg_wait<0>();
  k1_release(c, 6 % K1_NS);
  if ((threadIdx.x & 127) == 0) DBG(0, 5);
  const uint32_t sgn = (j < 4) ? 0u : 0x80008000u;
  const uint32_t sa = c.sb + K1_STG_OFF + (wq * 16 + st_row) * 224 + st_chunk * 16;
#pragma unroll
  for (int h = 0; h < 2; h++) {
    if (h == 1) { mbar_wait(c.bar_sfree, c.sphase, 6); c.sphase ^= 1; }
#pragma unroll
    for (int g = 0; g < 14; g += 2) {
      const float* a = &acc[h][4 * g];
      stmatrix_x4(sa + g * 16, pack_bf16(a[0], a[1]) ^ sgn, pack_bf16(a[2], a[3]) ^ sgn, pack_bf16(a[4], a[5]) ^ sgn, pack_bf16(a[6], a[7]) ^ sgn);
    }
    fence_async_smem();
    named_arrive(6, 160);
  }
}

__device__ __forceinline__ void k1_unit_gu(K1Ctx& c, int warp, int lane, int mt, int unit, int fb, int hsel, int full, int nunits) {
  const int wq = warp & 3;
  float acc[2][64];
  const uint32_t dA0 = c.dA + (full ? 0 : hsel * 512);
  int slot = (unit * 7) % K1_NS; uint32_t ph = ((unit * 7) / K1_NS) & 1;
  named_bar(2 + ((unit - 1) & 1), 256);
  if (full) {
#pragma unroll 1
    for (int kb = 0; kb < 7; kb++) {
      const int pslot = (slot == 0) ? K1_NS - 1 : slot - 1;
      mbar_wait(c.bar_full + 8 * slot, ph, 4);
      if (kb == 6 && unit + 1 < nunits) named_arrive(2 + (unit & 1), 256);
      if (kb == 0 && (threadIdx.x & 127) == 0) DBG(0, 4 + 3 * unit);
      wg_fence();
      const uint32_t da = dA0 + kb * 1024;
      const uint32_t db = c.dBn + slot * 1024;
#pragma unroll
      for (int k = 0; k < 4; k++) {
        wgmma_n128_tb(acc[0], da + k * 2, db + k * 128, (kb | k) != 0);
        wgmma_n128_tb(acc[1], da + 512 + k * 2, db + k * 128, (kb | k) != 0);
      }
      wg_commit();
      if (kb > 0) { wg_wait<1>(); k1_release(c, pslot); }
      if (++slot == K1_NS) { slot = 0; ph ^= 1; }
    }
  } else {
#pragma unroll 1
    for (int kb = 0; kb < 7; kb++) {
      const int pslot = (slot == 0) ? K1_NS - 1 : slot - 1;
      mbar_wait(c.bar_full + 8 * slot, ph, 5);
      if (kb == 0 && (threadIdx.x & 127) == 0) DBG(0, 4 + 3 * unit);
      wg_fence();
      const uint32_t da = dA0 + kb * 1024;
      const uint32_t db = c.dBn + slot * 1024;
#pragma unroll
      for (int k = 0; k < 4; k++) wgmma_n128_tb(acc[0], da + k * 2, db + k * 128, (kb | k) != 0);
      wg_commit();
      if (kb > 0) { wg_wait<1>(); k1_release(c, pslot); }
      if (++slot == K1_NS) { slot = 0; ph ^= 1; }
    }
  }
  wg_wait<0>();
  k1_release(c, (slot == 0) ? K1_NS - 1 : slot - 1);
  if (unit + 2 >= nunits && lane < 4) {
    asm volatile("mbarrier.arrive.shared::cluster.b64 _, [%0];" ::"r"(c.rel0 + 8 * (K1_NS + 4 + lane)) : "memory");
    asm volatile("mbarrier.arrive.shared::cluster.b64 _, [%0];" ::"r"(c.rel1 + 8 * (K1_NS + 4 + lane)) : "memory");
  }
  if ((threadIdx.x & 127) == 0) DBG(0, 5 + 3 * unit);
  const int st_row = (lane & 7) + 8 * ((lane >> 3) & 1);
  const int st_chunk = lane >> 4;
  const uint32_t sa = c.sb + K1_STG_OFF + (warp >> 2) * 16384 + (wq * 16 + st_row) * 128;
  if (unit >= 2) { mbar_wait(c.bar_sfree, c.sphase, 7); c.sphase ^= 1; }
#pragma unroll
  for (int h = 0; h < 2; h++) {
    if (h == 1 && !full) break;
#pragma unroll
    for (int g = 0; g < 8; g += 2) {
      uint32_t pk[4];
#pragma unroll
      for (int e = 0; e < 4; e++) {
        const int i = 4 * g + 2 * e;
        const uint32_t g2 = pack_bf16(acc[h][i], acc[h][i + 1]);
        const uint32_t u2 = pack_bf16(acc[h][32 + i], acc[h][32 + i + 1]);
        pk[e] = hmul2_bf16(pack_bf16(gelu_tanh(bf_lo(g2)), gelu_tanh(bf_hi(g2))), u2);
      }
      stmatrix_x4(sa + h * 8192 + (((g + st_chunk) ^ (st_row & 7)) * 16), pk[0], pk[1], pk[2], pk[3]);
    }
  }
  fence_async_smem();
  named_arrive(6 + (warp >> 2), 160);
}

constexpr int K2_NS = 4;
constexpr int K2_STAGE = 16384 + 32768;
constexpr int K2_PITCH = 464;

__device__ __forceinline__ void spin_flag(const unsigned int* flag, unsigned int target) {
  int it = 0;
  while (true) {
    unsigned int v;
    asm volatile("ld.acquire.gpu.global.u32 %0, [%1];" : "=r"(v) : "l"(flag) : "memory");
    if ((int)(v - target) >= 0) break;
    if (++it > SPIN_LIMIT) { TIMEOUT(20); break; }
  }
}

struct PfPtrs { const uint8_t* wg; const uint8_t* wu; const uint8_t* wd; };

__global__ void __cluster_dims__(2, 1, 1) __launch_bounds__(384, 1)
fused_kernel(const __grid_constant__ CUtensorMap tm_wr, const __grid_constant__ CUtensorMap tm_wi,
             const __grid_constant__ CUtensorMap tm_wg, const __grid_constant__ CUtensorMap tm_wu,
             const __grid_constant__ CUtensorMap tm_hs, const __grid_constant__ CUtensorMap tm_abs,
             const __grid_constant__ CUtensorMap tm_cr, const __grid_constant__ CUtensorMap tm_ci, const __grid_constant__ CUtensorMap tm_h,
             const __grid_constant__ CUtensorMap tm_ab, const __grid_constant__ CUtensorMap tm_wd,
             const __nv_bfloat16* __restrict__ x, __nv_bfloat16* __restrict__ out, const PfPtrs pf) {
  extern __shared__ uint8_t smem_raw[];
  const uint32_t sb = (s2u(smem_raw) + 1023) & ~1023u;
  const int tid = threadIdx.x, warp = tid >> 5, lane = tid & 31;
  uint32_t rank;
  asm volatile("mov.u32 %0, %%cluster_ctarank;" : "=r"(rank));
  const int cid = blockIdx.x >> 1;
  const int p = cid >> 3, j = cid & 7;
  const int mt = 2 * p + (int)rank;
  const uint32_t bar_full = sb + K1_BAR_OFF;
  const uint32_t bar_empty = bar_full + 8 * K1_NS;
  const uint32_t bar_full2 = bar_empty + 8 * K1_NS;
  const uint32_t bar_empty2 = bar_full2 + 8 * K2_NS;
  const int fb_base = 7 * (j >> 1);
  const int fb0 = fb_base + ((j & 1) ? 4 : 0);
  const int fbh = fb_base + 3;
  const int q = j & 3, n = j >> 2;
  const int tile = mt * 2 + n;
  const int nkb = (q == 0) ? 22 : (q == 3 ? 28 : 21);
  const int nunits = (q == 3) ? 4 : 5;
  const int u4full = (q == 2);

  if (tid == 0) DBG(0, 0);
  if (tid == 256) {
    for (int i = 0; i < K1_NS; i++) { mbar_init(bar_full + 8 * i, 1); mbar_init(bar_empty + 8 * i, 8); }
    for (int i = 0; i < K2_NS; i++) { mbar_init(bar_full2 + 8 * i, 1); mbar_init(bar_empty2 + 8 * i, 16); }
    mbar_init(bar_empty2 + 8 * K2_NS, 1);
    mbar_init(bar_empty2 + 8 * K2_NS + 8, 1);
    mbar_init(bar_empty2 + 8 * K2_NS + 16, 1);
    asm volatile("fence.mbarrier_init.release.cluster;" ::: "memory");
    prefetch_tmap((j < 4) ? &tm_wr : &tm_wi);
    prefetch_tmap(rank ? &tm_wu : &tm_wg);
    prefetch_tmap(&tm_abs);
    prefetch_tmap(&tm_hs);
  }
  __syncwarp();
  cluster_arrive_relaxed();

  if (warp >= 8) {
    reg_dec<40>();
    cluster_wait();
    if (tid == 256) {
      const unsigned int epoch = *reinterpret_cast<volatile unsigned int*>(&g_epoch);
      {
        const CUtensorMap* tw = (j < 4) ? &tm_wr : &tm_wi;
        const CUtensorMap* tgu = rank ? &tm_wu : &tm_wg;
        int slot = 0; uint32_t ph = 0;
        int kb = 0, unit = 0;
#pragma unroll 1
        for (int s = 0; s < 7 * nunits; s++) {
          if (s >= K1_NS) mbar_wait(bar_empty + 8 * slot, ph ^ 1, 2);
          const uint32_t dst = sb + K1_B_OFF + slot * 16384;
          if (unit == 0) {
            mbar_expect(bar_full + 8 * slot, 14336);
            tma2d_mc(dst + rank * 7168, tw, kb * 64, (j & 3) * 112 + rank * 56, bar_full + 8 * slot, 3);
          } else {
            const int fb = (unit == 4) ? fbh : (fb0 + unit - 1);
            mbar_expect(bar_full + 8 * slot, 16384);
            tma2d_mc(dst + rank * 8192, tgu, fb * 64, kb * 64, bar_full + 8 * slot, 3);
          }
          if (s == 21) {
            l2_prefetch(pf.wd + blockIdx.x * 12544, 12544);
            if (q < 3) {
              const int g0 = (q == 0) ? 0 : (q == 1 ? 22 : 43);
#pragma unroll 1
              for (int i = 0; i < 6; i++) tma2d_prefetch((g0 + i < 32) ? &tm_cr : &tm_ci, ((g0 + i) & 31) * 64, mt * 128);
            }
          }
          if (++kb == 7) { kb = 0; unit++; }
          if (++slot == K1_NS) { slot = 0; ph ^= 1; }
        }
      }
      {
        const int g0 = (q == 0) ? 0 : (q == 1 ? 22 : (q == 2 ? 43 : 64));
        const CUtensorMap* tb = (q < 3) ? &tm_ab : &tm_wd;
        prefetch_tmap(tb); prefetch_tmap((q < 3) ? ((g0 < 32) ? &tm_cr : &tm_ci) : &tm_h);
        const int kb0 = (q < 3) ? g0 : 0;
        if (q < 3) { spin_flag(&g_ab_cnt, 128u * (epoch + 1)); asm volatile("fence.proxy.async;" ::: "memory"); }
        DBG(1, 31);
        int slot = 0; uint32_t ph = 0;
#pragma unroll 1
        for (int s = 0; s < nkb; s++) {
          int kblk = kb0 + s;
          const CUtensorMap* ta = (kblk < 32) ? &tm_cr : &tm_ci;
          if (q == 3) {
            if ((s & 7) == 0) { spin_flag(&g_h_cnt[mt * 4 + (s >> 3)], ((s < 24) ? 8u : 6u) * (epoch + 1)); asm volatile("fence.proxy.async;" ::: "memory"); }
            const int i = s & 7;
            kblk = (s < 24) ? (7 * (i >> 1) + ((i & 1) ? 4 : 0) + (s >> 3)) : (7 * i + 3);
            ta = &tm_h;
          }
          mbar_wait(bar_empty2 + 8 * slot, ph, 10);
          const uint32_t dst = sb + slot * K2_STAGE;
          const uint32_t fb = bar_full2 + 8 * slot;
          mbar_expect(fb, K2_STAGE);
          tma2d(dst, ta, (kblk & 31) * 64, mt * 128, fb);
          tma3d_mc(dst + 16384 + (2 * rank) * 8192, tb, (2 * rank) * 64, n, kblk * 64, fb, 3);
          tma3d_mc(dst + 16384 + (2 * rank + 1) * 8192, tb, (2 * rank + 1) * 64, n, kblk * 64, fb, 3);
          if (++slot == K2_NS) { slot = 0; ph ^= 1; }
        }
        if (q == 3) {
          const uint32_t bar_p = bar_empty2 + 8 * K2_NS;
          spin_flag(&g_flags[tile], 3u * (epoch + 1));
          asm volatile("fence.proxy.async;" ::: "memory");
          mbar_expect(bar_p, 3 * 57344);
          const uint4* pp = g_part + (size_t)tile * (3 * 14 * 256);
#pragma unroll 1
          for (int c = 0; c < 7; c++) {
            if ((c & 1) == 0) mbar_wait(bar_empty2 + 8 * (c >> 1), ph, 13);
            bulk_load(sb + c * 24576, pp + c * 1536, 24576, bar_p);
          }
          DBG(1, 30);
        }
      }
    } else if (warp == 9 || warp == 10) {
      const int hw = warp - 9;
      const uint32_t stg = sb + K1_STG_OFF + hw * 16384;
      const uint32_t bar_sfree = bar_empty2 + 8 * K2_NS + 8 + 8 * hw;
      if (lane == 0) {
        const int b = blockIdx.x;
        l2_prefetch((hw ? pf.wu : pf.wg) + b * 12544, 12544);
      }
#pragma unroll 1
      for (int job = 0; job < (hw ? 2 : (nunits == 5 ? 4 : 3)); job++) {
        named_bar(6 + hw, 160);
        if (lane == 0) {
          const int unit = hw ? (1 + 2 * job) : (job < 2 ? 0 : 2 * job - 2);
          if (unit == 0) {
            tma2d_store(&tm_abs, stg, (j & 3) * 112, (j < 4 ? 0 : 2048) + mt * 128 + job * 64);
          } else {
            const int fb = (unit == 4) ? fbh : fb0 + unit - 1;
            const bool fullu = (unit < 4) || u4full;
            tma2d_store(&tm_hs, stg, fb * 64, mt * 128 + (fullu ? 0 : (j & 1) * 64));
            if (fullu) tma2d_store(&tm_hs, stg + 8192, fb * 64, mt * 128 + 64);
          }
          bulk_commit();
          bulk_wait_read0();
          asm volatile("mbarrier.arrive.shared::cta.b64 _, [%0];" ::"r"(bar_sfree) : "memory");
          if (unit != 0 || job == 1) {
            bulk_wait0();
            asm volatile("fence.proxy.async;" ::: "memory");
            __threadfence();
            if (unit == 0) {
              const unsigned int old = atomicAdd(&g_ab_cnt, 1u);
              if ((old & 127u) == 127u) *reinterpret_cast<volatile unsigned int*>(&g_epoch) = (old >> 7) + 1;
            } else {
              atomicAdd(&g_h_cnt[mt * 4 + unit - 1], 1u);
            }
          }
        }
        __syncwarp();
      }
    }
  } else {
    reg_inc<232>();
    const int wg = warp >> 2;
    {
      const int c = lane & 7;
      const int r0 = warp * 16 + (lane >> 3);
      const uint4* src = reinterpret_cast<const uint4*>(x + (size_t)(mt * 128 + r0) * 448) + c;
      uint4 nx[7];
#pragma unroll
      for (int b = 0; b < 7; b++)
        asm volatile("ld.global.nc.v4.u32 {%0,%1,%2,%3}, [%4];" : "=r"(nx[b].x), "=r"(nx[b].y), "=r"(nx[b].z), "=r"(nx[b].w) : "l"(src + b * 8) : "memory");
#pragma unroll
      for (int pass = 1; pass < 4; pass++) asm volatile("prefetch.global.L2 [%0];" ::"l"(src + pass * 4 * 56 + c * 7 - c) : "memory");
#pragma unroll 1
      for (int pass = 0; pass < 4; pass++) {
        uint4 v[7];
#pragma unroll
        for (int b = 0; b < 7; b++) v[b] = nx[b];
        if (pass < 3) {
          const uint4* s2 = src + (pass + 1) * 4 * 56;
#pragma unroll
          for (int b = 0; b < 7; b++)
            asm volatile("ld.global.nc.v4.u32 {%0,%1,%2,%3}, [%4];" : "=r"(nx[b].x), "=r"(nx[b].y), "=r"(nx[b].z), "=r"(nx[b].w) : "l"(s2 + b * 8) : "memory");
        }
        float s0 = 0.f, s1 = 0.f, s2v = 0.f, s3 = 0.f;
#pragma unroll
        for (int b = 0; b < 7; b++) {
          s0 += bf_lo(v[b].x) + bf_hi(v[b].x); s1 += bf_lo(v[b].y) + bf_hi(v[b].y);
          s2v += bf_lo(v[b].z) + bf_hi(v[b].z); s3 += bf_lo(v[b].w) + bf_hi(v[b].w);
        }
        float m = (s0 + s1) + (s2v + s3);
        m += __shfl_xor_sync(0xffffffffu, m, 1);
        m += __shfl_xor_sync(0xffffffffu, m, 2);
        m += __shfl_xor_sync(0xffffffffu, m, 4);
        m *= (1.0f / 448.0f);
        float q0 = 0.f, q1 = 0.f, q2 = 0.f, q3 = 0.f;
#pragma unroll
        for (int b = 0; b < 7; b++) {
          float d;
          d = bf_lo(v[b].x) - m; q0 = fmaf(d, d, q0); d = bf_hi(v[b].x) - m; q1 = fmaf(d, d, q1);
          d = bf_lo(v[b].y) - m; q2 = fmaf(d, d, q2); d = bf_hi(v[b].y) - m; q3 = fmaf(d, d, q3);
          d = bf_lo(v[b].z) - m; q0 = fmaf(d, d, q0); d = bf_hi(v[b].z) - m; q1 = fmaf(d, d, q1);
          d = bf_lo(v[b].w) - m; q2 = fmaf(d, d, q2); d = bf_hi(v[b].w) - m; q3 = fmaf(d, d, q3);
        }
        float q = (q0 + q1) + (q2 + q3);
        q += __shfl_xor_sync(0xffffffffu, q, 1);
        q += __shfl_xor_sync(0xffffffffu, q, 2);
        q += __shfl_xor_sync(0xffffffffu, q, 4);
        const float var_b = rbf(q * (1.0f / 448.0f));
        const float den = rbf(sqrtf(rbf(var_b + 1e-5f)));
        const float ri = 1.0f / den;
        const float rih = rbf(ri);
        const uint32_t rhi2 = pack_bf16(rih, rih), rlo2 = pack_bf16(ri - rih, ri - rih);
        const uint32_t m2 = pack_bf16(m, m);
        const int r = r0 + pass * 4;
        const uint32_t a0 = sb + r * 128 + ((c ^ (r & 7)) * 16);
#pragma unroll
        for (int b = 0; b < 7; b++) {
          uint32_t w4[4] = {v[b].x, v[b].y, v[b].z, v[b].w};
#pragma unroll
          for (int qq = 0; qq < 4; qq++) {
            const uint32_t dw = hsub2_bf16(w4[qq], m2);
            w4[qq] = hfma2_bf16(dw, rhi2, hmul2_bf16(dw, rlo2));
          }
          sts128(a0 + b * 16384, make_uint4(w4[0], w4[1], w4[2], w4[3]));
        }
      }
    }
    asm volatile("fence.proxy.async.shared::cta;" ::: "memory");
    named_bar(1, 256);
    cluster_wait();
    if (tid == 0) DBG(0, 3);

    uint32_t rel0, rel1;
    asm volatile("mapa.shared::cluster.u32 %0, %1, %2;" : "=r"(rel0) : "r"(bar_empty2), "r"(0));
    asm volatile("mapa.shared::cluster.u32 %0, %1, %2;" : "=r"(rel1) : "r"(bar_empty2), "r"(1));
    {
      K1Ctx c;
      c.sb = sb; c.bar_full = bar_full; c.lane0 = (lane == 0);
      c.rel0 = rel0 - 8 * (K1_NS + K2_NS); c.rel1 = rel1 - 8 * (K1_NS + K2_NS);
      c.bar_sfree = bar_empty2 + 8 * K2_NS + 8 + 8 * wg; c.sphase = 0;
      c.dA = make_desc(sb, 16, 1024);
      c.dBk = make_desc(sb + K1_B_OFF, 16, 1024);
      c.dBn = make_desc(sb + K1_B_OFF, 8192, 1024);
      if (wg == 0) {
        k1_unit_ab(c, warp, lane, mt, j);
        if (tid == 0) DBG(0, 6);
      }
#pragma unroll 1
      for (int unit = 2 - wg; unit < nunits; unit += 2) {
        k1_unit_gu(c, warp, lane, mt, unit, (unit == 4) ? fbh : fb0 + unit - 1, j & 1, (unit < 4) || u4full, nunits);
        if ((tid & 127) == 0) DBG(0, 6 + 3 * unit);
      }
    }

    float acc[112];
    const uint32_t dA0 = make_desc(sb + wg * 8192, 16, 1024);
    const uint32_t dB0 = make_desc(sb + 16384, 8192, 1024);
    int slot = 0; uint32_t ph = 0;
#pragma unroll 1
    for (int s = 0; s < nkb; s++) {
      mbar_wait(bar_full2 + 8 * slot, ph, 11);
      if (tid == 0) DBG(1, 1 + s);
      wg_fence();
      const uint32_t da = dA0 + slot * (K2_STAGE / 16);
      const uint32_t db = dB0 + slot * (K2_STAGE / 16);
#pragma unroll
      for (int k = 0; k < 4; k++) wgmma_n224_tb(acc, da + k * 2, db + k * 128, (s | k) != 0);
      wg_commit();
      if (s > 0) {
        wg_wait<1>();
        const int ps = (slot == 0) ? K2_NS - 1 : slot - 1;
        if (lane == 0) {
          asm volatile("mbarrier.arrive.shared::cluster.b64 _, [%0];" ::"r"(rel0 + 8 * ps) : "memory");
          asm volatile("mbarrier.arrive.shared::cluster.b64 _, [%0];" ::"r"(rel1 + 8 * ps) : "memory");
        }
      }
      if (++slot == K2_NS) { slot = 0; ph ^= 1; }
    }
    wg_wait<0>();
    if (tid == 0) DBG(1, 29);
    if (q < 3) {
      uint4* part = g_part + (size_t)(tile * 3 + q) * (14 * 256) + tid;
#pragma unroll
      for (int g = 0; g < 14; g++)
        part[g * 256] = make_uint4(pack_bf16(acc[8 * g], acc[8 * g + 1]), pack_bf16(acc[8 * g + 2], acc[8 * g + 3]),
                                   pack_bf16(acc[8 * g + 4], acc[8 * g + 5]), pack_bf16(acc[8 * g + 6], acc[8 * g + 7]));
      __threadfence();
      asm volatile("fence.proxy.async;" ::: "memory");
      named_bar(1, 256);
      if (tid == 0) atomicAdd(&g_flags[tile], 1u);
    } else {
      if (lane == 0) {
        asm volatile("mbarrier.arrive.shared::cluster.b64 _, [%0];" ::"r"(rel0 + 8 * (K2_NS - 1)) : "memory");
        asm volatile("mbarrier.arrive.shared::cluster.b64 _, [%0];" ::"r"(rel1 + 8 * (K2_NS - 1)) : "memory");
      }
      const uint32_t bar_p = bar_empty2 + 8 * K2_NS;
      const int lc = (lane < 28) ? lane : 27;
      const size_t gbase = (size_t)(mt * 128 + warp * 16) * 448 + n * 224 + lc * 8;
      uint4 xv[16];
#pragma unroll
      for (int t = 0; t < 16; t++) xv[t] = ldg128_cg(x + gbase + t * 448);
      uint32_t gw[56];
#pragma unroll
      for (int i = 0; i < 56; i++) {
        const uint32_t f2 = pack_bf16(acc[2 * i], acc[2 * i + 1]);
        gw[i] = pack_bf16(silu_f(bf_lo(f2)), silu_f(bf_hi(f2)));
      }
      if (tid == 0) DBG(1, 62);
      mbar_wait(bar_p, 0, 12);
      const uint32_t tb = sb + tid * 16;
#pragma unroll
      for (int g = 0; g < 14; g++) {
        const uint4 a = lds128(tb + g * 4096), b = lds128(tb + (14 + g) * 4096), cc = lds128(tb + (28 + g) * 4096);
        gw[4 * g] = hmul2_bf16(pack_bf16(bf_lo(a.x) + bf_lo(b.x) + bf_lo(cc.x), bf_hi(a.x) + bf_hi(b.x) + bf_hi(cc.x)), gw[4 * g]);
        gw[4 * g + 1] = hmul2_bf16(pack_bf16(bf_lo(a.y) + bf_lo(b.y) + bf_lo(cc.y), bf_hi(a.y) + bf_hi(b.y) + bf_hi(cc.y)), gw[4 * g + 1]);
        gw[4 * g + 2] = hmul2_bf16(pack_bf16(bf_lo(a.z) + bf_lo(b.z) + bf_lo(cc.z), bf_hi(a.z) + bf_hi(b.z) + bf_hi(cc.z)), gw[4 * g + 2]);
        gw[4 * g + 3] = hmul2_bf16(pack_bf16(bf_lo(a.w) + bf_lo(b.w) + bf_lo(cc.w), bf_hi(a.w) + bf_hi(b.w) + bf_hi(cc.w)), gw[4 * g + 3]);
      }
      named_bar(1, 256);
      const uint32_t wbase = sb + warp * 16 * K2_PITCH;
      const int st_row = (lane & 7) + 8 * ((lane >> 3) & 1);
      const uint32_t sa = wbase + st_row * K2_PITCH + (lane >> 4) * 16;
#pragma unroll
      for (int g = 0; g < 28; g += 2) stmatrix_x4(sa + g * 16, gw[2 * g], gw[2 * g + 1], gw[2 * g + 2], gw[2 * g + 3]);
      __syncwarp();
      const uint32_t lp = wbase + lc * 16;
#pragma unroll
      for (int t = 0; t < 16; t++) {
        const uint4 tv = lds128(lp + t * K2_PITCH);
        uint4 o;
        o.x = hadd2_bf16(xv[t].x, tv.x); o.y = hadd2_bf16(xv[t].y, tv.y); o.z = hadd2_bf16(xv[t].z, tv.z); o.w = hadd2_bf16(xv[t].w, tv.w);
        if (lane < 28) stg128(out + gbase + t * 448, o);
      }
    }
    if (tid == 0) DBG(1, 63);
  }
  __syncwarp();
  cluster_arrive_relaxed();
  cluster_wait();
}

typedef CUresult (*EncFn)(CUtensorMap*, CUtensorMapDataType, cuuint32_t, void*, const cuuint64_t*, const cuuint64_t*, const cuuint32_t*,
                          const cuuint32_t*, CUtensorMapInterleave, CUtensorMapSwizzle, CUtensorMapL2promotion, CUtensorMapFloatOOBfill);

void make2d(EncFn enc, CUtensorMap* tm, const void* ptr, uint64_t cols, uint64_t rows, uint32_t bc, uint32_t br, bool swz = true) {
  cuuint64_t gd[2] = {cols, rows};
  cuuint64_t gs[1] = {cols * 2};
  cuuint32_t bd[2] = {bc, br};
  cuuint32_t es[2] = {1, 1};
  enc(tm, CU_TENSOR_MAP_DATA_TYPE_BFLOAT16, 2, const_cast<void*>(ptr), gd, gs, bd, es, CU_TENSOR_MAP_INTERLEAVE_NONE,
      swz ? CU_TENSOR_MAP_SWIZZLE_128B : CU_TENSOR_MAP_SWIZZLE_NONE, CU_TENSOR_MAP_L2_PROMOTION_L2_128B, CU_TENSOR_MAP_FLOAT_OOB_FILL_NONE);
}
void make3d_half(EncFn enc, CUtensorMap* tm, const void* ptr, uint64_t rows) {
  cuuint64_t gd[3] = {224, 2, rows};
  cuuint64_t gs[2] = {448, 896};
  cuuint32_t bd[3] = {64, 1, 64};
  cuuint32_t es[3] = {1, 1, 1};
  enc(tm, CU_TENSOR_MAP_DATA_TYPE_BFLOAT16, 3, const_cast<void*>(ptr), gd, gs, bd, es, CU_TENSOR_MAP_INTERLEAVE_NONE,
      CU_TENSOR_MAP_SWIZZLE_128B, CU_TENSOR_MAP_L2_PROMOTION_L2_128B, CU_TENSOR_MAP_FLOAT_OOB_FILL_NONE);
}

struct Maps { CUtensorMap wr, wi, wg, wu, cr, ci, h, ab, wd, hs, abs; };

}

extern "C" void kernel_launch(void* const* d_in, const int* in_sizes, int n_in, void* d_out, int out_size) {
  (void)in_sizes; (void)n_in; (void)out_size;
  static Maps maps;
  static const void* cached[9] = {nullptr};
  static bool attr_done = false;
  bool same = true;
  for (int i = 0; i < 9; i++) same = same && (cached[i] == d_in[i]);
  if (!same) {
    void* fn = nullptr;
    cudaDriverEntryPointQueryResult qr;
    cudaGetDriverEntryPoint("cuTensorMapEncodeTiled", &fn, cudaEnableDefault, &qr);
    EncFn enc = (EncFn)fn;
    void *p_ab = nullptr, *p_h = nullptr;
    cudaGetSymbolAddress(&p_ab, g_ab);
    cudaGetSymbolAddress(&p_h, g_h);
    make2d(enc, &maps.cr, d_in[1], 2048, 2048, 64, 128);
    make2d(enc, &maps.ci, d_in[2], 2048, 2048, 64, 128);
    make2d(enc, &maps.wr, d_in[3], 448, 448, 64, 56);
    make2d(enc, &maps.wi, d_in[4], 448, 448, 64, 56);
    make2d(enc, &maps.wg, d_in[6], 1792, 448, 64, 64);
    make2d(enc, &maps.wu, d_in[7], 1792, 448, 64, 64);
    make3d_half(enc, &maps.wd, d_in[8], 1792);
    make2d(enc, &maps.h, p_h, 1792, 2048, 64, 128);
    make3d_half(enc, &maps.ab, p_ab, 4096);
    make2d(enc, &maps.hs, p_h, 1792, 2048, 64, 64);
    make2d(enc, &maps.abs, p_ab, 448, 4096, 112, 64, false);
    for (int i = 0; i < 9; i++) cached[i] = d_in[i];
  }
  if (!attr_done) {
    cudaFuncSetAttribute(fused_kernel, cudaFuncAttributeMaxDynamicSharedMemorySize, K1_SMEM);
    attr_done = true;
  }
  PfPtrs pf;
  pf.wg = (const uint8_t*)d_in[6]; pf.wu = (const uint8_t*)d_in[7]; pf.wd = (const uint8_t*)d_in[8];
  fused_kernel<<<128, 384, K1_SMEM>>>(maps.wr, maps.wi, maps.wg, maps.wu, maps.hs, maps.abs, maps.cr, maps.ci, maps.h, maps.ab, maps.wd,
                                      (const __nv_bfloat16*)d_in[0], (__nv_bfloat16*)d_out, pf);
}
```

```cpp
#include <cuda_runtime.h>
#include <cuda_bf16.h>
#include <cuda.h>
#include <stdint.h>

namespace {

__device__ __align__(1024) __nv_bfloat16 g_ab[4096 * 448];
__device__ __align__(1024) __nv_bfloat16 g_h[2048 * 1792];
__device__ uint4 g_part[32 * 3 * 14 * 256];
__device__ __align__(1024) __nv_bfloat16 g_s[2048 * 448];
__device__ unsigned int g_epoch;
__device__ unsigned int g_ab_cnt;
__device__ unsigned int g_h_cnt[16 * 4];
__device__ unsigned int g_flags[64];

#define DBG(k, i) do {} while (0)
#define DBGC(k, i) do {} while (0)

#define TIMEOUT(code) __trap()
#define SPIN_LIMIT (1 << 22)
__device__ __forceinline__ uint32_t s2u(const void* p) { return (uint32_t)__cvta_generic_to_shared(p); }
__device__ __forceinline__ void mbar_init(uint32_t b, int c) { asm volatile("mbarrier.init.shared::cta.b64 [%0], %1;" ::"r"(b), "r"(c)); }
__device__ __forceinline__ void mbar_expect(uint32_t b, uint32_t bytes) {
  asm volatile("mbarrier.arrive.expect_tx.shared::cta.b64 _, [%0], %1;" ::"r"(b), "r"(bytes) : "memory");
}
__device__ __forceinline__ void mbar_wait(uint32_t b, uint32_t ph, int code = 1) {
  uint32_t done = 0;
  int it = 0;
  while (true) {
    asm volatile("{.reg .pred p; mbarrier.try_wait.parity.shared::cta.b64 p, [%1], %2; selp.u32 %0,1,0,p;}" : "=r"(done) : "r"(b), "r"(ph) : "memory");
    if (done) break;
    if (++it > SPIN_LIMIT) { TIMEOUT(code); break; }
  }
}
__device__ __forceinline__ void mbar_arrive_cluster(uint32_t b, uint32_t cta) {
  uint32_t r;
  asm volatile("mapa.shared::cluster.u32 %0, %1, %2;" : "=r"(r) : "r"(b), "r"(cta));
  asm volatile("mbarrier.arrive.shared::cluster.b64 _, [%0];" ::"r"(r) : "memory");
}
__device__ __forceinline__ void tma2d(uint32_t dst, const CUtensorMap* m, int c0, int c1, uint32_t bar) {
  asm volatile("cp.async.bulk.tensor.2d.shared::cluster.global.mbarrier::complete_tx::bytes [%0], [%1, {%3,%4}], [%2];" ::"r"(dst), "l"(m), "r"(bar), "r"(c0), "r"(c1) : "memory");
}
__device__ __forceinline__ void tma2d_mc(uint32_t dst, const CUtensorMap* m, int c0, int c1, uint32_t bar, uint16_t mask) {
  asm volatile("cp.async.bulk.tensor.2d.shared::cluster.global.mbarrier::complete_tx::bytes.multicast::cluster [%0], [%1, {%3,%4}], [%2], %5;" ::"r"(dst), "l"(m), "r"(bar), "r"(c0), "r"(c1), "h"(mask) : "memory");
}
__device__ __forceinline__ void tma3d_mc(uint32_t dst, const CUtensorMap* m, int c0, int c1, int c2, uint32_t bar, uint16_t mask) {
  asm volatile("cp.async.bulk.tensor.3d.shared::cluster.global.mbarrier::complete_tx::bytes.multicast::cluster [%0], [%1, {%3,%4,%5}], [%2], %6;" ::"r"(dst), "l"(m), "r"(bar), "r"(c0), "r"(c1), "r"(c2), "h"(mask) : "memory");
}
__device__ __forceinline__ void tma2d_store(const CUtensorMap* m, uint32_t src, int c0, int c1) {
  asm volatile("cp.async.bulk.tensor.2d.global.shared::cta.bulk_group [%0, {%2,%3}], [%1];" ::"l"(m), "r"(src), "r"(c0), "r"(c1) : "memory");
}
__device__ __forceinline__ void bulk_load(uint32_t dst, const void* src, uint32_t bytes, uint32_t bar) {
  asm volatile("cp.async.bulk.shared::cluster.global.mbarrier::complete_tx::bytes [%0], [%1], %2, [%3];" ::"r"(dst), "l"(src), "r"(bytes), "r"(bar) : "memory");
}
__device__ __forceinline__ void tma2d_prefetch(const CUtensorMap* m, int c0, int c1) {
  asm volatile("cp.async.bulk.prefetch.tensor.2d.L2.global [%0, {%1,%2}];" ::"l"(m), "r"(c0), "r"(c1) : "memory");
}
__device__ __forceinline__ void bulk_commit() { asm volatile("cp.async.bulk.commit_group;" ::: "memory"); }
__device__ __forceinline__ void bulk_wait_read0() { asm volatile("cp.async.bulk.wait_group.read 0;" ::: "memory"); }
__device__ __forceinline__ void bulk_wait0() { asm volatile("cp.async.bulk.wait_group 0;" ::: "memory"); }
__device__ __forceinline__ void fence_async_smem() { asm volatile("fence.proxy.async.shared::cta;" ::: "memory"); }
__device__ __forceinline__ void prefetch_tmap(const CUtensorMap* m) { asm volatile("prefetch.tensormap [%0];" ::"l"(m) : "memory"); }
__device__ __forceinline__ void l2_prefetch(const void* p, uint32_t bytes) {
  asm volatile("cp.async.bulk.prefetch.L2.global [%0], %1;" ::"l"(p), "r"(bytes) : "memory");
}
__device__ __forceinline__ void cluster_arrive_relaxed() { asm volatile("barrier.cluster.arrive.relaxed.aligned;" ::: "memory"); }
__device__ __forceinline__ void cluster_wait() { asm volatile("barrier.cluster.wait.aligned;" ::: "memory"); }
__device__ __forceinline__ void wg_fence() { __syncwarp(); asm volatile("wgmma.fence.sync.aligned;" ::: "memory"); }
__device__ __forceinline__ void wg_commit() { asm volatile("wgmma.commit_group.sync.aligned;" ::: "memory"); }
template <int N> __device__ __forceinline__ void wg_wait() { __syncwarp(); asm volatile("wgmma.wait_group.sync.aligned %0;" ::"n"(N) : "memory"); }
__device__ __forceinline__ void named_bar(int id, int n) { asm volatile("bar.sync %0, %1;" ::"r"(id), "r"(n) : "memory"); }
__device__ __forceinline__ void named_arrive(int id, int n) { asm volatile("bar.arrive %0, %1;" ::"r"(id), "r"(n) : "memory"); }
template <int N> __device__ __forceinline__ void reg_inc() { asm volatile("setmaxnreg.inc.sync.aligned.u32 %0;" ::"n"(N)); }
template <int N> __device__ __forceinline__ void reg_dec() { asm volatile("setmaxnreg.dec.sync.aligned.u32 %0;" ::"n"(N)); }
__device__ __forceinline__ void pdl_wait() { asm volatile("griddepcontrol.wait;" ::: "memory"); }
__device__ __forceinline__ void pdl_launch() { asm volatile("griddepcontrol.launch_dependents;" ::: "memory"); }

__device__ __forceinline__ uint32_t make_desc(uint32_t addr, uint32_t lbo, uint32_t  ) {
  return ((addr & 0x3FFFF) >> 4) | ((lbo >> 4) << 16);
}
__device__ __forceinline__ void stmatrix_x4(uint32_t addr, uint32_t r0, uint32_t r1, uint32_t r2, uint32_t r3) {
  asm volatile("stmatrix.sync.aligned.m8n8.x4.shared.b16 [%0], {%1,%2,%3,%4};" ::"r"(addr), "r"(r0), "r"(r1), "r"(r2), "r"(r3) : "memory");
}
__device__ __forceinline__ uint4 lds128(uint32_t a) {
  uint4 v;
  asm volatile("ld.shared.v4.u32 {%0,%1,%2,%3}, [%4];" : "=r"(v.x), "=r"(v.y), "=r"(v.z), "=r"(v.w) : "r"(a) : "memory");
  return v;
}
__device__ __forceinline__ void sts128(uint32_t a, uint4 v) {
  asm volatile("st.shared.v4.u32 [%0], {%1,%2,%3,%4};" ::"r"(a), "r"(v.x), "r"(v.y), "r"(v.z), "r"(v.w) : "memory");
}
__device__ __forceinline__ void stg128(void* p, uint4 v) {
  asm volatile("st.global.v4.u32 [%0], {%1,%2,%3,%4};" ::"l"(p), "r"(v.x), "r"(v.y), "r"(v.z), "r"(v.w) : "memory");
}
__device__ __forceinline__ void cp_async16(uint32_t dst, const void* src) {
  asm volatile("cp.async.cg.shared.global [%0], [%1], 16;" ::"r"(dst), "l"(src) : "memory");
}
__device__ __forceinline__ void cp_async8(uint32_t dst, const void* src) {
  asm volatile("cp.async.ca.shared.global [%0], [%1], 8;" ::"r"(dst), "l"(src) : "memory");
}
__device__ __forceinline__ uint2 lds64(uint32_t a) {
  uint2 v;
  asm volatile("ld.shared.v2.u32 {%0,%1}, [%2];" : "=r"(v.x), "=r"(v.y) : "r"(a) : "memory");
  return v;
}
__device__ __forceinline__ void cp_async_wait_all() { asm volatile("cp.async.wait_all;" ::: "memory"); }
__device__ __forceinline__ uint32_t pack_bf16(float lo, float hi) {
  uint32_t r;
  asm("cvt.rn.bf16x2.f32 %0, %1, %2;" : "=r"(r) : "f"(hi), "f"(lo));
  return r;
}
__device__ __forceinline__ uint32_t hmul2_bf16(uint32_t a, uint32_t b) {
  uint32_t r;
  asm("mul.rn.bf16x2 %0, %1, %2;" : "=r"(r) : "r"(a), "r"(b));
  return r;
}
__device__ __forceinline__ uint32_t hsub2_bf16(uint32_t a, uint32_t b) {
  uint32_t r;
  asm("sub.rn.bf16x2 %0, %1, %2;" : "=r"(r) : "r"(a), "r"(b));
  return r;
}
__device__ __forceinline__ uint32_t hadd2_bf16(uint32_t a, uint32_t b) {
  uint32_t r;
  asm("add.rn.bf16x2 %0, %1, %2;" : "=r"(r) : "r"(a), "r"(b));
  return r;
}
__device__ __forceinline__ uint32_t hfma2_bf16(uint32_t a, uint32_t b, uint32_t c) {
  uint32_t r;
  asm("fma.rn.bf16x2 %0, %1, %2, %3;" : "=r"(r) : "r"(a), "r"(b), "r"(c));
  return r;
}
__device__ __forceinline__ bool mbar_test(uint32_t b, uint32_t ph) {
  uint32_t done;
  asm volatile("{.reg .pred p; mbarrier.test_wait.parity.shared::cta.b64 p, [%1], %2; selp.u32 %0,1,0,p;}" : "=r"(done) : "r"(b), "r"(ph) : "memory");
  return __all_sync(0xffffffffu, done != 0);
}
__device__ __forceinline__ uint4 ldg128_cg(const void* p) {
  uint4 v;
  asm volatile("ld.global.cg.v4.u32 {%0,%1,%2,%3}, [%4];" : "=r"(v.x), "=r"(v.y), "=r"(v.z), "=r"(v.w) : "l"(p) : "memory");
  return v;
}
__device__ __forceinline__ float bf_lo(uint32_t w) { return __uint_as_float(w << 16); }
__device__ __forceinline__ float bf_hi(uint32_t w) { return __uint_as_float(w & 0xffff0000u); }
__device__ __forceinline__ float rbf(float x) { return __bfloat162float(__float2bfloat16_rn(x)); }
__device__ __forceinline__ float ex2f(float x) { float r; asm("ex2.approx.ftz.f32 %0, %1;" : "=f"(r) : "f"(x)); return r; }
__device__ __forceinline__ float rcpf(float x) { float r; asm("rcp.approx.ftz.f32 %0, %1;" : "=f"(r) : "f"(x)); return r; }
__device__ __forceinline__ float tanhf_hw(float x) { float r; asm("tanh.approx.f32 %0, %1;" : "=f"(r) : "f"(x)); return r; }
__device__ __forceinline__ float gelu_tanh(float x) {
  const float c1 = 0.7978845608028654f;
  const float c2 = c1 * 0.044715f;
  const float t = tanhf_hw(x * fmaf(c2, x * x, c1));
  const float hx = 0.5f * x;
  return fmaf(hx, t, hx);
}
__device__ __forceinline__ float silu_f(float x) {
  const float hx = 0.5f * x;
  return fmaf(hx, tanhf_hw(hx), hx);
}

__device__ __forceinline__ void wgmma_n128_tb(float (&d)[64], uint32_t da, uint32_t db, int scale_d) {
  asm volatile(
    "{\n.reg .pred p;\n.reg .b64 da, db;\nsetp.ne.b32 p, %66, 0;\n"
    "mov.b64 da, {%64, 0x40000040};\nmov.b64 db, {%65, 0x40000040};\n"
    "wgmma.mma_async.sync.aligned.m64n128k16.f32.bf16.bf16 {%0, %1, %2, %3, %4, %5, %6, %7, %8, %9, %10, %11, %12, %13, %14, %15, %16, %17, %18, %19, %20, %21, %22, %23, %24, %25, %26, %27, %28, %29, %30, %31, %32, %33, %34, %35, %36, %37, %38, %39, %40, %41, %42, %43, %44, %45, %46, %47, %48, %49, %50, %51, %52, %53, %54, %55, %56, %57, %58, %59, %60, %61, %62, %63}, da, db, p, 1, 1, 0, 1;\n}\n"
    : "+f"(d[0]), "+f"(d[1]), "+f"(d[2]), "+f"(d[3]), "+f"(d[4]), "+f"(d[5]), "+f"(d[6]), "+f"(d[7]), "+f"(d[8]), "+f"(d[9]), "+f"(d[10]), "+f"(d[11]), "+f"(d[12]), "+f"(d[13]), "+f"(d[14]), "+f"(d[15]), "+f"(d[16]), "+f"(d[17]), "+f"(d[18]), "+f"(d[19]), "+f"(d[20]), "+f"(d[21]), "+f"(d[22]), "+f"(d[23]), "+f"(d[24]), "+f"(d[25]), "+f"(d[26]), "+f"(d[27]), "+f"(d[28]), "+f"(d[29]), "+f"(d[30]), "+f"(d[31]), "+f"(d[32]), "+f"(d[33]), "+f"(d[34]), "+f"(d[35]), "+f"(d[36]), "+f"(d[37]), "+f"(d[38]), "+f"(d[39]), "+f"(d[40]), "+f"(d[41]), "+f"(d[42]), "+f"(d[43]), "+f"(d[44]), "+f"(d[45]), "+f"(d[46]), "+f"(d[47]), "+f"(d[48]), "+f"(d[49]), "+f"(d[50]), "+f"(d[51]), "+f"(d[52]), "+f"(d[53]), "+f"(d[54]), "+f"(d[55]), "+f"(d[56]), "+f"(d[57]), "+f"(d[58]), "+f"(d[59]), "+f"(d[60]), "+f"(d[61]), "+f"(d[62]), "+f"(d[63])
    : "r"(da), "r"(db), "r"(scale_d));
}
__device__ __forceinline__ void wgmma_n128_tb_p(float (&d)[64], uint32_t da, uint32_t db, int scale_d, int enable) {
  asm volatile(
    "{\n.reg .pred p;\n.reg .b64 da, db;\nsetp.ne.b32 p, %66, 0;\n.reg .pred q;\nsetp.ne.b32 q, %67, 0;\n"
    "mov.b64 da, {%64, 0x40000040};\nmov.b64 db, {%65, 0x40000040};\n"
    "@q wgmma.mma_async.sync.aligned.m64n128k16.f32.bf16.bf16 {%0, %1, %2, %3, %4, %5, %6, %7, %8, %9, %10, %11, %12, %13, %14, %15, %16, %17, %18, %19, %20, %21, %22, %23, %24, %25, %26, %27, %28, %29, %30, %31, %32, %33, %34, %35, %36, %37, %38, %39, %40, %41, %42, %43, %44, %45, %46, %47, %48, %49, %50, %51, %52, %53, %54, %55, %56, %57, %58, %59, %60, %61, %62, %63}, da, db, p, 1, 1, 0, 1;\n}\n"
    : "+f"(d[0]), "+f"(d[1]), "+f"(d[2]), "+f"(d[3]), "+f"(d[4]), "+f"(d[5]), "+f"(d[6]), "+f"(d[7]), "+f"(d[8]), "+f"(d[9]), "+f"(d[10]), "+f"(d[11]), "+f"(d[12]), "+f"(d[13]), "+f"(d[14]), "+f"(d[15]), "+f"(d[16]), "+f"(d[17]), "+f"(d[18]), "+f"(d[19]), "+f"(d[20]), "+f"(d[21]), "+f"(d[22]), "+f"(d[23]), "+f"(d[24]), "+f"(d[25]), "+f"(d[26]), "+f"(d[27]), "+f"(d[28]), "+f"(d[29]), "+f"(d[30]), "+f"(d[31]), "+f"(d[32]), "+f"(d[33]), "+f"(d[34]), "+f"(d[35]), "+f"(d[36]), "+f"(d[37]), "+f"(d[38]), "+f"(d[39]), "+f"(d[40]), "+f"(d[41]), "+f"(d[42]), "+f"(d[43]), "+f"(d[44]), "+f"(d[45]), "+f"(d[46]), "+f"(d[47]), "+f"(d[48]), "+f"(d[49]), "+f"(d[50]), "+f"(d[51]), "+f"(d[52]), "+f"(d[53]), "+f"(d[54]), "+f"(d[55]), "+f"(d[56]), "+f"(d[57]), "+f"(d[58]), "+f"(d[59]), "+f"(d[60]), "+f"(d[61]), "+f"(d[62]), "+f"(d[63])
    : "r"(da), "r"(db), "r"(scale_d), "r"(enable));
}
__device__ __forceinline__ void wgmma_n112(float (&d)[56], uint32_t da, uint32_t db, int scale_d) {
  asm volatile(
    "{\n.reg .pred p;\n.reg .b64 da, db;\nsetp.ne.b32 p, %58, 0;\n"
    "mov.b64 da, {%56, 0x40000040};\nmov.b64 db, {%57, 0x40000040};\n"
    "wgmma.mma_async.sync.aligned.m64n112k16.f32.bf16.bf16 {%0, %1, %2, %3, %4, %5, %6, %7, %8, %9, %10, %11, %12, %13, %14, %15, %16, %17, %18, %19, %20, %21, %22, %23, %24, %25, %26, %27, %28, %29, %30, %31, %32, %33, %34, %35, %36, %37, %38, %39, %40, %41, %42, %43, %44, %45, %46, %47, %48, %49, %50, %51, %52, %53, %54, %55}, da, db, p, 1, 1, 0, 0;\n}\n"
    : "+f"(d[0]), "+f"(d[1]), "+f"(d[2]), "+f"(d[3]), "+f"(d[4]), "+f"(d[5]), "+f"(d[6]), "+f"(d[7]), "+f"(d[8]), "+f"(d[9]), "+f"(d[10]), "+f"(d[11]), "+f"(d[12]), "+f"(d[13]), "+f"(d[14]), "+f"(d[15]), "+f"(d[16]), "+f"(d[17]), "+f"(d[18]), "+f"(d[19]), "+f"(d[20]), "+f"(d[21]), "+f"(d[22]), "+f"(d[23]), "+f"(d[24]), "+f"(d[25]), "+f"(d[26]), "+f"(d[27]), "+f"(d[28]), "+f"(d[29]), "+f"(d[30]), "+f"(d[31]), "+f"(d[32]), "+f"(d[33]), "+f"(d[34]), "+f"(d[35]), "+f"(d[36]), "+f"(d[37]), "+f"(d[38]), "+f"(d[39]), "+f"(d[40]), "+f"(d[41]), "+f"(d[42]), "+f"(d[43]), "+f"(d[44]), "+f"(d[45]), "+f"(d[46]), "+f"(d[47]), "+f"(d[48]), "+f"(d[49]), "+f"(d[50]), "+f"(d[51]), "+f"(d[52]), "+f"(d[53]), "+f"(d[54]), "+f"(d[55])
    : "r"(da), "r"(db), "r"(scale_d));
}
__device__ __forceinline__ void wgmma_n224_tb(float (&d)[112], uint32_t da, uint32_t db, int scale_d) {
  asm volatile(
    "{\n.reg .pred p;\n.reg .b64 da, db;\nsetp.ne.b32 p, %114, 0;\n"
    "mov.b64 da, {%112, 0x40000040};\nmov.b64 db, {%113, 0x40000040};\n"
    "wgmma.mma_async.sync.aligned.m64n224k16.f32.bf16.bf16 {%0, %1, %2, %3, %4, %5, %6, %7, %8, %9, %10, %11, %12, %13, %14, %15, %16, %17, %18, %19, %20, %21, %22, %23, %24, %25, %26, %27, %28, %29, %30, %31, %32, %33, %34, %35, %36, %37, %38, %39, %40, %41, %42, %43, %44, %45, %46, %47, %48, %49, %50, %51, %52, %53, %54, %55, %56, %57, %58, %59, %60, %61, %62, %63, %64, %65, %66, %67, %68, %69, %70, %71, %72, %73, %74, %75, %76, %77, %78, %79, %80, %81, %82, %83, %84, %85, %86, %87, %88, %89, %90, %91, %92, %93, %94, %95, %96, %97, %98, %99, %100, %101, %102, %103, %104, %105, %106, %107, %108, %109, %110, %111}, da, db, p, 1, 1, 0, 1;\n}\n"
    : "+f"(d[0]), "+f"(d[1]), "+f"(d[2]), "+f"(d[3]), "+f"(d[4]), "+f"(d[5]), "+f"(d[6]), "+f"(d[7]), "+f"(d[8]), "+f"(d[9]), "+f"(d[10]), "+f"(d[11]), "+f"(d[12]), "+f"(d[13]), "+f"(d[14]), "+f"(d[15]), "+f"(d[16]), "+f"(d[17]), "+f"(d[18]), "+f"(d[19]), "+f"(d[20]), "+f"(d[21]), "+f"(d[22]), "+f"(d[23]), "+f"(d[24]), "+f"(d[25]), "+f"(d[26]), "+f"(d[27]), "+f"(d[28]), "+f"(d[29]), "+f"(d[30]), "+f"(d[31]), "+f"(d[32]), "+f"(d[33]), "+f"(d[34]), "+f"(d[35]), "+f"(d[36]), "+f"(d[37]), "+f"(d[38]), "+f"(d[39]), "+f"(d[40]), "+f"(d[41]), "+f"(d[42]), "+f"(d[43]), "+f"(d[44]), "+f"(d[45]), "+f"(d[46]), "+f"(d[47]), "+f"(d[48]), "+f"(d[49]), "+f"(d[50]), "+f"(d[51]), "+f"(d[52]), "+f"(d[53]), "+f"(d[54]), "+f"(d[55]), "+f"(d[56]), "+f"(d[57]), "+f"(d[58]), "+f"(d[59]), "+f"(d[60]), "+f"(d[61]), "+f"(d[62]), "+f"(d[63]), "+f"(d[64]), "+f"(d[65]), "+f"(d[66]), "+f"(d[67]), "+f"(d[68]), "+f"(d[69]), "+f"(d[70]), "+f"(d[71]), "+f"(d[72]), "+f"(d[73]), "+f"(d[74]), "+f"(d[75]), "+f"(d[76]), "+f"(d[77]), "+f"(d[78]), "+f"(d[79]), "+f"(d[80]), "+f"(d[81]), "+f"(d[82]), "+f"(d[83]), "+f"(d[84]), "+f"(d[85]), "+f"(d[86]), "+f"(d[87]), "+f"(d[88]), "+f"(d[89]), "+f"(d[90]), "+f"(d[91]), "+f"(d[92]), "+f"(d[93]), "+f"(d[94]), "+f"(d[95]), "+f"(d[96]), "+f"(d[97]), "+f"(d[98]), "+f"(d[99]), "+f"(d[100]), "+f"(d[101]), "+f"(d[102]), "+f"(d[103]), "+f"(d[104]), "+f"(d[105]), "+f"(d[106]), "+f"(d[107]), "+f"(d[108]), "+f"(d[109]), "+f"(d[110]), "+f"(d[111])
    : "r"(da), "r"(db), "r"(scale_d));
}

constexpr int K1_NS = 5;
constexpr int K1_A_BYTES = 7 * 16384;
constexpr int K1_B_OFF = K1_A_BYTES;
constexpr int K1_STG_OFF = K1_B_OFF + K1_NS * 16384;
constexpr int K1_BAR_OFF = K1_STG_OFF + 8 * 4096;
constexpr int K1_SMEM = K1_BAR_OFF + 256 + 1024;

struct K1Ctx {
  uint32_t sb, bar_full, rel0, rel1;
  uint32_t dA, dBk, dBn;
  bool lane0;
  uint32_t bar_sfree;
  uint32_t sphase;
};
__device__ __forceinline__ void k1_release(const K1Ctx& c, int slot) {
  if (c.lane0) {
    asm volatile("mbarrier.arrive.shared::cluster.b64 _, [%0];" ::"r"(c.rel0 + 8 * slot) : "memory");
    asm volatile("mbarrier.arrive.shared::cluster.b64 _, [%0];" ::"r"(c.rel1 + 8 * slot) : "memory");
  }
}

__device__ __forceinline__ void k1_unit_ab(K1Ctx& c, int warp, int lane, int mt, int j) {
  const int wq = warp & 3;
  const int st_row = (lane & 7) + 8 * ((lane >> 3) & 1);
  const int st_chunk = lane >> 4;
  float acc[2][56];
  int slot = 0; uint32_t ph = 0;
#pragma unroll 1
  for (int kb = 0; kb < 7; kb++) {
    const int pslot = (slot == 0) ? K1_NS - 1 : slot - 1;
    mbar_wait(c.bar_full + 8 * slot, ph, 3);
    if (kb == 6) named_arrive(2, 256);
    if (kb == 0 && (threadIdx.x & 127) == 0) DBG(0, 4);
    if ((threadIdx.x & 127) == 0) DBGC(1, 46 + kb);
    wg_fence();
    const uint32_t da = c.dA + kb * 1024;
    const uint32_t db = c.dBk + slot * 1024;
#pragma unroll
    for (int k = 0; k < 4; k++) {
      wgmma_n112(acc[0], da + k * 2, db + k * 2, (kb | k) != 0);
      wgmma_n112(acc[1], da + 512 + k * 2, db + k * 2, (kb | k) != 0);
    }
    wg_commit();
    if (kb > 0) { wg_wait<1>(); k1_release(c, pslot); }
    if (++slot == K1_NS) { slot = 0; ph ^= 1; }
  }
  wg_wait<0>();
  k1_release(c, 6 % K1_NS);
  if ((threadIdx.x & 127) == 0) DBG(0, 5);
  const uint32_t sgn = (j < 4) ? 0u : 0x80008000u;
  const uint32_t sa = c.sb + K1_STG_OFF + (wq * 16 + st_row) * 224 + st_chunk * 16;
#pragma unroll
  for (int h = 0; h < 2; h++) {
    if (h == 1) { mbar_wait(c.bar_sfree, c.sphase, 6); c.sphase ^= 1; }
#pragma unroll
    for (int g = 0; g < 14; g += 2) {
      const float* a = &acc[h][4 * g];
      stmatrix_x4(sa + g * 16, pack_bf16(a[0], a[1]) ^ sgn, pack_bf16(a[2], a[3]) ^ sgn, pack_bf16(a[4], a[5]) ^ sgn, pack_bf16(a[6], a[7]) ^ sgn);
    }
    fence_async_smem();
    named_arrive(6, 160);
  }
}

__device__ __forceinline__ void k1_unit_gu(K1Ctx& c, int warp, int lane, int mt, int unit, int fb, int hsel, int full, int nunits) {
  const int wq = warp & 3;
  float acc[2][64];
  const uint32_t dA0 = c.dA + (full ? 0 : hsel * 512);
  int slot = (unit * 7) % K1_NS; uint32_t ph = ((unit * 7) / K1_NS) & 1;
  named_bar(2 + ((unit - 1) & 1), 256);
  if (full) {
#pragma unroll 1
    for (int kb = 0; kb < 7; kb++) {
      const int pslot = (slot == 0) ? K1_NS - 1 : slot - 1;
      mbar_wait(c.bar_full + 8 * slot, ph, 4);
      if (kb == 6 && unit + 1 < nunits) named_arrive(2 + (unit & 1), 256);
      if (kb == 0 && (threadIdx.x & 127) == 0) DBG(0, 4 + 3 * unit);
      wg_fence();
      const uint32_t da = dA0 + kb * 1024;
      const uint32_t db = c.dBn + slot * 1024;
#pragma unroll
      for (int k = 0; k < 4; k++) {
        wgmma_n128_tb(acc[0], da + k * 2, db + k * 128, (kb | k) != 0);
        wgmma_n128_tb(acc[1], da + 512 + k * 2, db + k * 128, (kb | k) != 0);
      }
      wg_commit();
      if (kb > 0) { wg_wait<1>(); k1_release(c, pslot); }
      if (++slot == K1_NS) { slot = 0; ph ^= 1; }
    }
  } else {
#pragma unroll 1
    for (int kb = 0; kb < 7; kb++) {
      const int pslot = (slot == 0) ? K1_NS - 1 : slot - 1;
      mbar_wait(c.bar_full + 8 * slot, ph, 5);
      if (kb == 0 && (threadIdx.x & 127) == 0) DBG(0, 4 + 3 * unit);
      wg_fence();
      const uint32_t da = dA0 + kb * 1024;
      const uint32_t db = c.dBn + slot * 1024;
#pragma unroll
      for (int k = 0; k < 4; k++) wgmma_n128_tb(acc[0], da + k * 2, db + k * 128, (kb | k) != 0);
      wg_commit();
      if (kb > 0) { wg_wait<1>(); k1_release(c, pslot); }
      if (++slot == K1_NS) { slot = 0; ph ^= 1; }
    }
  }
  wg_wait<0>();
  k1_release(c, (slot == 0) ? K1_NS - 1 : slot - 1);
  if (unit + 2 >= nunits && lane < 4) {
    asm volatile("mbarrier.arrive.shared::cluster.b64 _, [%0];" ::"r"(c.rel0 + 8 * (K1_NS + 4 + lane)) : "memory");
    asm volatile("mbarrier.arrive.shared::cluster.b64 _, [%0];" ::"r"(c.rel1 + 8 * (K1_NS + 4 + lane)) : "memory");
  }
  if ((threadIdx.x & 127) == 0) DBG(0, 5 + 3 * unit);
  const int st_row = (lane & 7) + 8 * ((lane >> 3) & 1);
  const int st_chunk = lane >> 4;
  const uint32_t sa = c.sb + K1_STG_OFF + (warp >> 2) * 16384 + (wq * 16 + st_row) * 128;
  if (unit >= 2) { mbar_wait(c.bar_sfree, c.sphase, 7); c.sphase ^= 1; }
#pragma unroll
  for (int h = 0; h < 2; h++) {
    if (h == 1 && !full) break;
#pragma unroll
    for (int g = 0; g < 8; g += 2) {
      uint32_t pk[4];
#pragma unroll
      for (int e = 0; e < 4; e++) {
        const int i = 4 * g + 2 * e;
        const uint32_t g2 = pack_bf16(acc[h][i], acc[h][i + 1]);
        const uint32_t u2 = pack_bf16(acc[h][32 + i], acc[h][32 + i + 1]);
        pk[e] = hmul2_bf16(pack_bf16(gelu_tanh(bf_lo(g2)), gelu_tanh(bf_hi(g2))), u2);
      }
      stmatrix_x4(sa + h * 8192 + (((g + st_chunk) ^ (st_row & 7)) * 16), pk[0], pk[1], pk[2], pk[3]);
    }
  }
  fence_async_smem();
  named_arrive(6 + (warp >> 2), 160);
}

constexpr int K2_NS = 4;
constexpr int K2_STAGE = 16384 + 32768;
constexpr int K2_PITCH = 464;

__device__ __forceinline__ void spin_flag(const unsigned int* flag, unsigned int target) {
  int it = 0;
  while (true) {
    unsigned int v;
    asm volatile("ld.acquire.gpu.global.u32 %0, [%1];" : "=r"(v) : "l"(flag) : "memory");
    if ((int)(v - target) >= 0) break;
    if (++it > SPIN_LIMIT) { TIMEOUT(20); break; }
  }
}

__device__ __forceinline__ void ln_rows(const __nv_bfloat16* __restrict__ xt, uint32_t sb, int lw, int lane) {
  const int c = lane & 7;
  const int r0 = lw * 4 + (lane >> 3);
  const uint4* src = reinterpret_cast<const uint4*>(xt + (size_t)r0 * 448) + c;
  uint4 nx[7];
#pragma unroll
  for (int b = 0; b < 7; b++)
    asm volatile("ld.global.nc.v4.u32 {%0,%1,%2,%3}, [%4];" : "=r"(nx[b].x), "=r"(nx[b].y), "=r"(nx[b].z), "=r"(nx[b].w) : "l"(src + b * 8) : "memory");
  const int npass = (lw < 10) ? 3 : 2;
  if (c < 7) {
    asm volatile("prefetch.global.L2 [%0];" ::"l"(src + 44 * 56 + c * 7) : "memory");
    if (npass == 3) asm volatile("prefetch.global.L2 [%0];" ::"l"(src + 88 * 56 + c * 7) : "memory");
  }
#pragma unroll 1
  for (int pass = 0; pass < npass; pass++) {
    uint4 v[7];
#pragma unroll
    for (int b = 0; b < 7; b++) v[b] = nx[b];
    if (pass + 1 < npass) {
      const uint4* s2 = src + (pass + 1) * 44 * 56;
#pragma unroll
      for (int b = 0; b < 7; b++)
        asm volatile("ld.global.nc.v4.u32 {%0,%1,%2,%3}, [%4];" : "=r"(nx[b].x), "=r"(nx[b].y), "=r"(nx[b].z), "=r"(nx[b].w) : "l"(s2 + b * 8) : "memory");
    }
        float s0 = 0.f, s1 = 0.f, s2v = 0.f, s3 = 0.f;
#pragma unroll
        for (int b = 0; b < 7; b++) {
          s0 += bf_lo(v[b].x) + bf_hi(v[b].x); s1 += bf_lo(v[b].y) + bf_hi(v[b].y);
          s2v += bf_lo(v[b].z) + bf_hi(v[b].z); s3 += bf_lo(v[b].w) + bf_hi(v[b].w);
        }
        float m = (s0 + s1) + (s2v + s3);
        m += __shfl_xor_sync(0xffffffffu, m, 1);
        m += __shfl_xor_sync(0xffffffffu, m, 2);
        m += __shfl_xor_sync(0xffffffffu, m, 4);
        m *= (1.0f / 448.0f);
        float q0 = 0.f, q1 = 0.f, q2 = 0.f, q3 = 0.f;
#pragma unroll
        for (int b = 0; b < 7; b++) {
          float d;
          d = bf_lo(v[b].x) - m; q0 = fmaf(d, d, q0); d = bf_hi(v[b].x) - m; q1 = fmaf(d, d, q1);
          d = bf_lo(v[b].y) - m; q2 = fmaf(d, d, q2); d = bf_hi(v[b].y) - m; q3 = fmaf(d, d, q3);
          d = bf_lo(v[b].z) - m; q0 = fmaf(d, d, q0); d = bf_hi(v[b].z) - m; q1 = fmaf(d, d, q1);
          d = bf_lo(v[b].w) - m; q2 = fmaf(d, d, q2); d = bf_hi(v[b].w) - m; q3 = fmaf(d, d, q3);
        }
        float q = (q0 + q1) + (q2 + q3);
        q += __shfl_xor_sync(0xffffffffu, q, 1);
        q += __shfl_xor_sync(0xffffffffu, q, 2);
        q += __shfl_xor_sync(0xffffffffu, q, 4);
        const float var_b = rbf(q * (1.0f / 448.0f));
        const float den = rbf(sqrtf(rbf(var_b + 1e-5f)));
        const float ri = 1.0f / den;
        const float rih = rbf(ri);
        const uint32_t rhi2 = pack_bf16(rih, rih), rlo2 = pack_bf16(ri - rih, ri - rih);
        const uint32_t m2 = pack_bf16(m, m);
        const int r = r0 + pass * 44;
        const uint32_t a0 = sb + r * 128 + ((c ^ (r & 7)) * 16);
#pragma unroll
        for (int b = 0; b < 7; b++) {
          uint32_t w4[4] = {v[b].x, v[b].y, v[b].z, v[b].w};
#pragma unroll
          for (int qq = 0; qq < 4; qq++) {
            const uint32_t dw = hsub2_bf16(w4[qq], m2);
            w4[qq] = hfma2_bf16(dw, rhi2, hmul2_bf16(dw, rlo2));
          }
          sts128(a0 + b * 16384, make_uint4(w4[0], w4[1], w4[2], w4[3]));
        }
  }
}

struct PfPtrs { const uint8_t* wg; const uint8_t* wu; const uint8_t* wd; };

__global__ void __cluster_dims__(2, 1, 1) __launch_bounds__(384, 1)
fused_kernel(const __grid_constant__ CUtensorMap tm_wr, const __grid_constant__ CUtensorMap tm_wi,
             const __grid_constant__ CUtensorMap tm_wg, const __grid_constant__ CUtensorMap tm_wu,
             const __grid_constant__ CUtensorMap tm_hs, const __grid_constant__ CUtensorMap tm_abs,
             const __grid_constant__ CUtensorMap tm_cr, const __grid_constant__ CUtensorMap tm_ci, const __grid_constant__ CUtensorMap tm_h,
             const __grid_constant__ CUtensorMap tm_ab, const __grid_constant__ CUtensorMap tm_wd,
             const __nv_bfloat16* __restrict__ x, __nv_bfloat16* __restrict__ out, const PfPtrs pf) {
  extern __shared__ uint8_t smem_raw[];
  const uint32_t sb = (s2u(smem_raw) + 1023) & ~1023u;
  const int tid = threadIdx.x, warp = tid >> 5, lane = tid & 31;
  uint32_t rank;
  asm volatile("mov.u32 %0, %%cluster_ctarank;" : "=r"(rank));
  const int cid = blockIdx.x >> 1;
  const int p = cid >> 3, j = cid & 7;
  const int mt = 2 * p + (int)rank;
  const uint32_t bar_full = sb + K1_BAR_OFF;
  const uint32_t bar_empty = bar_full + 8 * K1_NS;
  const uint32_t bar_full2 = bar_empty + 8 * K1_NS;
  const uint32_t bar_empty2 = bar_full2 + 8 * K2_NS;
  const int fb_base = 7 * (j >> 1);
  const int fb0 = fb_base + ((j & 1) ? 4 : 0);
  const int fbh = fb_base + 3;
  const int q = j & 3, n = j >> 2;
  const int tile = mt * 2 + n;
  const int nkb = (q < 2) ? 22 : (q == 3 ? 28 : 20);
  const int nunits = (q == 3) ? 4 : 5;
  const int u4full = (q == 2);

  if (tid == 0) DBG(0, 0);
  if (tid == 256) {
    for (int i = 0; i < K1_NS; i++) { mbar_init(bar_full + 8 * i, 1); mbar_init(bar_empty + 8 * i, 8); }
    for (int i = 0; i < K2_NS; i++) { mbar_init(bar_full2 + 8 * i, 1); mbar_init(bar_empty2 + 8 * i, 16); }
    mbar_init(bar_empty2 + 8 * K2_NS, 1);
    mbar_init(bar_empty2 + 8 * K2_NS + 8, 1);
    mbar_init(bar_empty2 + 8 * K2_NS + 16, 1);
    asm volatile("fence.mbarrier_init.release.cluster;" ::: "memory");
    prefetch_tmap((j < 4) ? &tm_wr : &tm_wi);
    prefetch_tmap(rank ? &tm_wu : &tm_wg);
    prefetch_tmap(&tm_abs);
    prefetch_tmap(&tm_hs);
  }
  __syncwarp();
  cluster_arrive_relaxed();

  if (warp != 8) {
    ln_rows(x + (size_t)mt * 128 * 448, sb, warp < 8 ? warp : warp - 1, lane);
    asm volatile("fence.proxy.async.shared::cta;" ::: "memory");
  }
  if (warp >= 8) {
    if (warp > 8) named_arrive(8, 352);
    reg_dec<40>();
    cluster_wait();
    if (tid == 256) {
      const unsigned int epoch = *reinterpret_cast<volatile unsigned int*>(&g_epoch);
      {
        const CUtensorMap* tw = (j < 4) ? &tm_wr : &tm_wi;
        const CUtensorMap* tgu = rank ? &tm_wu : &tm_wg;
        int slot = 0; uint32_t ph = 0;
        int kb = 0, unit = 0;
#pragma unroll 1
        for (int s = 0; s < 7 * nunits; s++) {
          if (s >= K1_NS) mbar_wait(bar_empty + 8 * slot, ph ^ 1, 2);
          const uint32_t dst = sb + K1_B_OFF + slot * 16384;
          if (unit == 0) {
            mbar_expect(bar_full + 8 * slot, 14336);
            tma2d_mc(dst + rank * 7168, tw, kb * 64, (j & 3) * 112 + rank * 56, bar_full + 8 * slot, 3);
          } else {
            const int fb = (unit == 4) ? fbh : (fb0 + unit - 1);
            mbar_expect(bar_full + 8 * slot, 16384);
            tma2d_mc(dst + rank * 8192, tgu, fb * 64, kb * 64, bar_full + 8 * slot, 3);
          }
          if (s == 21) {
            l2_prefetch(pf.wd + blockIdx.x * 12544, 12544);
            if (q < 3) {
              const int g0 = q * 22;
#pragma unroll 1
              for (int i = 0; i < 6; i++) tma2d_prefetch((g0 + i < 32) ? &tm_cr : &tm_ci, ((g0 + i) & 31) * 64, mt * 128);
            }
          }
          if (++kb == 7) { kb = 0; unit++; }
          if (++slot == K1_NS) { slot = 0; ph ^= 1; }
        }
      }
      {
        const int g0 = (q == 0) ? 0 : (q == 1 ? 22 : (q == 2 ? 44 : 64));
        const CUtensorMap* tb = (q < 3) ? &tm_ab : &tm_wd;
        prefetch_tmap(tb); prefetch_tmap((q < 3) ? ((g0 < 32) ? &tm_cr : &tm_ci) : &tm_h);
        const int kb0 = (q < 3) ? g0 : 0;
        if (q < 3) { spin_flag(&g_ab_cnt, 128u * (epoch + 1)); asm volatile("fence.proxy.async;" ::: "memory"); }
        DBG(1, 31);
        int slot = 0; uint32_t ph = 0;
#pragma unroll 1
        for (int s = 0; s < nkb; s++) {
          int kblk = kb0 + s;
          const CUtensorMap* ta = (kblk < 32) ? &tm_cr : &tm_ci;
          if (q == 3) {
            if ((s & 7) == 0) { spin_flag(&g_h_cnt[mt * 4 + (s >> 3)], ((s < 24) ? 8u : 6u) * (epoch + 1)); asm volatile("fence.proxy.async;" ::: "memory"); }
            const int i = s & 7;
            kblk = (s < 24) ? (7 * (i >> 1) + ((i & 1) ? 4 : 0) + (s >> 3)) : (7 * i + 3);
            ta = &tm_h;
          }
          mbar_wait(bar_empty2 + 8 * slot, ph, 10);
          const uint32_t dst = sb + slot * K2_STAGE;
          const uint32_t fb = bar_full2 + 8 * slot;
          mbar_expect(fb, K2_STAGE);
          tma2d(dst, ta, (kblk & 31) * 64, mt * 128, fb);
          tma3d_mc(dst + 16384 + (2 * rank) * 8192, tb, (2 * rank) * 64, n, kblk * 64, fb, 3);
          tma3d_mc(dst + 16384 + (2 * rank + 1) * 8192, tb, (2 * rank + 1) * 64, n, kblk * 64, fb, 3);
          if (++slot == K2_NS) { slot = 0; ph ^= 1; }
        }
        if (q == 3) {
          const uint32_t bar_p = bar_empty2 + 8 * K2_NS;
          spin_flag(&g_flags[tile], 3u * (epoch + 1));
          asm volatile("fence.proxy.async;" ::: "memory");
          mbar_expect(bar_p, 3 * 57344);
          const uint4* pp = g_part + (size_t)tile * (3 * 14 * 256);
#pragma unroll 1
          for (int c = 0; c < 7; c++) {
            if ((c & 1) == 0) mbar_wait(bar_empty2 + 8 * (c >> 1), ph, 13);
            bulk_load(sb + c * 24576, pp + c * 1536, 24576, bar_p);
          }
          DBG(1, 30);
        }
      }
    } else if (warp == 9 || warp == 10) {
      const int hw = warp - 9;
      const uint32_t stg = sb + K1_STG_OFF + hw * 16384;
      const uint32_t bar_sfree = bar_empty2 + 8 * K2_NS + 8 + 8 * hw;
      if (lane == 0) {
        const int b = blockIdx.x;
        l2_prefetch((hw ? pf.wu : pf.wg) + b * 12544, 12544);
      }
#pragma unroll 1
      for (int job = 0; job < (hw ? 2 : (nunits == 5 ? 4 : 3)); job++) {
        named_bar(6 + hw, 160);
        if (lane == 0) {
          const int unit = hw ? (1 + 2 * job) : (job < 2 ? 0 : 2 * job - 2);
          if (unit == 0) {
            tma2d_store(&tm_abs, stg, (j & 3) * 112, (j < 4 ? 0 : 2048) + mt * 128 + job * 64);
          } else {
            const int fb = (unit == 4) ? fbh : fb0 + unit - 1;
            const bool fullu = (unit < 4) || u4full;
            tma2d_store(&tm_hs, stg, fb * 64, mt * 128 + (fullu ? 0 : (j & 1) * 64));
            if (fullu) tma2d_store(&tm_hs, stg + 8192, fb * 64, mt * 128 + 64);
          }
          bulk_commit();
          bulk_wait_read0();
          asm volatile("mbarrier.arrive.shared::cta.b64 _, [%0];" ::"r"(bar_sfree) : "memory");
          if (unit != 0 || job == 1) {
            bulk_wait0();
            asm volatile("fence.proxy.async;" ::: "memory");
            __threadfence();
            if (unit == 0) {
              const unsigned int old = atomicAdd(&g_ab_cnt, 1u);
              if ((old & 127u) == 127u) *reinterpret_cast<volatile unsigned int*>(&g_epoch) = (old >> 7) + 1;
            } else {
              atomicAdd(&g_h_cnt[mt * 4 + unit - 1], 1u);
            }
          }
        }
        __syncwarp();
      }
    }
  } else {
    const int wg = warp >> 2;
    named_bar(8, 352);
    reg_inc<232>();
    cluster_wait();
    if (tid == 0) DBG(0, 3);

    uint32_t rel0, rel1;
    asm volatile("mapa.shared::cluster.u32 %0, %1, %2;" : "=r"(rel0) : "r"(bar_empty2), "r"(0));
    asm volatile("mapa.shared::cluster.u32 %0, %1, %2;" : "=r"(rel1) : "r"(bar_empty2), "r"(1));
    {
      K1Ctx c;
      c.sb = sb; c.bar_full = bar_full; c.lane0 = (lane == 0);
      c.rel0 = rel0 - 8 * (K1_NS + K2_NS); c.rel1 = rel1 - 8 * (K1_NS + K2_NS);
      c.bar_sfree = bar_empty2 + 8 * K2_NS + 8 + 8 * wg; c.sphase = 0;
      c.dA = make_desc(sb, 16, 1024);
      c.dBk = make_desc(sb + K1_B_OFF, 16, 1024);
      c.dBn = make_desc(sb + K1_B_OFF, 8192, 1024);
      if (wg == 0) {
        k1_unit_ab(c, warp, lane, mt, j);
        if (tid == 0) DBG(0, 6);
      }
#pragma unroll 1
      for (int unit = 2 - wg; unit < nunits; unit += 2) {
        k1_unit_gu(c, warp, lane, mt, unit, (unit == 4) ? fbh : fb0 + unit - 1, j & 1, (unit < 4) || u4full, nunits);
        if ((tid & 127) == 0) DBG(0, 6 + 3 * unit);
      }
    }

    float acc[112];
    const uint32_t dA0 = make_desc(sb + wg * 8192, 16, 1024);
    const uint32_t dB0 = make_desc(sb + 16384, 8192, 1024);
    int slot = 0; uint32_t ph = 0;
#pragma unroll 1
    for (int s = 0; s < nkb; s++) {
      mbar_wait(bar_full2 + 8 * slot, ph, 11);
      if (tid == 0) DBG(1, 1 + s);
      wg_fence();
      const uint32_t da = dA0 + slot * (K2_STAGE / 16);
      const uint32_t db = dB0 + slot * (K2_STAGE / 16);
#pragma unroll
      for (int k = 0; k < 4; k++) wgmma_n224_tb(acc, da + k * 2, db + k * 128, (s | k) != 0);
      wg_commit();
      if (s > 0) {
        wg_wait<1>();
        const int ps = (slot == 0) ? K2_NS - 1 : slot - 1;
        if (lane == 0) {
          asm volatile("mbarrier.arrive.shared::cluster.b64 _, [%0];" ::"r"(rel0 + 8 * ps) : "memory");
          asm volatile("mbarrier.arrive.shared::cluster.b64 _, [%0];" ::"r"(rel1 + 8 * ps) : "memory");
        }
      }
      if (++slot == K2_NS) { slot = 0; ph ^= 1; }
    }
    wg_wait<0>();
    if (tid == 0) DBG(1, 29);
    if (q < 3) {
      uint4* part = g_part + (size_t)(tile * 3 + q) * (14 * 256) + tid;
#pragma unroll
      for (int g = 0; g < 14; g++)
        part[g * 256] = make_uint4(pack_bf16(acc[8 * g], acc[8 * g + 1]), pack_bf16(acc[8 * g + 2], acc[8 * g + 3]),
                                   pack_bf16(acc[8 * g + 4], acc[8 * g + 5]), pack_bf16(acc[8 * g + 6], acc[8 * g + 7]));
      __threadfence();
      asm volatile("fence.proxy.async;" ::: "memory");
      named_bar(1, 256);
      if (tid == 0) atomicAdd(&g_flags[tile], 1u);
    } else {
      if (lane == 0) {
        asm volatile("mbarrier.arrive.shared::cluster.b64 _, [%0];" ::"r"(rel0 + 8 * (K2_NS - 1)) : "memory");
        asm volatile("mbarrier.arrive.shared::cluster.b64 _, [%0];" ::"r"(rel1 + 8 * (K2_NS - 1)) : "memory");
      }
      const uint32_t bar_p = bar_empty2 + 8 * K2_NS;
      const int lc = (lane < 28) ? lane : 27;
      const size_t gbase = (size_t)(mt * 128 + warp * 16) * 448 + n * 224 + lc * 8;
      uint4 xv[16];
#pragma unroll
      for (int t = 0; t < 16; t++) xv[t] = ldg128_cg(x + gbase + t * 448);
      uint32_t gw[56];
#pragma unroll
      for (int i = 0; i < 56; i++) {
        const uint32_t f2 = pack_bf16(acc[2 * i], acc[2 * i + 1]);
        gw[i] = pack_bf16(silu_f(bf_lo(f2)), silu_f(bf_hi(f2)));
      }
      if (tid == 0) DBG(1, 62);
      mbar_wait(bar_p, 0, 12);
      const uint32_t tb = sb + tid * 16;
#pragma unroll
      for (int g = 0; g < 14; g++) {
        const uint4 a = lds128(tb + g * 4096), b = lds128(tb + (14 + g) * 4096), cc = lds128(tb + (28 + g) * 4096);
        gw[4 * g] = hmul2_bf16(pack_bf16(bf_lo(a.x) + bf_lo(b.x) + bf_lo(cc.x), bf_hi(a.x) + bf_hi(b.x) + bf_hi(cc.x)), gw[4 * g]);
        gw[4 * g + 1] = hmul2_bf16(pack_bf16(bf_lo(a.y) + bf_lo(b.y) + bf_lo(cc.y), bf_hi(a.y) + bf_hi(b.y) + bf_hi(cc.y)), gw[4 * g + 1]);
        gw[4 * g + 2] = hmul2_bf16(pack_bf16(bf_lo(a.z) + bf_lo(b.z) + bf_lo(cc.z), bf_hi(a.z) + bf_hi(b.z) + bf_hi(cc.z)), gw[4 * g + 2]);
        gw[4 * g + 3] = hmul2_bf16(pack_bf16(bf_lo(a.w) + bf_lo(b.w) + bf_lo(cc.w), bf_hi(a.w) + bf_hi(b.w) + bf_hi(cc.w)), gw[4 * g + 3]);
      }
      named_bar(1, 256);
      const uint32_t wbase = sb + warp * 16 * K2_PITCH;
      const int st_row = (lane & 7) + 8 * ((lane >> 3) & 1);
      const uint32_t sa = wbase + st_row * K2_PITCH + (lane >> 4) * 16;
#pragma unroll
      for (int g = 0; g < 28; g += 2) stmatrix_x4(sa + g * 16, gw[2 * g], gw[2 * g + 1], gw[2 * g + 2], gw[2 * g + 3]);
      __syncwarp();
      const uint32_t lp = wbase + lc * 16;
#pragma unroll
      for (int t = 0; t < 16; t++) {
        const uint4 tv = lds128(lp + t * K2_PITCH);
        uint4 o;
        o.x = hadd2_bf16(xv[t].x, tv.x); o.y = hadd2_bf16(xv[t].y, tv.y); o.z = hadd2_bf16(xv[t].z, tv.z); o.w = hadd2_bf16(xv[t].w, tv.w);
        if (lane < 28) stg128(out + gbase + t * 448, o);
      }
    }
    if (tid == 0) DBG(1, 63);
  }
  __syncwarp();
  cluster_arrive_relaxed();
  cluster_wait();
}

typedef CUresult (*EncFn)(CUtensorMap*, CUtensorMapDataType, cuuint32_t, void*, const cuuint64_t*, const cuuint64_t*, const cuuint32_t*,
                          const cuuint32_t*, CUtensorMapInterleave, CUtensorMapSwizzle, CUtensorMapL2promotion, CUtensorMapFloatOOBfill);

void make2d(EncFn enc, CUtensorMap* tm, const void* ptr, uint64_t cols, uint64_t rows, uint32_t bc, uint32_t br, bool swz = true) {
  cuuint64_t gd[2] = {cols, rows};
  cuuint64_t gs[1] = {cols * 2};
  cuuint32_t bd[2] = {bc, br};
  cuuint32_t es[2] = {1, 1};
  enc(tm, CU_TENSOR_MAP_DATA_TYPE_BFLOAT16, 2, const_cast<void*>(ptr), gd, gs, bd, es, CU_TENSOR_MAP_INTERLEAVE_NONE,
      swz ? CU_TENSOR_MAP_SWIZZLE_128B : CU_TENSOR_MAP_SWIZZLE_NONE, CU_TENSOR_MAP_L2_PROMOTION_L2_128B, CU_TENSOR_MAP_FLOAT_OOB_FILL_NONE);
}
void make3d_half(EncFn enc, CUtensorMap* tm, const void* ptr, uint64_t rows) {
  cuuint64_t gd[3] = {224, 2, rows};
  cuuint64_t gs[2] = {448, 896};
  cuuint32_t bd[3] = {64, 1, 64};
  cuuint32_t es[3] = {1, 1, 1};
  enc(tm, CU_TENSOR_MAP_DATA_TYPE_BFLOAT16, 3, const_cast<void*>(ptr), gd, gs, bd, es, CU_TENSOR_MAP_INTERLEAVE_NONE,
      CU_TENSOR_MAP_SWIZZLE_128B, CU_TENSOR_MAP_L2_PROMOTION_L2_128B, CU_TENSOR_MAP_FLOAT_OOB_FILL_NONE);
}

struct Maps { CUtensorMap wr, wi, wg, wu, cr, ci, h, ab, wd, hs, abs; };

}

extern "C" void kernel_launch(void* const* d_in, const int* in_sizes, int n_in, void* d_out, int out_size) {
  (void)in_sizes; (void)n_in; (void)out_size;
  static Maps maps;
  static const void* cached[9] = {nullptr};
  static bool attr_done = false;
  bool same = true;
  for (int i = 0; i < 9; i++) same = same && (cached[i] == d_in[i]);
  if (!same) {
    void* fn = nullptr;
    cudaDriverEntryPointQueryResult qr;
    cudaGetDriverEntryPoint("cuTensorMapEncodeTiled", &fn, cudaEnableDefault, &qr);
    EncFn enc = (EncFn)fn;
    void *p_ab = nullptr, *p_h = nullptr;
    cudaGetSymbolAddress(&p_ab, g_ab);
    cudaGetSymbolAddress(&p_h, g_h);
    make2d(enc, &maps.cr, d_in[1], 2048, 2048, 64, 128);
    make2d(enc, &maps.ci, d_in[2], 2048, 2048, 64, 128);
    make2d(enc, &maps.wr, d_in[3], 448, 448, 64, 56);
    make2d(enc, &maps.wi, d_in[4], 448, 448, 64, 56);
    make2d(enc, &maps.wg, d_in[6], 1792, 448, 64, 64);
    make2d(enc, &maps.wu, d_in[7], 1792, 448, 64, 64);
    make3d_half(enc, &maps.wd, d_in[8], 1792);
    make2d(enc, &maps.h, p_h, 1792, 2048, 64, 128);
    make3d_half(enc, &maps.ab, p_ab, 4096);
    make2d(enc, &maps.hs, p_h, 1792, 2048, 64, 64);
    make2d(enc, &maps.abs, p_ab, 448, 4096, 112, 64, false);
    for (int i = 0; i < 9; i++) cached[i] = d_in[i];
  }
  if (!attr_done) {
    cudaFuncSetAttribute(fused_kernel, cudaFuncAttributeMaxDynamicSharedMemorySize, K1_SMEM);
    attr_done = true;
  }
  PfPtrs pf;
  pf.wg = (const uint8_t*)d_in[6]; pf.wu = (const uint8_t*)d_in[7]; pf.wd = (const uint8_t*)d_in[8];
  fused_kernel<<<128, 384, K1_SMEM>>>(maps.wr, maps.wi, maps.wg, maps.wu, maps.hs, maps.abs, maps.cr, maps.ci, maps.h, maps.ab, maps.wd,
                                      (const __nv_bfloat16*)d_in[0], (__nv_bfloat16*)d_out, pf);
}
```

```cpp
#include <cuda_runtime.h>
#include <cuda_bf16.h>
#include <cuda.h>
#include <stdint.h>

namespace {

__device__ __align__(1024) __nv_bfloat16 g_ab[4096 * 448];
__device__ __align__(1024) __nv_bfloat16 g_h[2048 * 1792];
__device__ uint4 g_part[32 * 4 * 14 * 256];
__device__ __align__(1024) __nv_bfloat16 g_s[2048 * 448];
__device__ unsigned int g_epoch;
__device__ unsigned int g_ab_cnt;
__device__ unsigned int g_h_cnt[16 * 4];
__device__ unsigned int g_flags[64];

#define DBG(k, i) do {} while (0)
#define DBGC(k, i) do {} while (0)

#define TIMEOUT(code) __trap()
#define SPIN_LIMIT (1 << 22)
__device__ __forceinline__ uint32_t s2u(const void* p) { return (uint32_t)__cvta_generic_to_shared(p); }
__device__ __forceinline__ void mbar_init(uint32_t b, int c) { asm volatile("mbarrier.init.shared::cta.b64 [%0], %1;" ::"r"(b), "r"(c)); }
__device__ __forceinline__ void mbar_expect(uint32_t b, uint32_t bytes) {
  asm volatile("mbarrier.arrive.expect_tx.shared::cta.b64 _, [%0], %1;" ::"r"(b), "r"(bytes) : "memory");
}
__device__ __forceinline__ void mbar_wait(uint32_t b, uint32_t ph, int code = 1) {
  uint32_t done = 0;
  int it = 0;
  while (true) {
    asm volatile("{.reg .pred p; mbarrier.try_wait.parity.shared::cta.b64 p, [%1], %2; selp.u32 %0,1,0,p;}" : "=r"(done) : "r"(b), "r"(ph) : "memory");
    if (done) break;
    if (++it > SPIN_LIMIT) { TIMEOUT(code); break; }
  }
}
__device__ __forceinline__ void mbar_arrive_cluster(uint32_t b, uint32_t cta) {
  uint32_t r;
  asm volatile("mapa.shared::cluster.u32 %0, %1, %2;" : "=r"(r) : "r"(b), "r"(cta));
  asm volatile("mbarrier.arrive.shared::cluster.b64 _, [%0];" ::"r"(r) : "memory");
}
__device__ __forceinline__ void tma2d(uint32_t dst, const CUtensorMap* m, int c0, int c1, uint32_t bar) {
  asm volatile("cp.async.bulk.tensor.2d.shared::cluster.global.mbarrier::complete_tx::bytes [%0], [%1, {%3,%4}], [%2];" ::"r"(dst), "l"(m), "r"(bar), "r"(c0), "r"(c1) : "memory");
}
__device__ __forceinline__ void tma2d_mc(uint32_t dst, const CUtensorMap* m, int c0, int c1, uint32_t bar, uint16_t mask) {
  asm volatile("cp.async.bulk.tensor.2d.shared::cluster.global.mbarrier::complete_tx::bytes.multicast::cluster [%0], [%1, {%3,%4}], [%2], %5;" ::"r"(dst), "l"(m), "r"(bar), "r"(c0), "r"(c1), "h"(mask) : "memory");
}
__device__ __forceinline__ void tma3d_mc(uint32_t dst, const CUtensorMap* m, int c0, int c1, int c2, uint32_t bar, uint16_t mask) {
  asm volatile("cp.async.bulk.tensor.3d.shared::cluster.global.mbarrier::complete_tx::bytes.multicast::cluster [%0], [%1, {%3,%4,%5}], [%2], %6;" ::"r"(dst), "l"(m), "r"(bar), "r"(c0), "r"(c1), "r"(c2), "h"(mask) : "memory");
}
__device__ __forceinline__ void tma2d_store(const CUtensorMap* m, uint32_t src, int c0, int c1) {
  asm volatile("cp.async.bulk.tensor.2d.global.shared::cta.bulk_group [%0, {%2,%3}], [%1];" ::"l"(m), "r"(src), "r"(c0), "r"(c1) : "memory");
}
__device__ __forceinline__ void bulk_load(uint32_t dst, const void* src, uint32_t bytes, uint32_t bar) {
  asm volatile("cp.async.bulk.shared::cluster.global.mbarrier::complete_tx::bytes [%0], [%1], %2, [%3];" ::"r"(dst), "l"(src), "r"(bytes), "r"(bar) : "memory");
}
__device__ __forceinline__ void tma2d_prefetch(const CUtensorMap* m, int c0, int c1) {
  asm volatile("cp.async.bulk.prefetch.tensor.2d.L2.global [%0, {%1,%2}];" ::"l"(m), "r"(c0), "r"(c1) : "memory");
}
__device__ __forceinline__ void bulk_commit() { asm volatile("cp.async.bulk.commit_group;" ::: "memory"); }
__device__ __forceinline__ void bulk_wait_read0() { asm volatile("cp.async.bulk.wait_group.read 0;" ::: "memory"); }
__device__ __forceinline__ void bulk_wait0() { asm volatile("cp.async.bulk.wait_group 0;" ::: "memory"); }
__device__ __forceinline__ void fence_async_smem() { asm volatile("fence.proxy.async.shared::cta;" ::: "memory"); }
__device__ __forceinline__ void prefetch_tmap(const CUtensorMap* m) { asm volatile("prefetch.tensormap [%0];" ::"l"(m) : "memory"); }
__device__ __forceinline__ void l2_prefetch(const void* p, uint32_t bytes) {
  asm volatile("cp.async.bulk.prefetch.L2.global [%0], %1;" ::"l"(p), "r"(bytes) : "memory");
}
__device__ __forceinline__ void cluster_arrive_relaxed() { asm volatile("barrier.cluster.arrive.relaxed.aligned;" ::: "memory"); }
__device__ __forceinline__ void cluster_wait() { asm volatile("barrier.cluster.wait.aligned;" ::: "memory"); }
__device__ __forceinline__ void wg_fence() { __syncwarp(); asm volatile("wgmma.fence.sync.aligned;" ::: "memory"); }
__device__ __forceinline__ void wg_commit() { asm volatile("wgmma.commit_group.sync.aligned;" ::: "memory"); }
template <int N> __device__ __forceinline__ void wg_wait() { __syncwarp(); asm volatile("wgmma.wait_group.sync.aligned %0;" ::"n"(N) : "memory"); }
__device__ __forceinline__ void named_bar(int id, int n) { asm volatile("bar.sync %0, %1;" ::"r"(id), "r"(n) : "memory"); }
__device__ __forceinline__ void named_arrive(int id, int n) { asm volatile("bar.arrive %0, %1;" ::"r"(id), "r"(n) : "memory"); }
template <int N> __device__ __forceinline__ void reg_inc() { asm volatile("setmaxnreg.inc.sync.aligned.u32 %0;" ::"n"(N)); }
template <int N> __device__ __forceinline__ void reg_dec() { asm volatile("setmaxnreg.dec.sync.aligned.u32 %0;" ::"n"(N)); }
__device__ __forceinline__ void pdl_wait() { asm volatile("griddepcontrol.wait;" ::: "memory"); }
__device__ __forceinline__ void pdl_launch() { asm volatile("griddepcontrol.launch_dependents;" ::: "memory"); }

__device__ __forceinline__ uint32_t make_desc(uint32_t addr, uint32_t lbo, uint32_t  ) {
  return ((addr & 0x3FFFF) >> 4) | ((lbo >> 4) << 16);
}
__device__ __forceinline__ void stmatrix_x4(uint32_t addr, uint32_t r0, uint32_t r1, uint32_t r2, uint32_t r3) {
  asm volatile("stmatrix.sync.aligned.m8n8.x4.shared.b16 [%0], {%1,%2,%3,%4};" ::"r"(addr), "r"(r0), "r"(r1), "r"(r2), "r"(r3) : "memory");
}
__device__ __forceinline__ uint4 lds128(uint32_t a) {
  uint4 v;
  asm volatile("ld.shared.v4.u32 {%0,%1,%2,%3}, [%4];" : "=r"(v.x), "=r"(v.y), "=r"(v.z), "=r"(v.w) : "r"(a) : "memory");
  return v;
}
__device__ __forceinline__ void sts128(uint32_t a, uint4 v) {
  asm volatile("st.shared.v4.u32 [%0], {%1,%2,%3,%4};" ::"r"(a), "r"(v.x), "r"(v.y), "r"(v.z), "r"(v.w) : "memory");
}
__device__ __forceinline__ void stg128(void* p, uint4 v) {
  asm volatile("st.global.v4.u32 [%0], {%1,%2,%3,%4};" ::"l"(p), "r"(v.x), "r"(v.y), "r"(v.z), "r"(v.w) : "memory");
}
__device__ __forceinline__ void cp_async16(uint32_t dst, const void* src) {
  asm volatile("cp.async.cg.shared.global [%0], [%1], 16;" ::"r"(dst), "l"(src) : "memory");
}
__device__ __forceinline__ void cp_async8(uint32_t dst, const void* src) {
  asm volatile("cp.async.ca.shared.global [%0], [%1], 8;" ::"r"(dst), "l"(src) : "memory");
}
__device__ __forceinline__ uint2 lds64(uint32_t a) {
  uint2 v;
  asm volatile("ld.shared.v2.u32 {%0,%1}, [%2];" : "=r"(v.x), "=r"(v.y) : "r"(a) : "memory");
  return v;
}
__device__ __forceinline__ void cp_async_wait_all() { asm volatile("cp.async.wait_all;" ::: "memory"); }
__device__ __forceinline__ uint32_t pack_bf16(float lo, float hi) {
  uint32_t r;
  asm("cvt.rn.bf16x2.f32 %0, %1, %2;" : "=r"(r) : "f"(hi), "f"(lo));
  return r;
}
__device__ __forceinline__ uint32_t hmul2_bf16(uint32_t a, uint32_t b) {
  uint32_t r;
  asm("mul.rn.bf16x2 %0, %1, %2;" : "=r"(r) : "r"(a), "r"(b));
  return r;
}
__device__ __forceinline__ uint32_t hsub2_bf16(uint32_t a, uint32_t b) {
  uint32_t r;
  asm("sub.rn.bf16x2 %0, %1, %2;" : "=r"(r) : "r"(a), "r"(b));
  return r;
}
__device__ __forceinline__ uint32_t hadd2_bf16(uint32_t a, uint32_t b) {
  uint32_t r;
  asm("add.rn.bf16x2 %0, %1, %2;" : "=r"(r) : "r"(a), "r"(b));
  return r;
}
__device__ __forceinline__ uint32_t hfma2_bf16(uint32_t a, uint32_t b, uint32_t c) {
  uint32_t r;
  asm("fma.rn.bf16x2 %0, %1, %2, %3;" : "=r"(r) : "r"(a), "r"(b), "r"(c));
  return r;
}
__device__ __forceinline__ bool mbar_test(uint32_t b, uint32_t ph) {
  uint32_t done;
  asm volatile("{.reg .pred p; mbarrier.test_wait.parity.shared::cta.b64 p, [%1], %2; selp.u32 %0,1,0,p;}" : "=r"(done) : "r"(b), "r"(ph) : "memory");
  return __all_sync(0xffffffffu, done != 0);
}
__device__ __forceinline__ uint4 ldg128_cg(const void* p) {
  uint4 v;
  asm volatile("ld.global.cg.v4.u32 {%0,%1,%2,%3}, [%4];" : "=r"(v.x), "=r"(v.y), "=r"(v.z), "=r"(v.w) : "l"(p) : "memory");
  return v;
}
__device__ __forceinline__ float bf_lo(uint32_t w) { return __uint_as_float(w << 16); }
__device__ __forceinline__ float bf_hi(uint32_t w) { return __uint_as_float(w & 0xffff0000u); }
__device__ __forceinline__ float rbf(float x) { return __bfloat162float(__float2bfloat16_rn(x)); }
__device__ __forceinline__ float ex2f(float x) { float r; asm("ex2.approx.ftz.f32 %0, %1;" : "=f"(r) : "f"(x)); return r; }
__device__ __forceinline__ float rcpf(float x) { float r; asm("rcp.approx.ftz.f32 %0, %1;" : "=f"(r) : "f"(x)); return r; }
__device__ __forceinline__ float tanhf_hw(float x) { float r; asm("tanh.approx.f32 %0, %1;" : "=f"(r) : "f"(x)); return r; }
__device__ __forceinline__ float gelu_tanh(float x) {
  const float c1 = 0.7978845608028654f;
  const float c2 = c1 * 0.044715f;
  const float t = tanhf_hw(x * fmaf(c2, x * x, c1));
  const float hx = 0.5f * x;
  return fmaf(hx, t, hx);
}
__device__ __forceinline__ float silu_f(float x) {
  const float hx = 0.5f * x;
  return fmaf(hx, tanhf_hw(hx), hx);
}

__device__ __forceinline__ void wgmma_n128_tb(float (&d)[64], uint32_t da, uint32_t db, int scale_d) {
  asm volatile(
    "{\n.reg .pred p;\n.reg .b64 da, db;\nsetp.ne.b32 p, %66, 0;\n"
    "mov.b64 da, {%64, 0x40000040};\nmov.b64 db, {%65, 0x40000040};\n"
    "wgmma.mma_async.sync.aligned.m64n128k16.f32.bf16.bf16 {%0, %1, %2, %3, %4, %5, %6, %7, %8, %9, %10, %11, %12, %13, %14, %15, %16, %17, %18, %19, %20, %21, %22, %23, %24, %25, %26, %27, %28, %29, %30, %31, %32, %33, %34, %35, %36, %37, %38, %39, %40, %41, %42, %43, %44, %45, %46, %47, %48, %49, %50, %51, %52, %53, %54, %55, %56, %57, %58, %59, %60, %61, %62, %63}, da, db, p, 1, 1, 0, 1;\n}\n"
    : "+f"(d[0]), "+f"(d[1]), "+f"(d[2]), "+f"(d[3]), "+f"(d[4]), "+f"(d[5]), "+f"(d[6]), "+f"(d[7]), "+f"(d[8]), "+f"(d[9]), "+f"(d[10]), "+f"(d[11]), "+f"(d[12]), "+f"(d[13]), "+f"(d[14]), "+f"(d[15]), "+f"(d[16]), "+f"(d[17]), "+f"(d[18]), "+f"(d[19]), "+f"(d[20]), "+f"(d[21]), "+f"(d[22]), "+f"(d[23]), "+f"(d[24]), "+f"(d[25]), "+f"(d[26]), "+f"(d[27]), "+f"(d[28]), "+f"(d[29]), "+f"(d[30]), "+f"(d[31]), "+f"(d[32]), "+f"(d[33]), "+f"(d[34]), "+f"(d[35]), "+f"(d[36]), "+f"(d[37]), "+f"(d[38]), "+f"(d[39]), "+f"(d[40]), "+f"(d[41]), "+f"(d[42]), "+f"(d[43]), "+f"(d[44]), "+f"(d[45]), "+f"(d[46]), "+f"(d[47]), "+f"(d[48]), "+f"(d[49]), "+f"(d[50]), "+f"(d[51]), "+f"(d[52]), "+f"(d[53]), "+f"(d[54]), "+f"(d[55]), "+f"(d[56]), "+f"(d[57]), "+f"(d[58]), "+f"(d[59]), "+f"(d[60]), "+f"(d[61]), "+f"(d[62]), "+f"(d[63])
    : "r"(da), "r"(db), "r"(scale_d));
}
__device__ __forceinline__ void wgmma_n128_tb_p(float (&d)[64], uint32_t da, uint32_t db, int scale_d, int enable) {
  asm volatile(
    "{\n.reg .pred p;\n.reg .b64 da, db;\nsetp.ne.b32 p, %66, 0;\n.reg .pred q;\nsetp.ne.b32 q, %67, 0;\n"
    "mov.b64 da, {%64, 0x40000040};\nmov.b64 db, {%65, 0x40000040};\n"
    "@q wgmma.mma_async.sync.aligned.m64n128k16.f32.bf16.bf16 {%0, %1, %2, %3, %4, %5, %6, %7, %8, %9, %10, %11, %12, %13, %14, %15, %16, %17, %18, %19, %20, %21, %22, %23, %24, %25, %26, %27, %28, %29, %30, %31, %32, %33, %34, %35, %36, %37, %38, %39, %40, %41, %42, %43, %44, %45, %46, %47, %48, %49, %50, %51, %52, %53, %54, %55, %56, %57, %58, %59, %60, %61, %62, %63}, da, db, p, 1, 1, 0, 1;\n}\n"
    : "+f"(d[0]), "+f"(d[1]), "+f"(d[2]), "+f"(d[3]), "+f"(d[4]), "+f"(d[5]), "+f"(d[6]), "+f"(d[7]), "+f"(d[8]), "+f"(d[9]), "+f"(d[10]), "+f"(d[11]), "+f"(d[12]), "+f"(d[13]), "+f"(d[14]), "+f"(d[15]), "+f"(d[16]), "+f"(d[17]), "+f"(d[18]), "+f"(d[19]), "+f"(d[20]), "+f"(d[21]), "+f"(d[22]), "+f"(d[23]), "+f"(d[24]), "+f"(d[25]), "+f"(d[26]), "+f"(d[27]), "+f"(d[28]), "+f"(d[29]), "+f"(d[30]), "+f"(d[31]), "+f"(d[32]), "+f"(d[33]), "+f"(d[34]), "+f"(d[35]), "+f"(d[36]), "+f"(d[37]), "+f"(d[38]), "+f"(d[39]), "+f"(d[40]), "+f"(d[41]), "+f"(d[42]), "+f"(d[43]), "+f"(d[44]), "+f"(d[45]), "+f"(d[46]), "+f"(d[47]), "+f"(d[48]), "+f"(d[49]), "+f"(d[50]), "+f"(d[51]), "+f"(d[52]), "+f"(d[53]), "+f"(d[54]), "+f"(d[55]), "+f"(d[56]), "+f"(d[57]), "+f"(d[58]), "+f"(d[59]), "+f"(d[60]), "+f"(d[61]), "+f"(d[62]), "+f"(d[63])
    : "r"(da), "r"(db), "r"(scale_d), "r"(enable));
}
__device__ __forceinline__ void wgmma_n112(float (&d)[56], uint32_t da, uint32_t db, int scale_d) {
  asm volatile(
    "{\n.reg .pred p;\n.reg .b64 da, db;\nsetp.ne.b32 p, %58, 0;\n"
    "mov.b64 da, {%56, 0x40000040};\nmov.b64 db, {%57, 0x40000040};\n"
    "wgmma.mma_async.sync.aligned.m64n112k16.f32.bf16.bf16 {%0, %1, %2, %3, %4, %5, %6, %7, %8, %9, %10, %11, %12, %13, %14, %15, %16, %17, %18, %19, %20, %21, %22, %23, %24, %25, %26, %27, %28, %29, %30, %31, %32, %33, %34, %35, %36, %37, %38, %39, %40, %41, %42, %43, %44, %45, %46, %47, %48, %49, %50, %51, %52, %53, %54, %55}, da, db, p, 1, 1, 0, 0;\n}\n"
    : "+f"(d[0]), "+f"(d[1]), "+f"(d[2]), "+f"(d[3]), "+f"(d[4]), "+f"(d[5]), "+f"(d[6]), "+f"(d[7]), "+f"(d[8]), "+f"(d[9]), "+f"(d[10]), "+f"(d[11]), "+f"(d[12]), "+f"(d[13]), "+f"(d[14]), "+f"(d[15]), "+f"(d[16]), "+f"(d[17]), "+f"(d[18]), "+f"(d[19]), "+f"(d[20]), "+f"(d[21]), "+f"(d[22]), "+f"(d[23]), "+f"(d[24]), "+f"(d[25]), "+f"(d[26]), "+f"(d[27]), "+f"(d[28]), "+f"(d[29]), "+f"(d[30]), "+f"(d[31]), "+f"(d[32]), "+f"(d[33]), "+f"(d[34]), "+f"(d[35]), "+f"(d[36]), "+f"(d[37]), "+f"(d[38]), "+f"(d[39]), "+f"(d[40]), "+f"(d[41]), "+f"(d[42]), "+f"(d[43]), "+f"(d[44]), "+f"(d[45]), "+f"(d[46]), "+f"(d[47]), "+f"(d[48]), "+f"(d[49]), "+f"(d[50]), "+f"(d[51]), "+f"(d[52]), "+f"(d[53]), "+f"(d[54]), "+f"(d[55])
    : "r"(da), "r"(db), "r"(scale_d));
}
__device__ __forceinline__ void wgmma_n224_tb(float (&d)[112], uint32_t da, uint32_t db, int scale_d) {
  asm volatile(
    "{\n.reg .pred p;\n.reg .b64 da, db;\nsetp.ne.b32 p, %114, 0;\n"
    "mov.b64 da, {%112, 0x40000040};\nmov.b64 db, {%113, 0x40000040};\n"
    "wgmma.mma_async.sync.aligned.m64n224k16.f32.bf16.bf16 {%0, %1, %2, %3, %4, %5, %6, %7, %8, %9, %10, %11, %12, %13, %14, %15, %16, %17, %18, %19, %20, %21, %22, %23, %24, %25, %26, %27, %28, %29, %30, %31, %32, %33, %34, %35, %36, %37, %38, %39, %40, %41, %42, %43, %44, %45, %46, %47, %48, %49, %50, %51, %52, %53, %54, %55, %56, %57, %58, %59, %60, %61, %62, %63, %64, %65, %66, %67, %68, %69, %70, %71, %72, %73, %74, %75, %76, %77, %78, %79, %80, %81, %82, %83, %84, %85, %86, %87, %88, %89, %90, %91, %92, %93, %94, %95, %96, %97, %98, %99, %100, %101, %102, %103, %104, %105, %106, %107, %108, %109, %110, %111}, da, db, p, 1, 1, 0, 1;\n}\n"
    : "+f"(d[0]), "+f"(d[1]), "+f"(d[2]), "+f"(d[3]), "+f"(d[4]), "+f"(d[5]), "+f"(d[6]), "+f"(d[7]), "+f"(d[8]), "+f"(d[9]), "+f"(d[10]), "+f"(d[11]), "+f"(d[12]), "+f"(d[13]), "+f"(d[14]), "+f"(d[15]), "+f"(d[16]), "+f"(d[17]), "+f"(d[18]), "+f"(d[19]), "+f"(d[20]), "+f"(d[21]), "+f"(d[22]), "+f"(d[23]), "+f"(d[24]), "+f"(d[25]), "+f"(d[26]), "+f"(d[27]), "+f"(d[28]), "+f"(d[29]), "+f"(d[30]), "+f"(d[31]), "+f"(d[32]), "+f"(d[33]), "+f"(d[34]), "+f"(d[35]), "+f"(d[36]), "+f"(d[37]), "+f"(d[38]), "+f"(d[39]), "+f"(d[40]), "+f"(d[41]), "+f"(d[42]), "+f"(d[43]), "+f"(d[44]), "+f"(d[45]), "+f"(d[46]), "+f"(d[47]), "+f"(d[48]), "+f"(d[49]), "+f"(d[50]), "+f"(d[51]), "+f"(d[52]), "+f"(d[53]), "+f"(d[54]), "+f"(d[55]), "+f"(d[56]), "+f"(d[57]), "+f"(d[58]), "+f"(d[59]), "+f"(d[60]), "+f"(d[61]), "+f"(d[62]), "+f"(d[63]), "+f"(d[64]), "+f"(d[65]), "+f"(d[66]), "+f"(d[67]), "+f"(d[68]), "+f"(d[69]), "+f"(d[70]), "+f"(d[71]), "+f"(d[72]), "+f"(d[73]), "+f"(d[74]), "+f"(d[75]), "+f"(d[76]), "+f"(d[77]), "+f"(d[78]), "+f"(d[79]), "+f"(d[80]), "+f"(d[81]), "+f"(d[82]), "+f"(d[83]), "+f"(d[84]), "+f"(d[85]), "+f"(d[86]), "+f"(d[87]), "+f"(d[88]), "+f"(d[89]), "+f"(d[90]), "+f"(d[91]), "+f"(d[92]), "+f"(d[93]), "+f"(d[94]), "+f"(d[95]), "+f"(d[96]), "+f"(d[97]), "+f"(d[98]), "+f"(d[99]), "+f"(d[100]), "+f"(d[101]), "+f"(d[102]), "+f"(d[103]), "+f"(d[104]), "+f"(d[105]), "+f"(d[106]), "+f"(d[107]), "+f"(d[108]), "+f"(d[109]), "+f"(d[110]), "+f"(d[111])
    : "r"(da), "r"(db), "r"(scale_d));
}

constexpr int K1_NS = 5;
constexpr int K1_A_BYTES = 7 * 16384;
constexpr int K1_B_OFF = K1_A_BYTES;
constexpr int K1_STG_OFF = K1_B_OFF + K1_NS * 16384;
constexpr int K1_BAR_OFF = K1_STG_OFF + 8 * 4096;
constexpr int K1_SMEM = K1_BAR_OFF + 256 + 1024;

struct K1Ctx {
  uint32_t sb, bar_full, rel0, rel1;
  uint32_t dA, dBk, dBn;
  bool lane0;
  uint32_t bar_sfree;
  uint32_t sphase;
};
__device__ __forceinline__ void k1_release(const K1Ctx& c, int slot) {
  if (c.lane0) {
    asm volatile("mbarrier.arrive.shared::cluster.b64 _, [%0];" ::"r"(c.rel0 + 8 * slot) : "memory");
    asm volatile("mbarrier.arrive.shared::cluster.b64 _, [%0];" ::"r"(c.rel1 + 8 * slot) : "memory");
  }
}

__device__ __forceinline__ void k1_unit_ab(K1Ctx& c, int warp, int lane, int mt, int j) {
  const int wq = warp & 3;
  const int st_row = (lane & 7) + 8 * ((lane >> 3) & 1);
  const int st_chunk = lane >> 4;
  float acc[2][56];
  int slot = 0; uint32_t ph = 0;
#pragma unroll 1
  for (int kb = 0; kb < 7; kb++) {
    const int pslot = (slot == 0) ? K1_NS - 1 : slot - 1;
    mbar_wait(c.bar_full + 8 * slot, ph, 3);
    if (kb == 6) named_arrive(2, 256);
    if (kb == 0 && (threadIdx.x & 127) == 0) DBG(0, 4);
    if ((threadIdx.x & 127) == 0) DBGC(1, 46 + kb);
    wg_fence();
    const uint32_t da = c.dA + kb * 1024;
    const uint32_t db = c.dBk + slot * 1024;
#pragma unroll
    for (int k = 0; k < 4; k++) {
      wgmma_n112(acc[0], da + k * 2, db + k * 2, (kb | k) != 0);
      wgmma_n112(acc[1], da + 512 + k * 2, db + k * 2, (kb | k) != 0);
    }
    wg_commit();
    if (kb > 0) { wg_wait<1>(); k1_release(c, pslot); }
    if (++slot == K1_NS) { slot = 0; ph ^= 1; }
  }
  wg_wait<0>();
  k1_release(c, 6 % K1_NS);
  if ((threadIdx.x & 127) == 0) DBG(0, 5);
  const uint32_t sgn = (j < 4) ? 0u : 0x80008000u;
  const uint32_t sa = c.sb + K1_STG_OFF + (wq * 16 + st_row) * 224 + st_chunk * 16;
#pragma unroll
  for (int h = 0; h < 2; h++) {
    if (h == 1) { mbar_wait(c.bar_sfree, c.sphase, 6); c.sphase ^= 1; }
#pragma unroll
    for (int g = 0; g < 14; g += 2) {
      const float* a = &acc[h][4 * g];
      stmatrix_x4(sa + g * 16, pack_bf16(a[0], a[1]) ^ sgn, pack_bf16(a[2], a[3]) ^ sgn, pack_bf16(a[4], a[5]) ^ sgn, pack_bf16(a[6], a[7]) ^ sgn);
    }
    fence_async_smem();
    named_arrive(6, 160);
  }
}

__device__ __forceinline__ void k1_unit_gu(K1Ctx& c, int warp, int lane, int mt, int unit, int fb, int hsel, int full, int nunits) {
  const int wq = warp & 3;
  float acc[2][64];
  const uint32_t dA0 = c.dA + (full ? 0 : hsel * 512);
  int slot = (unit * 7) % K1_NS; uint32_t ph = ((unit * 7) / K1_NS) & 1;
  named_bar(2 + ((unit - 1) & 1), 256);
  if (full) {
#pragma unroll 1
    for (int kb = 0; kb < 7; kb++) {
      const int pslot = (slot == 0) ? K1_NS - 1 : slot - 1;
      mbar_wait(c.bar_full + 8 * slot, ph, 4);
      if (kb == 6 && unit + 1 < nunits) named_arrive(2 + (unit & 1), 256);
      if (kb == 0 && (threadIdx.x & 127) == 0) DBG(0, 4 + 3 * unit);
      wg_fence();
      const uint32_t da = dA0 + kb * 1024;
      const uint32_t db = c.dBn + slot * 1024;
#pragma unroll
      for (int k = 0; k < 4; k++) {
        wgmma_n128_tb(acc[0], da + k * 2, db + k * 128, (kb | k) != 0);
        wgmma_n128_tb(acc[1], da + 512 + k * 2, db + k * 128, (kb | k) != 0);
      }
      wg_commit();
      if (kb > 0) { wg_wait<1>(); k1_release(c, pslot); }
      if (++slot == K1_NS) { slot = 0; ph ^= 1; }
    }
  } else {
#pragma unroll 1
    for (int kb = 0; kb < 7; kb++) {
      const int pslot = (slot == 0) ? K1_NS - 1 : slot - 1;
      mbar_wait(c.bar_full + 8 * slot, ph, 5);
      if (kb == 0 && (threadIdx.x & 127) == 0) DBG(0, 4 + 3 * unit);
      wg_fence();
      const uint32_t da = dA0 + kb * 1024;
      const uint32_t db = c.dBn + slot * 1024;
#pragma unroll
      for (int k = 0; k < 4; k++) wgmma_n128_tb(acc[0], da + k * 2, db + k * 128, (kb | k) != 0);
      wg_commit();
      if (kb > 0) { wg_wait<1>(); k1_release(c, pslot); }
      if (++slot == K1_NS) { slot = 0; ph ^= 1; }
    }
  }
  wg_wait<0>();
  k1_release(c, (slot == 0) ? K1_NS - 1 : slot - 1);
  if (unit + 2 >= nunits && lane < 4) {
    asm volatile("mbarrier.arrive.shared::cluster.b64 _, [%0];" ::"r"(c.rel0 + 8 * (K1_NS + 4 + lane)) : "memory");
    asm volatile("mbarrier.arrive.shared::cluster.b64 _, [%0];" ::"r"(c.rel1 + 8 * (K1_NS + 4 + lane)) : "memory");
  }
  if ((threadIdx.x & 127) == 0) DBG(0, 5 + 3 * unit);
  const int st_row = (lane & 7) + 8 * ((lane >> 3) & 1);
  const int st_chunk = lane >> 4;
  const uint32_t sa = c.sb + K1_STG_OFF + (warp >> 2) * 16384 + (wq * 16 + st_row) * 128;
  if (unit >= 2) { mbar_wait(c.bar_sfree, c.sphase, 7); c.sphase ^= 1; }
#pragma unroll
  for (int h = 0; h < 2; h++) {
    if (h == 1 && !full) break;
#pragma unroll
    for (int g = 0; g < 8; g += 2) {
      uint32_t pk[4];
#pragma unroll
      for (int e = 0; e < 4; e++) {
        const int i = 4 * g + 2 * e;
        const uint32_t g2 = pack_bf16(acc[h][i], acc[h][i + 1]);
        const uint32_t u2 = pack_bf16(acc[h][32 + i], acc[h][32 + i + 1]);
        pk[e] = hmul2_bf16(pack_bf16(gelu_tanh(bf_lo(g2)), gelu_tanh(bf_hi(g2))), u2);
      }
      stmatrix_x4(sa + h * 8192 + (((g + st_chunk) ^ (st_row & 7)) * 16), pk[0], pk[1], pk[2], pk[3]);
    }
  }
  fence_async_smem();
  named_arrive(6 + (warp >> 2), 160);
}

constexpr int K2_NS = 4;
constexpr int K2_STAGE = 16384 + 32768;
constexpr int K2_PITCH = 464;

__device__ __forceinline__ void spin_flag(const unsigned int* flag, unsigned int target) {
  int it = 0;
  while (true) {
    unsigned int v;
    asm volatile("ld.acquire.gpu.global.u32 %0, [%1];" : "=r"(v) : "l"(flag) : "memory");
    if ((int)(v - target) >= 0) break;
    if (++it > SPIN_LIMIT) { TIMEOUT(20); break; }
  }
}

__device__ __forceinline__ void ln_rows(const __nv_bfloat16* __restrict__ xt, uint32_t sb, int lw, int lane) {
  const int c = lane & 7;
  const int r0 = lw * 4 + (lane >> 3);
  const uint4* src = reinterpret_cast<const uint4*>(xt + (size_t)r0 * 448) + c;
  uint4 nx[7];
#pragma unroll
  for (int b = 0; b < 7; b++)
    asm volatile("ld.global.nc.v4.u32 {%0,%1,%2,%3}, [%4];" : "=r"(nx[b].x), "=r"(nx[b].y), "=r"(nx[b].z), "=r"(nx[b].w) : "l"(src + b * 8) : "memory");
  const int npass = (lw < 10) ? 3 : 2;
  if (c < 7) {
    asm volatile("prefetch.global.L2 [%0];" ::"l"(src + 44 * 56 + c * 7) : "memory");
    if (npass == 3) asm volatile("prefetch.global.L2 [%0];" ::"l"(src + 88 * 56 + c * 7) : "memory");
  }
#pragma unroll 1
  for (int pass = 0; pass < npass; pass++) {
    uint4 v[7];
#pragma unroll
    for (int b = 0; b < 7; b++) v[b] = nx[b];
    if (pass + 1 < npass) {
      const uint4* s2 = src + (pass + 1) * 44 * 56;
#pragma unroll
      for (int b = 0; b < 7; b++)
        asm volatile("ld.global.nc.v4.u32 {%0,%1,%2,%3}, [%4];" : "=r"(nx[b].x), "=r"(nx[b].y), "=r"(nx[b].z), "=r"(nx[b].w) : "l"(s2 + b * 8) : "memory");
    }
        float s0 = 0.f, s1 = 0.f, s2v = 0.f, s3 = 0.f;
#pragma unroll
        for (int b = 0; b < 7; b++) {
          s0 += bf_lo(v[b].x) + bf_hi(v[b].x); s1 += bf_lo(v[b].y) + bf_hi(v[b].y);
          s2v += bf_lo(v[b].z) + bf_hi(v[b].z); s3 += bf_lo(v[b].w) + bf_hi(v[b].w);
        }
        float m = (s0 + s1) + (s2v + s3);
        m += __shfl_xor_sync(0xffffffffu, m, 1);
        m += __shfl_xor_sync(0xffffffffu, m, 2);
        m += __shfl_xor_sync(0xffffffffu, m, 4);
        m *= (1.0f / 448.0f);
        float q0 = 0.f, q1 = 0.f, q2 = 0.f, q3 = 0.f;
#pragma unroll
        for (int b = 0; b < 7; b++) {
          float d;
          d = bf_lo(v[b].x) - m; q0 = fmaf(d, d, q0); d = bf_hi(v[b].x) - m; q1 = fmaf(d, d, q1);
          d = bf_lo(v[b].y) - m; q2 = fmaf(d, d, q2); d = bf_hi(v[b].y) - m; q3 = fmaf(d, d, q3);
          d = bf_lo(v[b].z) - m; q0 = fmaf(d, d, q0); d = bf_hi(v[b].z) - m; q1 = fmaf(d, d, q1);
          d = bf_lo(v[b].w) - m; q2 = fmaf(d, d, q2); d = bf_hi(v[b].w) - m; q3 = fmaf(d, d, q3);
        }
        float q = (q0 + q1) + (q2 + q3);
        q += __shfl_xor_sync(0xffffffffu, q, 1);
        q += __shfl_xor_sync(0xffffffffu, q, 2);
        q += __shfl_xor_sync(0xffffffffu, q, 4);
        const float var_b = rbf(q * (1.0f / 448.0f));
        const float den = rbf(sqrtf(rbf(var_b + 1e-5f)));
        const float ri = 1.0f / den;
        const float rih = rbf(ri);
        const uint32_t rhi2 = pack_bf16(rih, rih), rlo2 = pack_bf16(ri - rih, ri - rih);
        const uint32_t m2 = pack_bf16(m, m);
        const int r = r0 + pass * 44;
        const uint32_t a0 = sb + r * 128 + ((c ^ (r & 7)) * 16);
#pragma unroll
        for (int b = 0; b < 7; b++) {
          uint32_t w4[4] = {v[b].x, v[b].y, v[b].z, v[b].w};
#pragma unroll
          for (int qq = 0; qq < 4; qq++) {
            const uint32_t dw = hsub2_bf16(w4[qq], m2);
            w4[qq] = hfma2_bf16(dw, rhi2, hmul2_bf16(dw, rlo2));
          }
          sts128(a0 + b * 16384, make_uint4(w4[0], w4[1], w4[2], w4[3]));
        }
  }
}

struct PfPtrs { const uint8_t* wg; const uint8_t* wu; const uint8_t* wd; };

__global__ void __cluster_dims__(2, 1, 1) __launch_bounds__(384, 1)
fused_kernel(const __grid_constant__ CUtensorMap tm_wr, const __grid_constant__ CUtensorMap tm_wi,
             const __grid_constant__ CUtensorMap tm_wg, const __grid_constant__ CUtensorMap tm_wu,
             const __grid_constant__ CUtensorMap tm_hs, const __grid_constant__ CUtensorMap tm_abs,
             const __grid_constant__ CUtensorMap tm_cr, const __grid_constant__ CUtensorMap tm_ci, const __grid_constant__ CUtensorMap tm_h,
             const __grid_constant__ CUtensorMap tm_ab, const __grid_constant__ CUtensorMap tm_wd,
             const __nv_bfloat16* __restrict__ x, __nv_bfloat16* __restrict__ out, const PfPtrs pf) {
  extern __shared__ uint8_t smem_raw[];
  const uint32_t sb = (s2u(smem_raw) + 1023) & ~1023u;
  const int tid = threadIdx.x, warp = tid >> 5, lane = tid & 31;
  uint32_t rank;
  asm volatile("mov.u32 %0, %%cluster_ctarank;" : "=r"(rank));
  const int cid = blockIdx.x >> 1;
  const int p = cid >> 3, j = cid & 7;
  const int mt = 2 * p + (int)rank;
  const uint32_t bar_full = sb + K1_BAR_OFF;
  const uint32_t bar_empty = bar_full + 8 * K1_NS;
  const uint32_t bar_full2 = bar_empty + 8 * K1_NS;
  const uint32_t bar_empty2 = bar_full2 + 8 * K2_NS;
  const int fb_base = 7 * (j >> 1);
  const int fb0 = fb_base + ((j & 1) ? 4 : 0);
  const int fbh = fb_base + 3;
  const int q = j & 3, n = j >> 2;
  const int tile = mt * 2 + n;
  const int nkb = (q < 2) ? 22 : (q == 3 ? 28 : 20);
  const int nunits = (q == 3) ? 4 : 5;
  const int u4full = (q == 2);

  if (tid == 0) DBG(0, 0);
  if (tid == 256) {
    for (int i = 0; i < K1_NS; i++) { mbar_init(bar_full + 8 * i, 1); mbar_init(bar_empty + 8 * i, 8); }
    for (int i = 0; i < K2_NS; i++) { mbar_init(bar_full2 + 8 * i, 1); mbar_init(bar_empty2 + 8 * i, 16); }
    mbar_init(bar_empty2 + 8 * K2_NS, 1);
    mbar_init(bar_empty2 + 8 * K2_NS + 8, 1);
    mbar_init(bar_empty2 + 8 * K2_NS + 16, 1);
    asm volatile("fence.mbarrier_init.release.cluster;" ::: "memory");
    prefetch_tmap((j < 4) ? &tm_wr : &tm_wi);
    prefetch_tmap(rank ? &tm_wu : &tm_wg);
    prefetch_tmap(&tm_abs);
    prefetch_tmap(&tm_hs);
  }
  __syncwarp();
  cluster_arrive_relaxed();

  if (warp != 8) {
    ln_rows(x + (size_t)mt * 128 * 448, sb, warp < 8 ? warp : warp - 1, lane);
    asm volatile("fence.proxy.async.shared::cta;" ::: "memory");
  }
  if (warp >= 8) {
    if (warp > 8) named_arrive(8, 352);
    reg_dec<40>();
    cluster_wait();
    if (tid == 256) {
      const unsigned int epoch = *reinterpret_cast<volatile unsigned int*>(&g_epoch);
      {
        const CUtensorMap* tw = (j < 4) ? &tm_wr : &tm_wi;
        const CUtensorMap* tgu = rank ? &tm_wu : &tm_wg;
        int slot = 0; uint32_t ph = 0;
        int kb = 0, unit = 0;
#pragma unroll 1
        for (int s = 0; s < 7 * nunits; s++) {
          if (s >= K1_NS) mbar_wait(bar_empty + 8 * slot, ph ^ 1, 2);
          const uint32_t dst = sb + K1_B_OFF + slot * 16384;
          if (unit == 0) {
            mbar_expect(bar_full + 8 * slot, 14336);
            tma2d_mc(dst + rank * 7168, tw, kb * 64, (j & 3) * 112 + rank * 56, bar_full + 8 * slot, 3);
          } else {
            const int fb = (unit == 4) ? fbh : (fb0 + unit - 1);
            mbar_expect(bar_full + 8 * slot, 16384);
            tma2d_mc(dst + rank * 8192, tgu, fb * 64, kb * 64, bar_full + 8 * slot, 3);
          }
          if (s == 21) {
            l2_prefetch(pf.wd + blockIdx.x * 12544, 12544);
            if (q < 3) {
              const int g0 = q * 22;
#pragma unroll 1
              for (int i = 0; i < 6; i++) tma2d_prefetch((g0 + i < 32) ? &tm_cr : &tm_ci, ((g0 + i) & 31) * 64, mt * 128);
            }
          }
          if (++kb == 7) { kb = 0; unit++; }
          if (++slot == K1_NS) { slot = 0; ph ^= 1; }
        }
      }
      {
        const int g0 = (q == 0) ? 0 : (q == 1 ? 22 : (q == 2 ? 44 : 64));
        const CUtensorMap* tb = (q < 3) ? &tm_ab : &tm_wd;
        prefetch_tmap(tb); prefetch_tmap((q < 3) ? ((g0 < 32) ? &tm_cr : &tm_ci) : &tm_h);
        const int kb0 = (q < 3) ? g0 : 0;
        if (q < 3) { spin_flag(&g_ab_cnt, 128u * (epoch + 1)); asm volatile("fence.proxy.async;" ::: "memory"); }
        DBG(1, 31);
        int slot = 0; uint32_t ph = 0;
#pragma unroll 1
        for (int s = 0; s < nkb; s++) {
          int kblk = kb0 + s;
          const CUtensorMap* ta = (kblk < 32) ? &tm_cr : &tm_ci;
          if (q == 3) {
            if ((s & 7) == 0) { spin_flag(&g_h_cnt[mt * 4 + (s >> 3)], ((s < 24) ? 8u : 6u) * (epoch + 1)); asm volatile("fence.proxy.async;" ::: "memory"); }
            const int i = s & 7;
            kblk = (s < 24) ? (7 * (i >> 1) + ((i & 1) ? 4 : 0) + (s >> 3)) : (7 * i + 3);
            ta = &tm_h;
          }
          mbar_wait(bar_empty2 + 8 * slot, ph, 10);
          const uint32_t dst = sb + slot * K2_STAGE;
          const uint32_t fb = bar_full2 + 8 * slot;
          mbar_expect(fb, K2_STAGE);
          tma2d(dst, ta, (kblk & 31) * 64, mt * 128, fb);
          tma3d_mc(dst + 16384 + (2 * rank) * 8192, tb, (2 * rank) * 64, n, kblk * 64, fb, 3);
          tma3d_mc(dst + 16384 + (2 * rank + 1) * 8192, tb, (2 * rank + 1) * 64, n, kblk * 64, fb, 3);
          if (++slot == K2_NS) { slot = 0; ph ^= 1; }
        }
      }
    } else if (warp == 9 || warp == 10) {
      const int hw = warp - 9;
      const uint32_t stg = sb + K1_STG_OFF + hw * 16384;
      const uint32_t bar_sfree = bar_empty2 + 8 * K2_NS + 8 + 8 * hw;
      if (lane == 0) {
        const int b = blockIdx.x;
        l2_prefetch((hw ? pf.wu : pf.wg) + b * 12544, 12544);
      }
#pragma unroll 1
      for (int job = 0; job < (hw ? 2 : (nunits == 5 ? 4 : 3)); job++) {
        named_bar(6 + hw, 160);
        if (lane == 0) {
          const int unit = hw ? (1 + 2 * job) : (job < 2 ? 0 : 2 * job - 2);
          if (unit == 0) {
            tma2d_store(&tm_abs, stg, (j & 3) * 112, (j < 4 ? 0 : 2048) + mt * 128 + job * 64);
          } else {
            const int fb = (unit == 4) ? fbh : fb0 + unit - 1;
            const bool fullu = (unit < 4) || u4full;
            tma2d_store(&tm_hs, stg, fb * 64, mt * 128 + (fullu ? 0 : (j & 1) * 64));
            if (fullu) tma2d_store(&tm_hs, stg + 8192, fb * 64, mt * 128 + 64);
          }
          bulk_commit();
          bulk_wait_read0();
          asm volatile("mbarrier.arrive.shared::cta.b64 _, [%0];" ::"r"(bar_sfree) : "memory");
          if (unit != 0 || job == 1) {
            bulk_wait0();
            asm volatile("fence.proxy.async;" ::: "memory");
            __threadfence();
            if (unit == 0) {
              const unsigned int old = atomicAdd(&g_ab_cnt, 1u);
              if ((old & 127u) == 127u) *reinterpret_cast<volatile unsigned int*>(&g_epoch) = (old >> 7) + 1;
            } else {
              atomicAdd(&g_h_cnt[mt * 4 + unit - 1], 1u);
            }
          }
        }
        __syncwarp();
      }
    }
  } else {
    const int wg = warp >> 2;
    named_bar(8, 352);
    reg_inc<232>();
    cluster_wait();
    if (tid == 0) DBG(0, 3);

    uint32_t rel0, rel1;
    asm volatile("mapa.shared::cluster.u32 %0, %1, %2;" : "=r"(rel0) : "r"(bar_empty2), "r"(0));
    asm volatile("mapa.shared::cluster.u32 %0, %1, %2;" : "=r"(rel1) : "r"(bar_empty2), "r"(1));
    {
      K1Ctx c;
      c.sb = sb; c.bar_full = bar_full; c.lane0 = (lane == 0);
      c.rel0 = rel0 - 8 * (K1_NS + K2_NS); c.rel1 = rel1 - 8 * (K1_NS + K2_NS);
      c.bar_sfree = bar_empty2 + 8 * K2_NS + 8 + 8 * wg; c.sphase = 0;
      c.dA = make_desc(sb, 16, 1024);
      c.dBk = make_desc(sb + K1_B_OFF, 16, 1024);
      c.dBn = make_desc(sb + K1_B_OFF, 8192, 1024);
      if (wg == 0) {
        k1_unit_ab(c, warp, lane, mt, j);
        if (tid == 0) DBG(0, 6);
      }
#pragma unroll 1
      for (int unit = 2 - wg; unit < nunits; unit += 2) {
        k1_unit_gu(c, warp, lane, mt, unit, (unit == 4) ? fbh : fb0 + unit - 1, j & 1, (unit < 4) || u4full, nunits);
        if ((tid & 127) == 0) DBG(0, 6 + 3 * unit);
      }
    }

    float acc[112];
    unsigned int ticket = 0;
    const uint32_t dA0 = make_desc(sb + wg * 8192, 16, 1024);
    const uint32_t dB0 = make_desc(sb + 16384, 8192, 1024);
    int slot = 0; uint32_t ph = 0;
#pragma unroll 1
    for (int s = 0; s < nkb; s++) {
      if (s == nkb - 1 && tid == 0) ticket = atomicAdd(&g_flags[tile], 1u);
      mbar_wait(bar_full2 + 8 * slot, ph, 11);
      if (tid == 0) DBG(1, 1 + s);
      wg_fence();
      const uint32_t da = dA0 + slot * (K2_STAGE / 16);
      const uint32_t db = dB0 + slot * (K2_STAGE / 16);
#pragma unroll
      for (int k = 0; k < 4; k++) wgmma_n224_tb(acc, da + k * 2, db + k * 128, (s | k) != 0);
      wg_commit();
      if (s > 0) {
        wg_wait<1>();
        const int ps = (slot == 0) ? K2_NS - 1 : slot - 1;
        if (lane == 0) {
          asm volatile("mbarrier.arrive.shared::cluster.b64 _, [%0];" ::"r"(rel0 + 8 * ps) : "memory");
          asm volatile("mbarrier.arrive.shared::cluster.b64 _, [%0];" ::"r"(rel1 + 8 * ps) : "memory");
        }
      }
      if (++slot == K2_NS) { slot = 0; ph ^= 1; }
    }
    wg_wait<0>();
    if (tid == 0) DBG(1, 29);
    uint32_t ow[56];
#pragma unroll
    for (int i = 0; i < 56; i++) ow[i] = pack_bf16(acc[2 * i], acc[2 * i + 1]);
    if (q == 3) {
#pragma unroll
      for (int i = 0; i < 56; i++) ow[i] = pack_bf16(silu_f(bf_lo(ow[i])), silu_f(bf_hi(ow[i])));
    }
    const uint32_t tk_addr = bar_empty2 + 8 * K2_NS + 24;
    if (tid == 0) asm volatile("st.shared.u32 [%0], %1;" ::"r"(tk_addr), "r"(ticket) : "memory");
    named_bar(1, 256);
    asm volatile("ld.shared.u32 %0, [%1];" : "=r"(ticket) : "r"(tk_addr) : "memory");
    if ((ticket & 3u) != 3u) {
      uint4* part = g_part + (size_t)(tile * 4 + q) * (14 * 256) + tid;
#pragma unroll
      for (int g = 0; g < 14; g++) part[g * 256] = make_uint4(ow[4 * g], ow[4 * g + 1], ow[4 * g + 2], ow[4 * g + 3]);
      __threadfence();
      asm volatile("fence.proxy.async;" ::: "memory");
      named_bar(1, 256);
      if (tid == 0) atomicAdd(&g_flags[32 + tile], 1u);
    } else {
      const uint32_t bar_p = bar_empty2 + 8 * K2_NS;
      if (tid == 0) {
        spin_flag(&g_flags[32 + tile], 3u * ((ticket >> 2) + 1u));
        asm volatile("fence.proxy.async;" ::: "memory");
        mbar_expect(bar_p, 3 * 57344);
#pragma unroll 1
        for (int i = 0; i < 3; i++) bulk_load(sb + i * 57344, g_part + (size_t)(tile * 4 + (i < q ? i : i + 1)) * (14 * 256), 57344, bar_p);
        DBG(1, 30);
      }
      const int lc = (lane < 28) ? lane : 27;
      const size_t gbase = (size_t)(mt * 128 + warp * 16) * 448 + n * 224 + lc * 8;
      uint4 xv[16];
#pragma unroll
      for (int t = 0; t < 16; t++) xv[t] = ldg128_cg(x + gbase + t * 448);
      mbar_wait(bar_p, 0, 12);
      if (tid == 0) DBG(1, 62);
      const uint32_t tb = sb + tid * 16;
      const bool isf = (q == 3);
#pragma unroll
      for (int g = 0; g < 14; g++) {
        const uint4 a = lds128(tb + g * 4096), b = lds128(tb + (14 + g) * 4096), cc = lds128(tb + (28 + g) * 4096);
        const uint32_t av[4] = {a.x, a.y, a.z, a.w}, bv[4] = {b.x, b.y, b.z, b.w}, cv[4] = {cc.x, cc.y, cc.z, cc.w};
#pragma unroll
        for (int e = 0; e < 4; e++) {
          const uint32_t o = ow[4 * g + e];
          const uint32_t y3 = isf ? cv[e] : o, gg = isf ? o : cv[e];
          ow[4 * g + e] = hmul2_bf16(pack_bf16(bf_lo(av[e]) + bf_lo(bv[e]) + bf_lo(y3), bf_hi(av[e]) + bf_hi(bv[e]) + bf_hi(y3)), gg);
        }
      }
      named_bar(1, 256);
      const uint32_t wbase = sb + warp * 16 * K2_PITCH;
      const int st_row = (lane & 7) + 8 * ((lane >> 3) & 1);
      const uint32_t sa = wbase + st_row * K2_PITCH + (lane >> 4) * 16;
#pragma unroll
      for (int g = 0; g < 28; g += 2) stmatrix_x4(sa + g * 16, ow[2 * g], ow[2 * g + 1], ow[2 * g + 2], ow[2 * g + 3]);
      __syncwarp();
      const uint32_t lp = wbase + lc * 16;
#pragma unroll
      for (int t = 0; t < 16; t++) {
        const uint4 tv = lds128(lp + t * K2_PITCH);
        uint4 o;
        o.x = hadd2_bf16(xv[t].x, tv.x); o.y = hadd2_bf16(xv[t].y, tv.y); o.z = hadd2_bf16(xv[t].z, tv.z); o.w = hadd2_bf16(xv[t].w, tv.w);
        if (lane < 28) stg128(out + gbase + t * 448, o);
      }
    }
    if (tid == 0) DBG(1, 63);
  }
  __syncwarp();
  cluster_arrive_relaxed();
  cluster_wait();
}

typedef CUresult (*EncFn)(CUtensorMap*, CUtensorMapDataType, cuuint32_t, void*, const cuuint64_t*, const cuuint64_t*, const cuuint32_t*,
                          const cuuint32_t*, CUtensorMapInterleave, CUtensorMapSwizzle, CUtensorMapL2promotion, CUtensorMapFloatOOBfill);

void make2d(EncFn enc, CUtensorMap* tm, const void* ptr, uint64_t cols, uint64_t rows, uint32_t bc, uint32_t br, bool swz = true) {
  cuuint64_t gd[2] = {cols, rows};
  cuuint64_t gs[1] = {cols * 2};
  cuuint32_t bd[2] = {bc, br};
  cuuint32_t es[2] = {1, 1};
  enc(tm, CU_TENSOR_MAP_DATA_TYPE_BFLOAT16, 2, const_cast<void*>(ptr), gd, gs, bd, es, CU_TENSOR_MAP_INTERLEAVE_NONE,
      swz ? CU_TENSOR_MAP_SWIZZLE_128B : CU_TENSOR_MAP_SWIZZLE_NONE, CU_TENSOR_MAP_L2_PROMOTION_L2_128B, CU_TENSOR_MAP_FLOAT_OOB_FILL_NONE);
}
void make3d_half(EncFn enc, CUtensorMap* tm, const void* ptr, uint64_t rows) {
  cuuint64_t gd[3] = {224, 2, rows};
  cuuint64_t gs[2] = {448, 896};
  cuuint32_t bd[3] = {64, 1, 64};
  cuuint32_t es[3] = {1, 1, 1};
  enc(tm, CU_TENSOR_MAP_DATA_TYPE_BFLOAT16, 3, const_cast<void*>(ptr), gd, gs, bd, es, CU_TENSOR_MAP_INTERLEAVE_NONE,
      CU_TENSOR_MAP_SWIZZLE_128B, CU_TENSOR_MAP_L2_PROMOTION_L2_128B, CU_TENSOR_MAP_FLOAT_OOB_FILL_NONE);
}

struct Maps { CUtensorMap wr, wi, wg, wu, cr, ci, h, ab, wd, hs, abs; };

}

extern "C" void kernel_launch(void* const* d_in, const int* in_sizes, int n_in, void* d_out, int out_size) {
  (void)in_sizes; (void)n_in; (void)out_size;
  static Maps maps;
  static const void* cached[9] = {nullptr};
  static bool attr_done = false;
  bool same = true;
  for (int i = 0; i < 9; i++) same = same && (cached[i] == d_in[i]);
  if (!same) {
    void* fn = nullptr;
    cudaDriverEntryPointQueryResult qr;
    cudaGetDriverEntryPoint("cuTensorMapEncodeTiled", &fn, cudaEnableDefault, &qr);
    EncFn enc = (EncFn)fn;
    void *p_ab = nullptr, *p_h = nullptr;
    cudaGetSymbolAddress(&p_ab, g_ab);
    cudaGetSymbolAddress(&p_h, g_h);
    make2d(enc, &maps.cr, d_in[1], 2048, 2048, 64, 128);
    make2d(enc, &maps.ci, d_in[2], 2048, 2048, 64, 128);
    make2d(enc, &maps.wr, d_in[3], 448, 448, 64, 56);
    make2d(enc, &maps.wi, d_in[4], 448, 448, 64, 56);
    make2d(enc, &maps.wg, d_in[6], 1792, 448, 64, 64);
    make2d(enc, &maps.wu, d_in[7], 1792, 448, 64, 64);
    make3d_half(enc, &maps.wd, d_in[8], 1792);
    make2d(enc, &maps.h, p_h, 1792, 2048, 64, 128);
    make3d_half(enc, &maps.ab, p_ab, 4096);
    make2d(enc, &maps.hs, p_h, 1792, 2048, 64, 64);
    make2d(enc, &maps.abs, p_ab, 448, 4096, 112, 64, false);
    for (int i = 0; i < 9; i++) cached[i] = d_in[i];
  }
  if (!attr_done) {
    cudaFuncSetAttribute(fused_kernel, cudaFuncAttributeMaxDynamicSharedMemorySize, K1_SMEM);
    attr_done = true;
  }
  PfPtrs pf;
  pf.wg = (const uint8_t*)d_in[6]; pf.wu = (const uint8_t*)d_in[7]; pf.wd = (const uint8_t*)d_in[8];
  fused_kernel<<<128, 384, K1_SMEM>>>(maps.wr, maps.wi, maps.wg, maps.wu, maps.hs, maps.abs, maps.cr, maps.ci, maps.h, maps.ab, maps.wd,
                                      (const __nv_bfloat16*)d_in[0], (__nv_bfloat16*)d_out, pf);
}
```

```cpp
#include <cuda_runtime.h>
#include <cuda_bf16.h>
#include <cuda.h>
#include <stdint.h>

namespace {

__device__ __align__(1024) __nv_bfloat16 g_ab[4096 * 448];
__device__ __align__(1024) __nv_bfloat16 g_h[2048 * 1792];
__device__ uint4 g_part[32 * 3 * 14 * 256];
__device__ __align__(1024) __nv_bfloat16 g_s[2048 * 448];
__device__ unsigned int g_epoch;
__device__ unsigned int g_ab_cnt;
__device__ unsigned int g_h_cnt[16 * 4];
__device__ unsigned int g_flags[64];

#define DBG(k, i) do {} while (0)
#define DBGC(k, i) do {} while (0)

#define TIMEOUT(code) __trap()
#define SPIN_LIMIT (1 << 22)
__device__ __forceinline__ uint32_t s2u(const void* p) { return (uint32_t)__cvta_generic_to_shared(p); }
__device__ __forceinline__ void mbar_init(uint32_t b, int c) { asm volatile("mbarrier.init.shared::cta.b64 [%0], %1;" ::"r"(b), "r"(c)); }
__device__ __forceinline__ void mbar_expect(uint32_t b, uint32_t bytes) {
  asm volatile("mbarrier.arrive.expect_tx.shared::cta.b64 _, [%0], %1;" ::"r"(b), "r"(bytes) : "memory");
}
__device__ __forceinline__ void mbar_wait(uint32_t b, uint32_t ph, int code = 1) {
  uint32_t done = 0;
  int it = 0;
  while (true) {
    asm volatile("{.reg .pred p; mbarrier.try_wait.parity.shared::cta.b64 p, [%1], %2; selp.u32 %0,1,0,p;}" : "=r"(done) : "r"(b), "r"(ph) : "memory");
    if (done) break;
    if (++it > SPIN_LIMIT) { TIMEOUT(code); break; }
  }
}
__device__ __forceinline__ void mbar_arrive_cluster(uint32_t b, uint32_t cta) {
  uint32_t r;
  asm volatile("mapa.shared::cluster.u32 %0, %1, %2;" : "=r"(r) : "r"(b), "r"(cta));
  asm volatile("mbarrier.arrive.shared::cluster.b64 _, [%0];" ::"r"(r) : "memory");
}
__device__ __forceinline__ void tma2d(uint32_t dst, const CUtensorMap* m, int c0, int c1, uint32_t bar) {
  asm volatile("cp.async.bulk.tensor.2d.shared::cluster.global.mbarrier::complete_tx::bytes [%0], [%1, {%3,%4}], [%2];" ::"r"(dst), "l"(m), "r"(bar), "r"(c0), "r"(c1) : "memory");
}
__device__ __forceinline__ void tma2d_mc(uint32_t dst, const CUtensorMap* m, int c0, int c1, uint32_t bar, uint16_t mask) {
  asm volatile("cp.async.bulk.tensor.2d.shared::cluster.global.mbarrier::complete_tx::bytes.multicast::cluster [%0], [%1, {%3,%4}], [%2], %5;" ::"r"(dst), "l"(m), "r"(bar), "r"(c0), "r"(c1), "h"(mask) : "memory");
}
__device__ __forceinline__ void tma3d_mc(uint32_t dst, const CUtensorMap* m, int c0, int c1, int c2, uint32_t bar, uint16_t mask) {
  asm volatile("cp.async.bulk.tensor.3d.shared::cluster.global.mbarrier::complete_tx::bytes.multicast::cluster [%0], [%1, {%3,%4,%5}], [%2], %6;" ::"r"(dst), "l"(m), "r"(bar), "r"(c0), "r"(c1), "r"(c2), "h"(mask) : "memory");
}
__device__ __forceinline__ void tma2d_store(const CUtensorMap* m, uint32_t src, int c0, int c1) {
  asm volatile("cp.async.bulk.tensor.2d.global.shared::cta.bulk_group [%0, {%2,%3}], [%1];" ::"l"(m), "r"(src), "r"(c0), "r"(c1) : "memory");
}
__device__ __forceinline__ void bulk_load(uint32_t dst, const void* src, uint32_t bytes, uint32_t bar) {
  asm volatile("cp.async.bulk.shared::cluster.global.mbarrier::complete_tx::bytes [%0], [%1], %2, [%3];" ::"r"(dst), "l"(src), "r"(bytes), "r"(bar) : "memory");
}
__device__ __forceinline__ void tma2d_prefetch(const CUtensorMap* m, int c0, int c1) {
  asm volatile("cp.async.bulk.prefetch.tensor.2d.L2.global [%0, {%1,%2}];" ::"l"(m), "r"(c0), "r"(c1) : "memory");
}
__device__ __forceinline__ void bulk_commit() { asm volatile("cp.async.bulk.commit_group;" ::: "memory"); }
__device__ __forceinline__ void bulk_wait_read0() { asm volatile("cp.async.bulk.wait_group.read 0;" ::: "memory"); }
__device__ __forceinline__ void bulk_wait0() { asm volatile("cp.async.bulk.wait_group 0;" ::: "memory"); }
__device__ __forceinline__ void fence_async_smem() { asm volatile("fence.proxy.async.shared::cta;" ::: "memory"); }
__device__ __forceinline__ void prefetch_tmap(const CUtensorMap* m) { asm volatile("prefetch.tensormap [%0];" ::"l"(m) : "memory"); }
__device__ __forceinline__ void l2_prefetch(const void* p, uint32_t bytes) {
  asm volatile("cp.async.bulk.prefetch.L2.global [%0], %1;" ::"l"(p), "r"(bytes) : "memory");
}
__device__ __forceinline__ void cluster_arrive_relaxed() { asm volatile("barrier.cluster.arrive.relaxed.aligned;" ::: "memory"); }
__device__ __forceinline__ void cluster_wait() { asm volatile("barrier.cluster.wait.aligned;" ::: "memory"); }
__device__ __forceinline__ void wg_fence() { __syncwarp(); asm volatile("wgmma.fence.sync.aligned;" ::: "memory"); }
__device__ __forceinline__ void wg_commit() { asm volatile("wgmma.commit_group.sync.aligned;" ::: "memory"); }
template <int N> __device__ __forceinline__ void wg_wait() { __syncwarp(); asm volatile("wgmma.wait_group.sync.aligned %0;" ::"n"(N) : "memory"); }
__device__ __forceinline__ void named_bar(int id, int n) { asm volatile("bar.sync %0, %1;" ::"r"(id), "r"(n) : "memory"); }
__device__ __forceinline__ void named_arrive(int id, int n) { asm volatile("bar.arrive %0, %1;" ::"r"(id), "r"(n) : "memory"); }
template <int N> __device__ __forceinline__ void reg_inc() { asm volatile("setmaxnreg.inc.sync.aligned.u32 %0;" ::"n"(N)); }
template <int N> __device__ __forceinline__ void reg_dec() { asm volatile("setmaxnreg.dec.sync.aligned.u32 %0;" ::"n"(N)); }
__device__ __forceinline__ void pdl_wait() { asm volatile("griddepcontrol.wait;" ::: "memory"); }
__device__ __forceinline__ void pdl_launch() { asm volatile("griddepcontrol.launch_dependents;" ::: "memory"); }

__device__ __forceinline__ uint32_t make_desc(uint32_t addr, uint32_t lbo, uint32_t  ) {
  return ((addr & 0x3FFFF) >> 4) | ((lbo >> 4) << 16);
}
__device__ __forceinline__ void stmatrix_x4(uint32_t addr, uint32_t r0, uint32_t r1, uint32_t r2, uint32_t r3) {
  asm volatile("stmatrix.sync.aligned.m8n8.x4.shared.b16 [%0], {%1,%2,%3,%4};" ::"r"(addr), "r"(r0), "r"(r1), "r"(r2), "r"(r3) : "memory");
}
__device__ __forceinline__ uint4 lds128(uint32_t a) {
  uint4 v;
  asm volatile("ld.shared.v4.u32 {%0,%1,%2,%3}, [%4];" : "=r"(v.x), "=r"(v.y), "=r"(v.z), "=r"(v.w) : "r"(a) : "memory");
  return v;
}
__device__ __forceinline__ void sts128(uint32_t a, uint4 v) {
  asm volatile("st.shared.v4.u32 [%0], {%1,%2,%3,%4};" ::"r"(a), "r"(v.x), "r"(v.y), "r"(v.z), "r"(v.w) : "memory");
}
__device__ __forceinline__ void stg128(void* p, uint4 v) {
  asm volatile("st.global.v4.u32 [%0], {%1,%2,%3,%4};" ::"l"(p), "r"(v.x), "r"(v.y), "r"(v.z), "r"(v.w) : "memory");
}
__device__ __forceinline__ void cp_async16(uint32_t dst, const void* src) {
  asm volatile("cp.async.cg.shared.global [%0], [%1], 16;" ::"r"(dst), "l"(src) : "memory");
}
__device__ __forceinline__ void cp_async8(uint32_t dst, const void* src) {
  asm volatile("cp.async.ca.shared.global [%0], [%1], 8;" ::"r"(dst), "l"(src) : "memory");
}
__device__ __forceinline__ uint2 lds64(uint32_t a) {
  uint2 v;
  asm volatile("ld.shared.v2.u32 {%0,%1}, [%2];" : "=r"(v.x), "=r"(v.y) : "r"(a) : "memory");
  return v;
}
__device__ __forceinline__ void cp_async_wait_all() { asm volatile("cp.async.wait_all;" ::: "memory"); }
__device__ __forceinline__ uint32_t pack_bf16(float lo, float hi) {
  uint32_t r;
  asm("cvt.rn.bf16x2.f32 %0, %1, %2;" : "=r"(r) : "f"(hi), "f"(lo));
  return r;
}
__device__ __forceinline__ uint32_t hmul2_bf16(uint32_t a, uint32_t b) {
  uint32_t r;
  asm("mul.rn.bf16x2 %0, %1, %2;" : "=r"(r) : "r"(a), "r"(b));
  return r;
}
__device__ __forceinline__ uint32_t hsub2_bf16(uint32_t a, uint32_t b) {
  uint32_t r;
  asm("sub.rn.bf16x2 %0, %1, %2;" : "=r"(r) : "r"(a), "r"(b));
  return r;
}
__device__ __forceinline__ uint32_t hadd2_bf16(uint32_t a, uint32_t b) {
  uint32_t r;
  asm("add.rn.bf16x2 %0, %1, %2;" : "=r"(r) : "r"(a), "r"(b));
  return r;
}
__device__ __forceinline__ uint32_t hfma2_bf16(uint32_t a, uint32_t b, uint32_t c) {
  uint32_t r;
  asm("fma.rn.bf16x2 %0, %1, %2, %3;" : "=r"(r) : "r"(a), "r"(b), "r"(c));
  return r;
}
__device__ __forceinline__ bool mbar_test(uint32_t b, uint32_t ph) {
  uint32_t done;
  asm volatile("{.reg .pred p; mbarrier.test_wait.parity.shared::cta.b64 p, [%1], %2; selp.u32 %0,1,0,p;}" : "=r"(done) : "r"(b), "r"(ph) : "memory");
  return __all_sync(0xffffffffu, done != 0);
}
__device__ __forceinline__ uint4 ldg128_cg(const void* p) {
  uint4 v;
  asm volatile("ld.global.cg.v4.u32 {%0,%1,%2,%3}, [%4];" : "=r"(v.x), "=r"(v.y), "=r"(v.z), "=r"(v.w) : "l"(p) : "memory");
  return v;
}
__device__ __forceinline__ float bf_lo(uint32_t w) { return __uint_as_float(w << 16); }
__device__ __forceinline__ float bf_hi(uint32_t w) { return __uint_as_float(w & 0xffff0000u); }
__device__ __forceinline__ float rbf(float x) { return __bfloat162float(__float2bfloat16_rn(x)); }
__device__ __forceinline__ float ex2f(float x) { float r; asm("ex2.approx.ftz.f32 %0, %1;" : "=f"(r) : "f"(x)); return r; }
__device__ __forceinline__ float rcpf(float x) { float r; asm("rcp.approx.ftz.f32 %0, %1;" : "=f"(r) : "f"(x)); return r; }
__device__ __forceinline__ float tanhf_hw(float x) { float r; asm("tanh.approx.f32 %0, %1;" : "=f"(r) : "f"(x)); return r; }
__device__ __forceinline__ float gelu_tanh(float x) {
  const float c1 = 0.7978845608028654f;
  const float c2 = c1 * 0.044715f;
  const float t = tanhf_hw(x * fmaf(c2, x * x, c1));
  const float hx = 0.5f * x;
  return fmaf(hx, t, hx);
}
__device__ __forceinline__ float silu_f(float x) {
  const float hx = 0.5f * x;
  return fmaf(hx, tanhf_hw(hx), hx);
}

__device__ __forceinline__ void wgmma_n128_tb(float (&d)[64], uint32_t da, uint32_t db, int scale_d) {
  asm volatile(
    "{\n.reg .pred p;\n.reg .b64 da, db;\nsetp.ne.b32 p, %66, 0;\n"
    "mov.b64 da, {%64, 0x40000040};\nmov.b64 db, {%65, 0x40000040};\n"
    "wgmma.mma_async.sync.aligned.m64n128k16.f32.bf16.bf16 {%0, %1, %2, %3, %4, %5, %6, %7, %8, %9, %10, %11, %12, %13, %14, %15, %16, %17, %18, %19, %20, %21, %22, %23, %24, %25, %26, %27, %28, %29, %30, %31, %32, %33, %34, %35, %36, %37, %38, %39, %40, %41, %42, %43, %44, %45, %46, %47, %48, %49, %50, %51, %52, %53, %54, %55, %56, %57, %58, %59, %60, %61, %62, %63}, da, db, p, 1, 1, 0, 1;\n}\n"
    : "+f"(d[0]), "+f"(d[1]), "+f"(d[2]), "+f"(d[3]), "+f"(d[4]), "+f"(d[5]), "+f"(d[6]), "+f"(d[7]), "+f"(d[8]), "+f"(d[9]), "+f"(d[10]), "+f"(d[11]), "+f"(d[12]), "+f"(d[13]), "+f"(d[14]), "+f"(d[15]), "+f"(d[16]), "+f"(d[17]), "+f"(d[18]), "+f"(d[19]), "+f"(d[20]), "+f"(d[21]), "+f"(d[22]), "+f"(d[23]), "+f"(d[24]), "+f"(d[25]), "+f"(d[26]), "+f"(d[27]), "+f"(d[28]), "+f"(d[29]), "+f"(d[30]), "+f"(d[31]), "+f"(d[32]), "+f"(d[33]), "+f"(d[34]), "+f"(d[35]), "+f"(d[36]), "+f"(d[37]), "+f"(d[38]), "+f"(d[39]), "+f"(d[40]), "+f"(d[41]), "+f"(d[42]), "+f"(d[43]), "+f"(d[44]), "+f"(d[45]), "+f"(d[46]), "+f"(d[47]), "+f"(d[48]), "+f"(d[49]), "+f"(d[50]), "+f"(d[51]), "+f"(d[52]), "+f"(d[53]), "+f"(d[54]), "+f"(d[55]), "+f"(d[56]), "+f"(d[57]), "+f"(d[58]), "+f"(d[59]), "+f"(d[60]), "+f"(d[61]), "+f"(d[62]), "+f"(d[63])
    : "r"(da), "r"(db), "r"(scale_d));
}
__device__ __forceinline__ void wgmma_n128_tb_p(float (&d)[64], uint32_t da, uint32_t db, int scale_d, int enable) {
  asm volatile(
    "{\n.reg .pred p;\n.reg .b64 da, db;\nsetp.ne.b32 p, %66, 0;\n.reg .pred q;\nsetp.ne.b32 q, %67, 0;\n"
    "mov.b64 da, {%64, 0x40000040};\nmov.b64 db, {%65, 0x40000040};\n"
    "@q wgmma.mma_async.sync.aligned.m64n128k16.f32.bf16.bf16 {%0, %1, %2, %3, %4, %5, %6, %7, %8, %9, %10, %11, %12, %13, %14, %15, %16, %17, %18, %19, %20, %21, %22, %23, %24, %25, %26, %27, %28, %29, %30, %31, %32, %33, %34, %35, %36, %37, %38, %39, %40, %41, %42, %43, %44, %45, %46, %47, %48, %49, %50, %51, %52, %53, %54, %55, %56, %57, %58, %59, %60, %61, %62, %63}, da, db, p, 1, 1, 0, 1;\n}\n"
    : "+f"(d[0]), "+f"(d[1]), "+f"(d[2]), "+f"(d[3]), "+f"(d[4]), "+f"(d[5]), "+f"(d[6]), "+f"(d[7]), "+f"(d[8]), "+f"(d[9]), "+f"(d[10]), "+f"(d[11]), "+f"(d[12]), "+f"(d[13]), "+f"(d[14]), "+f"(d[15]), "+f"(d[16]), "+f"(d[17]), "+f"(d[18]), "+f"(d[19]), "+f"(d[20]), "+f"(d[21]), "+f"(d[22]), "+f"(d[23]), "+f"(d[24]), "+f"(d[25]), "+f"(d[26]), "+f"(d[27]), "+f"(d[28]), "+f"(d[29]), "+f"(d[30]), "+f"(d[31]), "+f"(d[32]), "+f"(d[33]), "+f"(d[34]), "+f"(d[35]), "+f"(d[36]), "+f"(d[37]), "+f"(d[38]), "+f"(d[39]), "+f"(d[40]), "+f"(d[41]), "+f"(d[42]), "+f"(d[43]), "+f"(d[44]), "+f"(d[45]), "+f"(d[46]), "+f"(d[47]), "+f"(d[48]), "+f"(d[49]), "+f"(d[50]), "+f"(d[51]), "+f"(d[52]), "+f"(d[53]), "+f"(d[54]), "+f"(d[55]), "+f"(d[56]), "+f"(d[57]), "+f"(d[58]), "+f"(d[59]), "+f"(d[60]), "+f"(d[61]), "+f"(d[62]), "+f"(d[63])
    : "r"(da), "r"(db), "r"(scale_d), "r"(enable));
}
__device__ __forceinline__ void wgmma_n112(float (&d)[56], uint32_t da, uint32_t db, int scale_d) {
  asm volatile(
    "{\n.reg .pred p;\n.reg .b64 da, db;\nsetp.ne.b32 p, %58, 0;\n"
    "mov.b64 da, {%56, 0x40000040};\nmov.b64 db, {%57, 0x40000040};\n"
    "wgmma.mma_async.sync.aligned.m64n112k16.f32.bf16.bf16 {%0, %1, %2, %3, %4, %5, %6, %7, %8, %9, %10, %11, %12, %13, %14, %15, %16, %17, %18, %19, %20, %21, %22, %23, %24, %25, %26, %27, %28, %29, %30, %31, %32, %33, %34, %35, %36, %37, %38, %39, %40, %41, %42, %43, %44, %45, %46, %47, %48, %49, %50, %51, %52, %53, %54, %55}, da, db, p, 1, 1, 0, 0;\n}\n"
    : "+f"(d[0]), "+f"(d[1]), "+f"(d[2]), "+f"(d[3]), "+f"(d[4]), "+f"(d[5]), "+f"(d[6]), "+f"(d[7]), "+f"(d[8]), "+f"(d[9]), "+f"(d[10]), "+f"(d[11]), "+f"(d[12]), "+f"(d[13]), "+f"(d[14]), "+f"(d[15]), "+f"(d[16]), "+f"(d[17]), "+f"(d[18]), "+f"(d[19]), "+f"(d[20]), "+f"(d[21]), "+f"(d[22]), "+f"(d[23]), "+f"(d[24]), "+f"(d[25]), "+f"(d[26]), "+f"(d[27]), "+f"(d[28]), "+f"(d[29]), "+f"(d[30]), "+f"(d[31]), "+f"(d[32]), "+f"(d[33]), "+f"(d[34]), "+f"(d[35]), "+f"(d[36]), "+f"(d[37]), "+f"(d[38]), "+f"(d[39]), "+f"(d[40]), "+f"(d[41]), "+f"(d[42]), "+f"(d[43]), "+f"(d[44]), "+f"(d[45]), "+f"(d[46]), "+f"(d[47]), "+f"(d[48]), "+f"(d[49]), "+f"(d[50]), "+f"(d[51]), "+f"(d[52]), "+f"(d[53]), "+f"(d[54]), "+f"(d[55])
    : "r"(da), "r"(db), "r"(scale_d));
}
__device__ __forceinline__ void wgmma_n224_tb(float (&d)[112], uint32_t da, uint32_t db, int scale_d) {
  asm volatile(
    "{\n.reg .pred p;\n.reg .b64 da, db;\nsetp.ne.b32 p, %114, 0;\n"
    "mov.b64 da, {%112, 0x40000040};\nmov.b64 db, {%113, 0x40000040};\n"
    "wgmma.mma_async.sync.aligned.m64n224k16.f32.bf16.bf16 {%0, %1, %2, %3, %4, %5, %6, %7, %8, %9, %10, %11, %12, %13, %14, %15, %16, %17, %18, %19, %20, %21, %22, %23, %24, %25, %26, %27, %28, %29, %30, %31, %32, %33, %34, %35, %36, %37, %38, %39, %40, %41, %42, %43, %44, %45, %46, %47, %48, %49, %50, %51, %52, %53, %54, %55, %56, %57, %58, %59, %60, %61, %62, %63, %64, %65, %66, %67, %68, %69, %70, %71, %72, %73, %74, %75, %76, %77, %78, %79, %80, %81, %82, %83, %84, %85, %86, %87, %88, %89, %90, %91, %92, %93, %94, %95, %96, %97, %98, %99, %100, %101, %102, %103, %104, %105, %106, %107, %108, %109, %110, %111}, da, db, p, 1, 1, 0, 1;\n}\n"
    : "+f"(d[0]), "+f"(d[1]), "+f"(d[2]), "+f"(d[3]), "+f"(d[4]), "+f"(d[5]), "+f"(d[6]), "+f"(d[7]), "+f"(d[8]), "+f"(d[9]), "+f"(d[10]), "+f"(d[11]), "+f"(d[12]), "+f"(d[13]), "+f"(d[14]), "+f"(d[15]), "+f"(d[16]), "+f"(d[17]), "+f"(d[18]), "+f"(d[19]), "+f"(d[20]), "+f"(d[21]), "+f"(d[22]), "+f"(d[23]), "+f"(d[24]), "+f"(d[25]), "+f"(d[26]), "+f"(d[27]), "+f"(d[28]), "+f"(d[29]), "+f"(d[30]), "+f"(d[31]), "+f"(d[32]), "+f"(d[33]), "+f"(d[34]), "+f"(d[35]), "+f"(d[36]), "+f"(d[37]), "+f"(d[38]), "+f"(d[39]), "+f"(d[40]), "+f"(d[41]), "+f"(d[42]), "+f"(d[43]), "+f"(d[44]), "+f"(d[45]), "+f"(d[46]), "+f"(d[47]), "+f"(d[48]), "+f"(d[49]), "+f"(d[50]), "+f"(d[51]), "+f"(d[52]), "+f"(d[53]), "+f"(d[54]), "+f"(d[55]), "+f"(d[56]), "+f"(d[57]), "+f"(d[58]), "+f"(d[59]), "+f"(d[60]), "+f"(d[61]), "+f"(d[62]), "+f"(d[63]), "+f"(d[64]), "+f"(d[65]), "+f"(d[66]), "+f"(d[67]), "+f"(d[68]), "+f"(d[69]), "+f"(d[70]), "+f"(d[71]), "+f"(d[72]), "+f"(d[73]), "+f"(d[74]), "+f"(d[75]), "+f"(d[76]), "+f"(d[77]), "+f"(d[78]), "+f"(d[79]), "+f"(d[80]), "+f"(d[81]), "+f"(d[82]), "+f"(d[83]), "+f"(d[84]), "+f"(d[85]), "+f"(d[86]), "+f"(d[87]), "+f"(d[88]), "+f"(d[89]), "+f"(d[90]), "+f"(d[91]), "+f"(d[92]), "+f"(d[93]), "+f"(d[94]), "+f"(d[95]), "+f"(d[96]), "+f"(d[97]), "+f"(d[98]), "+f"(d[99]), "+f"(d[100]), "+f"(d[101]), "+f"(d[102]), "+f"(d[103]), "+f"(d[104]), "+f"(d[105]), "+f"(d[106]), "+f"(d[107]), "+f"(d[108]), "+f"(d[109]), "+f"(d[110]), "+f"(d[111])
    : "r"(da), "r"(db), "r"(scale_d));
}

constexpr int K1_NS = 5;
constexpr int K1_A_BYTES = 7 * 16384;
constexpr int K1_B_OFF = K1_A_BYTES;
constexpr int K1_STG_OFF = K1_B_OFF + K1_NS * 16384;
constexpr int K1_BAR_OFF = K1_STG_OFF + 8 * 4096;
constexpr int K1_SMEM = K1_BAR_OFF + 256 + 1024;

struct K1Ctx {
  uint32_t sb, bar_full, rel0, rel1;
  uint32_t dA, dBk, dBn;
  bool lane0;
  uint32_t bar_sfree;
  uint32_t sphase;
};
__device__ __forceinline__ void k1_release(const K1Ctx& c, int slot) {
  if (c.lane0) {
    asm volatile("mbarrier.arrive.shared::cluster.b64 _, [%0];" ::"r"(c.rel0 + 8 * slot) : "memory");
    asm volatile("mbarrier.arrive.shared::cluster.b64 _, [%0];" ::"r"(c.rel1 + 8 * slot) : "memory");
  }
}

__device__ __forceinline__ void k1_unit_ab(K1Ctx& c, int warp, int lane, int mt, int j) {
  const int wq = warp & 3;
  const int st_row = (lane & 7) + 8 * ((lane >> 3) & 1);
  const int st_chunk = lane >> 4;
  float acc[2][56];
  int slot = 0; uint32_t ph = 0;
#pragma unroll 1
  for (int kb = 0; kb < 7; kb++) {
    const int pslot = (slot == 0) ? K1_NS - 1 : slot - 1;
    mbar_wait(c.bar_full + 8 * slot, ph, 3);
    if (kb == 6) named_arrive(2, 256);
    if (kb == 0 && (threadIdx.x & 127) == 0) DBG(0, 4);
    if ((threadIdx.x & 127) == 0) DBGC(1, 46 + kb);
    wg_fence();
    const uint32_t da = c.dA + kb * 1024;
    const uint32_t db = c.dBk + slot * 1024;
#pragma unroll
    for (int k = 0; k < 4; k++) {
      wgmma_n112(acc[0], da + k * 2, db + k * 2, (kb | k) != 0);
      wgmma_n112(acc[1], da + 512 + k * 2, db + k * 2, (kb | k) != 0);
    }
    wg_commit();
    if (kb > 0) { wg_wait<1>(); k1_release(c, pslot); }
    if (++slot == K1_NS) { slot = 0; ph ^= 1; }
  }
  wg_wait<0>();
  k1_release(c, 6 % K1_NS);
  if ((threadIdx.x & 127) == 0) DBG(0, 5);
  const uint32_t sgn = (j < 4) ? 0u : 0x80008000u;
  const uint32_t sa = c.sb + K1_STG_OFF + (wq * 16 + st_row) * 224 + st_chunk * 16;
#pragma unroll
  for (int h = 0; h < 2; h++) {
    if (h == 1) { mbar_wait(c.bar_sfree, c.sphase, 6); c.sphase ^= 1; }
#pragma unroll
    for (int g = 0; g < 14; g += 2) {
      const float* a = &acc[h][4 * g];
      stmatrix_x4(sa + g * 16, pack_bf16(a[0], a[1]) ^ sgn, pack_bf16(a[2], a[3]) ^ sgn, pack_bf16(a[4], a[5]) ^ sgn, pack_bf16(a[6], a[7]) ^ sgn);
    }
    fence_async_smem();
    named_arrive(6, 160);
  }
}

__device__ __forceinline__ void k1_unit_gu(K1Ctx& c, int warp, int lane, int mt, int unit, int fb, int hsel, int full, int nunits) {
  const int wq = warp & 3;
  float acc[2][64];
  const uint32_t dA0 = c.dA + (full ? 0 : hsel * 512);
  int slot = (unit * 7) % K1_NS; uint32_t ph = ((unit * 7) / K1_NS) & 1;
  named_bar(2 + ((unit - 1) & 1), 256);
  if (full) {
#pragma unroll 1
    for (int kb = 0; kb < 7; kb++) {
      const int pslot = (slot == 0) ? K1_NS - 1 : slot - 1;
      mbar_wait(c.bar_full + 8 * slot, ph, 4);
      if (kb == 6 && unit + 1 < nunits) named_arrive(2 + (unit & 1), 256);
      if (kb == 0 && (threadIdx.x & 127) == 0) DBG(0, 4 + 3 * unit);
      wg_fence();
      const uint32_t da = dA0 + kb * 1024;
      const uint32_t db = c.dBn + slot * 1024;
#pragma unroll
      for (int k = 0; k < 4; k++) {
        wgmma_n128_tb(acc[0], da + k * 2, db + k * 128, (kb | k) != 0);
        wgmma_n128_tb(acc[1], da + 512 + k * 2, db + k * 128, (kb | k) != 0);
      }
      wg_commit();
      if (kb > 0) { wg_wait<1>(); k1_release(c, pslot); }
      if (++slot == K1_NS) { slot = 0; ph ^= 1; }
    }
  } else {
#pragma unroll 1
    for (int kb = 0; kb < 7; kb++) {
      const int pslot = (slot == 0) ? K1_NS - 1 : slot - 1;
      mbar_wait(c.bar_full + 8 * slot, ph, 5);
      if (kb == 0 && (threadIdx.x & 127) == 0) DBG(0, 4 + 3 * unit);
      wg_fence();
      const uint32_t da = dA0 + kb * 1024;
      const uint32_t db = c.dBn + slot * 1024;
#pragma unroll
      for (int k = 0; k < 4; k++) wgmma_n128_tb(acc[0], da + k * 2, db + k * 128, (kb | k) != 0);
      wg_commit();
      if (kb > 0) { wg_wait<1>(); k1_release(c, pslot); }
      if (++slot == K1_NS) { slot = 0; ph ^= 1; }
    }
  }
  wg_wait<0>();
  k1_release(c, (slot == 0) ? K1_NS - 1 : slot - 1);
  if (unit + 2 >= nunits && lane < 4) {
    asm volatile("mbarrier.arrive.shared::cluster.b64 _, [%0];" ::"r"(c.rel0 + 8 * (K1_NS + 4 + lane)) : "memory");
    asm volatile("mbarrier.arrive.shared::cluster.b64 _, [%0];" ::"r"(c.rel1 + 8 * (K1_NS + 4 + lane)) : "memory");
  }
  if ((threadIdx.x & 127) == 0) DBG(0, 5 + 3 * unit);
  const int st_row = (lane & 7) + 8 * ((lane >> 3) & 1);
  const int st_chunk = lane >> 4;
  const uint32_t sa = c.sb + K1_STG_OFF + (warp >> 2) * 16384 + (wq * 16 + st_row) * 128;
  if (unit >= 2) { mbar_wait(c.bar_sfree, c.sphase, 7); c.sphase ^= 1; }
#pragma unroll
  for (int h = 0; h < 2; h++) {
    if (h == 1 && !full) break;
#pragma unroll
    for (int g = 0; g < 8; g += 2) {
      uint32_t pk[4];
#pragma unroll
      for (int e = 0; e < 4; e++) {
        const int i = 4 * g + 2 * e;
        const uint32_t g2 = pack_bf16(acc[h][i], acc[h][i + 1]);
        const uint32_t u2 = pack_bf16(acc[h][32 + i], acc[h][32 + i + 1]);
        pk[e] = hmul2_bf16(pack_bf16(gelu_tanh(bf_lo(g2)), gelu_tanh(bf_hi(g2))), u2);
      }
      stmatrix_x4(sa + h * 8192 + (((g + st_chunk) ^ (st_row & 7)) * 16), pk[0], pk[1], pk[2], pk[3]);
    }
  }
  fence_async_smem();
  named_arrive(6 + (warp >> 2), 160);
}

constexpr int K2_NS = 4;
constexpr int K2_STAGE = 16384 + 32768;
constexpr int K2_PITCH = 464;

__device__ __forceinline__ void spin_flag(const unsigned int* flag, unsigned int target) {
  int it = 0;
  while (true) {
    unsigned int v;
    asm volatile("ld.acquire.gpu.global.u32 %0, [%1];" : "=r"(v) : "l"(flag) : "memory");
    if ((int)(v - target) >= 0) break;
    if (++it > SPIN_LIMIT) { TIMEOUT(20); break; }
  }
}

__device__ __forceinline__ void ln_rows(const __nv_bfloat16* __restrict__ xt, uint32_t sb, int lw, int lane) {
  const int c = lane & 7;
  const int r0 = lw * 4 + (lane >> 3);
  const uint4* src = reinterpret_cast<const uint4*>(xt + (size_t)r0 * 448) + c;
  uint4 nx[7];
#pragma unroll
  for (int b = 0; b < 7; b++)
    asm volatile("ld.global.nc.v4.u32 {%0,%1,%2,%3}, [%4];" : "=r"(nx[b].x), "=r"(nx[b].y), "=r"(nx[b].z), "=r"(nx[b].w) : "l"(src + b * 8) : "memory");
  const int npass = (lw < 10) ? 3 : 2;
  if (c < 7) {
    asm volatile("prefetch.global.L2 [%0];" ::"l"(src + 44 * 56 + c * 7) : "memory");
    if (npass == 3) asm volatile("prefetch.global.L2 [%0];" ::"l"(src + 88 * 56 + c * 7) : "memory");
  }
#pragma unroll 1
  for (int pass = 0; pass < npass; pass++) {
    uint4 v[7];
#pragma unroll
    for (int b = 0; b < 7; b++) v[b] = nx[b];
    if (pass + 1 < npass) {
      const uint4* s2 = src + (pass + 1) * 44 * 56;
#pragma unroll
      for (int b = 0; b < 7; b++)
        asm volatile("ld.global.nc.v4.u32 {%0,%1,%2,%3}, [%4];" : "=r"(nx[b].x), "=r"(nx[b].y), "=r"(nx[b].z), "=r"(nx[b].w) : "l"(s2 + b * 8) : "memory");
    }
        float s0 = 0.f, s1 = 0.f, s2v = 0.f, s3 = 0.f;
#pragma unroll
        for (int b = 0; b < 7; b++) {
          s0 += bf_lo(v[b].x) + bf_hi(v[b].x); s1 += bf_lo(v[b].y) + bf_hi(v[b].y);
          s2v += bf_lo(v[b].z) + bf_hi(v[b].z); s3 += bf_lo(v[b].w) + bf_hi(v[b].w);
        }
        float m = (s0 + s1) + (s2v + s3);
        m += __shfl_xor_sync(0xffffffffu, m, 1);
        m += __shfl_xor_sync(0xffffffffu, m, 2);
        m += __shfl_xor_sync(0xffffffffu, m, 4);
        m *= (1.0f / 448.0f);
        float q0 = 0.f, q1 = 0.f, q2 = 0.f, q3 = 0.f;
#pragma unroll
        for (int b = 0; b < 7; b++) {
          float d;
          d = bf_lo(v[b].x) - m; q0 = fmaf(d, d, q0); d = bf_hi(v[b].x) - m; q1 = fmaf(d, d, q1);
          d = bf_lo(v[b].y) - m; q2 = fmaf(d, d, q2); d = bf_hi(v[b].y) - m; q3 = fmaf(d, d, q3);
          d = bf_lo(v[b].z) - m; q0 = fmaf(d, d, q0); d = bf_hi(v[b].z) - m; q1 = fmaf(d, d, q1);
          d = bf_lo(v[b].w) - m; q2 = fmaf(d, d, q2); d = bf_hi(v[b].w) - m; q3 = fmaf(d, d, q3);
        }
        float q = (q0 + q1) + (q2 + q3);
        q += __shfl_xor_sync(0xffffffffu, q, 1);
        q += __shfl_xor_sync(0xffffffffu, q, 2);
        q += __shfl_xor_sync(0xffffffffu, q, 4);
        const float var_b = rbf(q * (1.0f / 448.0f));
        const float den = rbf(sqrtf(rbf(var_b + 1e-5f)));
        const float ri = 1.0f / den;
        const float rih = rbf(ri);
        const uint32_t rhi2 = pack_bf16(rih, rih), rlo2 = pack_bf16(ri - rih, ri - rih);
        const uint32_t m2 = pack_bf16(m, m);
        const int r = r0 + pass * 44;
        const uint32_t a0 = sb + r * 128 + ((c ^ (r & 7)) * 16);
#pragma unroll
        for (int b = 0; b < 7; b++) {
          uint32_t w4[4] = {v[b].x, v[b].y, v[b].z, v[b].w};
#pragma unroll
          for (int qq = 0; qq < 4; qq++) {
            const uint32_t dw = hsub2_bf16(w4[qq], m2);
            w4[qq] = hfma2_bf16(dw, rhi2, hmul2_bf16(dw, rlo2));
          }
          sts128(a0 + b * 16384, make_uint4(w4[0], w4[1], w4[2], w4[3]));
        }
  }
}

struct PfPtrs { const uint8_t* wg; const uint8_t* wu; const uint8_t* wd; };

__global__ void __cluster_dims__(2, 1, 1) __launch_bounds__(384, 1)
fused_kernel(const __grid_constant__ CUtensorMap tm_wr, const __grid_constant__ CUtensorMap tm_wi,
             const __grid_constant__ CUtensorMap tm_wg, const __grid_constant__ CUtensorMap tm_wu,
             const __grid_constant__ CUtensorMap tm_hs, const __grid_constant__ CUtensorMap tm_abs,
             const __grid_constant__ CUtensorMap tm_cr, const __grid_constant__ CUtensorMap tm_ci, const __grid_constant__ CUtensorMap tm_h,
             const __grid_constant__ CUtensorMap tm_ab, const __grid_constant__ CUtensorMap tm_wd,
             const __nv_bfloat16* __restrict__ x, __nv_bfloat16* __restrict__ out, const PfPtrs pf) {
  extern __shared__ uint8_t smem_raw[];
  const uint32_t sb = (s2u(smem_raw) + 1023) & ~1023u;
  const int tid = threadIdx.x, warp = tid >> 5, lane = tid & 31;
  uint32_t rank;
  asm volatile("mov.u32 %0, %%cluster_ctarank;" : "=r"(rank));
  const int cid = blockIdx.x >> 1;
  const int p = cid >> 3, j = cid & 7;
  const int mt = 2 * p + (int)rank;
  const uint32_t bar_full = sb + K1_BAR_OFF;
  const uint32_t bar_empty = bar_full + 8 * K1_NS;
  const uint32_t bar_full2 = bar_empty + 8 * K1_NS;
  const uint32_t bar_empty2 = bar_full2 + 8 * K2_NS;
  const int fb_base = 7 * (j >> 1);
  const int fb0 = fb_base + ((j & 1) ? 4 : 0);
  const int fbh = fb_base + 3;
  const int q = j & 3, n = j >> 2;
  const int tile = mt * 2 + n;
  const int nkb = (q < 2) ? 22 : (q == 3 ? 28 : 20);
  const int nunits = (q == 3) ? 4 : 5;
  const int u4full = (q == 2);

  if (tid == 0) DBG(0, 0);
  if (tid == 256) {
    for (int i = 0; i < K1_NS; i++) { mbar_init(bar_full + 8 * i, 1); mbar_init(bar_empty + 8 * i, 8); }
    for (int i = 0; i < K2_NS; i++) { mbar_init(bar_full2 + 8 * i, 1); mbar_init(bar_empty2 + 8 * i, 16); }
    mbar_init(bar_empty2 + 8 * K2_NS, 1);
    mbar_init(bar_empty2 + 8 * K2_NS + 8, 1);
    mbar_init(bar_empty2 + 8 * K2_NS + 16, 1);
    asm volatile("fence.mbarrier_init.release.cluster;" ::: "memory");
    prefetch_tmap((j < 4) ? &tm_wr : &tm_wi);
    prefetch_tmap(rank ? &tm_wu : &tm_wg);
    prefetch_tmap(&tm_abs);
    prefetch_tmap(&tm_hs);
  }
  __syncwarp();
  cluster_arrive_relaxed();

  if (warp != 8) {
    ln_rows(x + (size_t)mt * 128 * 448, sb, warp < 8 ? warp : warp - 1, lane);
    asm volatile("fence.proxy.async.shared::cta;" ::: "memory");
  }
  if (warp >= 8) {
    if (warp > 8) named_arrive(8, 352);
    reg_dec<40>();
    cluster_wait();
    if (tid == 256) {
      const unsigned int epoch = *reinterpret_cast<volatile unsigned int*>(&g_epoch);
      {
        const CUtensorMap* tw = (j < 4) ? &tm_wr : &tm_wi;
        const CUtensorMap* tgu = rank ? &tm_wu : &tm_wg;
        int slot = 0; uint32_t ph = 0;
        int kb = 0, unit = 0;
#pragma unroll 1
        for (int s = 0; s < 7 * nunits; s++) {
          if (s >= K1_NS) mbar_wait(bar_empty + 8 * slot, ph ^ 1, 2);
          const uint32_t dst = sb + K1_B_OFF + slot * 16384;
          if (unit == 0) {
            mbar_expect(bar_full + 8 * slot, 14336);
            tma2d_mc(dst + rank * 7168, tw, kb * 64, (j & 3) * 112 + rank * 56, bar_full + 8 * slot, 3);
          } else {
            const int fb = (unit == 4) ? fbh : (fb0 + unit - 1);
            mbar_expect(bar_full + 8 * slot, 16384);
            tma2d_mc(dst + rank * 8192, tgu, fb * 64, kb * 64, bar_full + 8 * slot, 3);
          }
          if (s == 21) {
            l2_prefetch(pf.wd + blockIdx.x * 12544, 12544);
            if (q < 3) {
              const int g0 = q * 22;
#pragma unroll 1
              for (int i = 0; i < 6; i++) tma2d_prefetch((g0 + i < 32) ? &tm_cr : &tm_ci, ((g0 + i) & 31) * 64, mt * 128);
            }
          }
          if (++kb == 7) { kb = 0; unit++; }
          if (++slot == K1_NS) { slot = 0; ph ^= 1; }
        }
      }
      {
        const int g0 = (q == 0) ? 0 : (q == 1 ? 22 : (q == 2 ? 44 : 64));
        const CUtensorMap* tb = (q < 3) ? &tm_ab : &tm_wd;
        prefetch_tmap(tb); prefetch_tmap((q < 3) ? ((g0 < 32) ? &tm_cr : &tm_ci) : &tm_h);
        const int kb0 = (q < 3) ? g0 : 0;
        if (q < 3) { spin_flag(&g_ab_cnt, 128u * (epoch + 1)); asm volatile("fence.proxy.async;" ::: "memory"); }
        DBG(1, 31);
        int slot = 0; uint32_t ph = 0;
#pragma unroll 1
        for (int s = 0; s < nkb; s++) {
          int kblk = kb0 + s;
          const CUtensorMap* ta = (kblk < 32) ? &tm_cr : &tm_ci;
          if (q == 3) {
            if ((s & 7) == 0) { spin_flag(&g_h_cnt[mt * 4 + (s >> 3)], ((s < 24) ? 8u : 6u) * (epoch + 1)); asm volatile("fence.proxy.async;" ::: "memory"); }
            const int i = s & 7;
            kblk = (s < 24) ? (7 * (i >> 1) + ((i & 1) ? 4 : 0) + (s >> 3)) : (7 * i + 3);
            ta = &tm_h;
          }
          mbar_wait(bar_empty2 + 8 * slot, ph, 10);
          const uint32_t dst = sb + slot * K2_STAGE;
          const uint32_t fb = bar_full2 + 8 * slot;
          mbar_expect(fb, K2_STAGE);
          tma2d(dst, ta, (kblk & 31) * 64, mt * 128, fb);
          tma3d_mc(dst + 16384 + (2 * rank) * 8192, tb, (2 * rank) * 64, n, kblk * 64, fb, 3);
          tma3d_mc(dst + 16384 + (2 * rank + 1) * 8192, tb, (2 * rank + 1) * 64, n, kblk * 64, fb, 3);
          if (++slot == K2_NS) { slot = 0; ph ^= 1; }
        }
        if (q == 3) {
          const uint32_t bar_p = bar_empty2 + 8 * K2_NS;
          spin_flag(&g_flags[tile], 24u * (epoch + 1));
          asm volatile("fence.proxy.async;" ::: "memory");
          mbar_expect(bar_p, 3 * 57344);
          const uint4* pp = g_part + (size_t)tile * (3 * 14 * 256);
#pragma unroll 1
          for (int c = 0; c < 7; c++) {
            if ((c & 1) == 0) mbar_wait(bar_empty2 + 8 * (c >> 1), ph, 13);
            bulk_load(sb + c * 24576, pp + c * 1536, 24576, bar_p);
          }
          DBG(1, 30);
        }
      }
    } else if (warp == 9 || warp == 10) {
      const int hw = warp - 9;
      const uint32_t stg = sb + K1_STG_OFF + hw * 16384;
      const uint32_t bar_sfree = bar_empty2 + 8 * K2_NS + 8 + 8 * hw;
      if (lane == 0) {
        const int b = blockIdx.x;
        l2_prefetch((hw ? pf.wu : pf.wg) + b * 12544, 12544);
      }
#pragma unroll 1
      for (int job = 0; job < (hw ? 2 : (nunits == 5 ? 4 : 3)); job++) {
        named_bar(6 + hw, 160);
        if (lane == 0) {
          const int unit = hw ? (1 + 2 * job) : (job < 2 ? 0 : 2 * job - 2);
          if (unit == 0) {
            tma2d_store(&tm_abs, stg, (j & 3) * 112, (j < 4 ? 0 : 2048) + mt * 128 + job * 64);
          } else {
            const int fb = (unit == 4) ? fbh : fb0 + unit - 1;
            const bool fullu = (unit < 4) || u4full;
            tma2d_store(&tm_hs, stg, fb * 64, mt * 128 + (fullu ? 0 : (j & 1) * 64));
            if (fullu) tma2d_store(&tm_hs, stg + 8192, fb * 64, mt * 128 + 64);
          }
          bulk_commit();
          bulk_wait_read0();
          asm volatile("mbarrier.arrive.shared::cta.b64 _, [%0];" ::"r"(bar_sfree) : "memory");
          if (unit != 0 || job == 1) {
            bulk_wait0();
            asm volatile("fence.proxy.async;" ::: "memory");
            __threadfence();
            if (unit == 0) {
              const unsigned int old = atomicAdd(&g_ab_cnt, 1u);
              if ((old & 127u) == 127u) *reinterpret_cast<volatile unsigned int*>(&g_epoch) = (old >> 7) + 1;
            } else {
              atomicAdd(&g_h_cnt[mt * 4 + unit - 1], 1u);
            }
          }
        }
        __syncwarp();
      }
    }
  } else {
    const int wg = warp >> 2;
    named_bar(8, 352);
    reg_inc<232>();
    cluster_wait();
    if (tid == 0) DBG(0, 3);

    uint32_t rel0, rel1;
    asm volatile("mapa.shared::cluster.u32 %0, %1, %2;" : "=r"(rel0) : "r"(bar_empty2), "r"(0));
    asm volatile("mapa.shared::cluster.u32 %0, %1, %2;" : "=r"(rel1) : "r"(bar_empty2), "r"(1));
    {
      K1Ctx c;
      c.sb = sb; c.bar_full = bar_full; c.lane0 = (lane == 0);
      c.rel0 = rel0 - 8 * (K1_NS + K2_NS); c.rel1 = rel1 - 8 * (K1_NS + K2_NS);
      c.bar_sfree = bar_empty2 + 8 * K2_NS + 8 + 8 * wg; c.sphase = 0;
      c.dA = make_desc(sb, 16, 1024);
      c.dBk = make_desc(sb + K1_B_OFF, 16, 1024);
      c.dBn = make_desc(sb + K1_B_OFF, 8192, 1024);
      if (wg == 0) {
        k1_unit_ab(c, warp, lane, mt, j);
        if (tid == 0) DBG(0, 6);
      }
#pragma unroll 1
      for (int unit = 2 - wg; unit < nunits; unit += 2) {
        k1_unit_gu(c, warp, lane, mt, unit, (unit == 4) ? fbh : fb0 + unit - 1, j & 1, (unit < 4) || u4full, nunits);
        if ((tid & 127) == 0) DBG(0, 6 + 3 * unit);
      }
    }

    float acc[112];
    const uint32_t dA0 = make_desc(sb + wg * 8192, 16, 1024);
    const uint32_t dB0 = make_desc(sb + 16384, 8192, 1024);
    int slot = 0; uint32_t ph = 0;
#pragma unroll 1
    for (int s = 0; s < nkb; s++) {
      mbar_wait(bar_full2 + 8 * slot, ph, 11);
      if (tid == 0) DBG(1, 1 + s);
      wg_fence();
      const uint32_t da = dA0 + slot * (K2_STAGE / 16);
      const uint32_t db = dB0 + slot * (K2_STAGE / 16);
#pragma unroll
      for (int k = 0; k < 4; k++) wgmma_n224_tb(acc, da + k * 2, db + k * 128, (s | k) != 0);
      wg_commit();
      if (s > 0) {
        wg_wait<1>();
        const int ps = (slot == 0) ? K2_NS - 1 : slot - 1;
        if (lane == 0) {
          asm volatile("mbarrier.arrive.shared::cluster.b64 _, [%0];" ::"r"(rel0 + 8 * ps) : "memory");
          asm volatile("mbarrier.arrive.shared::cluster.b64 _, [%0];" ::"r"(rel1 + 8 * ps) : "memory");
        }
      }
      if (++slot == K2_NS) { slot = 0; ph ^= 1; }
    }
    wg_wait<0>();
    if (tid == 0) DBG(1, 29);
    if (q < 3) {
      uint4* part = g_part + (size_t)(tile * 3 + q) * (14 * 256) + tid;
#pragma unroll
      for (int g = 0; g < 14; g++)
        part[g * 256] = make_uint4(pack_bf16(acc[8 * g], acc[8 * g + 1]), pack_bf16(acc[8 * g + 2], acc[8 * g + 3]),
                                   pack_bf16(acc[8 * g + 4], acc[8 * g + 5]), pack_bf16(acc[8 * g + 6], acc[8 * g + 7]));
      __syncwarp();
      if (lane == 0) { __threadfence(); atomicAdd(&g_flags[tile], 1u); }
    } else {
      if (lane == 0) {
        asm volatile("mbarrier.arrive.shared::cluster.b64 _, [%0];" ::"r"(rel0 + 8 * (K2_NS - 1)) : "memory");
        asm volatile("mbarrier.arrive.shared::cluster.b64 _, [%0];" ::"r"(rel1 + 8 * (K2_NS - 1)) : "memory");
      }
      const uint32_t bar_p = bar_empty2 + 8 * K2_NS;
      const int lc = (lane < 28) ? lane : 27;
      const size_t gbase = (size_t)(mt * 128 + warp * 16) * 448 + n * 224 + lc * 8;
      uint4 xv[16];
#pragma unroll
      for (int t = 0; t < 16; t++) xv[t] = ldg128_cg(x + gbase + t * 448);
      uint32_t gw[56];
#pragma unroll
      for (int i = 0; i < 56; i++) {
        const uint32_t f2 = pack_bf16(acc[2 * i], acc[2 * i + 1]);
        gw[i] = pack_bf16(silu_f(bf_lo(f2)), silu_f(bf_hi(f2)));
      }
      if (tid == 0) DBG(1, 62);
      mbar_wait(bar_p, 0, 12);
      const uint32_t tb = sb + tid * 16;
#pragma unroll
      for (int g = 0; g < 14; g++) {
        const uint4 a = lds128(tb + g * 4096), b = lds128(tb + (14 + g) * 4096), cc = lds128(tb + (28 + g) * 4096);
        gw[4 * g] = hmul2_bf16(pack_bf16(bf_lo(a.x) + bf_lo(b.x) + bf_lo(cc.x), bf_hi(a.x) + bf_hi(b.x) + bf_hi(cc.x)), gw[4 * g]);
        gw[4 * g + 1] = hmul2_bf16(pack_bf16(bf_lo(a.y) + bf_lo(b.y) + bf_lo(cc.y), bf_hi(a.y) + bf_hi(b.y) + bf_hi(cc.y)), gw[4 * g + 1]);
        gw[4 * g + 2] = hmul2_bf16(pack_bf16(bf_lo(a.z) + bf_lo(b.z) + bf_lo(cc.z), bf_hi(a.z) + bf_hi(b.z) + bf_hi(cc.z)), gw[4 * g + 2]);
        gw[4 * g + 3] = hmul2_bf16(pack_bf16(bf_lo(a.w) + bf_lo(b.w) + bf_lo(cc.w), bf_hi(a.w) + bf_hi(b.w) + bf_hi(cc.w)), gw[4 * g + 3]);
      }
      named_bar(1, 256);
      const uint32_t wbase = sb + warp * 16 * K2_PITCH;
      const int st_row = (lane & 7) + 8 * ((lane >> 3) & 1);
      const uint32_t sa = wbase + st_row * K2_PITCH + (lane >> 4) * 16;
#pragma unroll
      for (int g = 0; g < 28; g += 2) stmatrix_x4(sa + g * 16, gw[2 * g], gw[2 * g + 1], gw[2 * g + 2], gw[2 * g + 3]);
      __syncwarp();
      const uint32_t lp = wbase + lc * 16;
#pragma unroll
      for (int t = 0; t < 16; t++) {
        const uint4 tv = lds128(lp + t * K2_PITCH);
        uint4 o;
        o.x = hadd2_bf16(xv[t].x, tv.x); o.y = hadd2_bf16(xv[t].y, tv.y); o.z = hadd2_bf16(xv[t].z, tv.z); o.w = hadd2_bf16(xv[t].w, tv.w);
        if (lane < 28) stg128(out + gbase + t * 448, o);
      }
    }
    if (tid == 0) DBG(1, 63);
  }
  __syncwarp();
  cluster_arrive_relaxed();
  cluster_wait();
}

typedef CUresult (*EncFn)(CUtensorMap*, CUtensorMapDataType, cuuint32_t, void*, const cuuint64_t*, const cuuint64_t*, const cuuint32_t*,
                          const cuuint32_t*, CUtensorMapInterleave, CUtensorMapSwizzle, CUtensorMapL2promotion, CUtensorMapFloatOOBfill);

void make2d(EncFn enc, CUtensorMap* tm, const void* ptr, uint64_t cols, uint64_t rows, uint32_t bc, uint32_t br, bool swz = true) {
  cuuint64_t gd[2] = {cols, rows};
  cuuint64_t gs[1] = {cols * 2};
  cuuint32_t bd[2] = {bc, br};
  cuuint32_t es[2] = {1, 1};
  enc(tm, CU_TENSOR_MAP_DATA_TYPE_BFLOAT16, 2, const_cast<void*>(ptr), gd, gs, bd, es, CU_TENSOR_MAP_INTERLEAVE_NONE,
      swz ? CU_TENSOR_MAP_SWIZZLE_128B : CU_TENSOR_MAP_SWIZZLE_NONE, CU_TENSOR_MAP_L2_PROMOTION_L2_128B, CU_TENSOR_MAP_FLOAT_OOB_FILL_NONE);
}
void make3d_half(EncFn enc, CUtensorMap* tm, const void* ptr, uint64_t rows) {
  cuuint64_t gd[3] = {224, 2, rows};
  cuuint64_t gs[2] = {448, 896};
  cuuint32_t bd[3] = {64, 1, 64};
  cuuint32_t es[3] = {1, 1, 1};
  enc(tm, CU_TENSOR_MAP_DATA_TYPE_BFLOAT16, 3, const_cast<void*>(ptr), gd, gs, bd, es, CU_TENSOR_MAP_INTERLEAVE_NONE,
      CU_TENSOR_MAP_SWIZZLE_128B, CU_TENSOR_MAP_L2_PROMOTION_L2_128B, CU_TENSOR_MAP_FLOAT_OOB_FILL_NONE);
}

struct Maps { CUtensorMap wr, wi, wg, wu, cr, ci, h, ab, wd, hs, abs; };

}

extern "C" void kernel_launch(void* const* d_in, const int* in_sizes, int n_in, void* d_out, int out_size) {
  (void)in_sizes; (void)n_in; (void)out_size;
  static Maps maps;
  static const void* cached[9] = {nullptr};
  static bool attr_done = false;
  bool same = true;
  for (int i = 0; i < 9; i++) same = same && (cached[i] == d_in[i]);
  if (!same) {
    void* fn = nullptr;
    cudaDriverEntryPointQueryResult qr;
    cudaGetDriverEntryPoint("cuTensorMapEncodeTiled", &fn, cudaEnableDefault, &qr);
    EncFn enc = (EncFn)fn;
    void *p_ab = nullptr, *p_h = nullptr;
    cudaGetSymbolAddress(&p_ab, g_ab);
    cudaGetSymbolAddress(&p_h, g_h);
    make2d(enc, &maps.cr, d_in[1], 2048, 2048, 64, 128);
    make2d(enc, &maps.ci, d_in[2], 2048, 2048, 64, 128);
    make2d(enc, &maps.wr, d_in[3], 448, 448, 64, 56);
    make2d(enc, &maps.wi, d_in[4], 448, 448, 64, 56);
    make2d(enc, &maps.wg, d_in[6], 1792, 448, 64, 64);
    make2d(enc, &maps.wu, d_in[7], 1792, 448, 64, 64);
    make3d_half(enc, &maps.wd, d_in[8], 1792);
    make2d(enc, &maps.h, p_h, 1792, 2048, 64, 128);
    make3d_half(enc, &maps.ab, p_ab, 4096);
    make2d(enc, &maps.hs, p_h, 1792, 2048, 64, 64);
    make2d(enc, &maps.abs, p_ab, 448, 4096, 112, 64, false);
    for (int i = 0; i < 9; i++) cached[i] = d_in[i];
  }
  if (!attr_done) {
    cudaFuncSetAttribute(fused_kernel, cudaFuncAttributeMaxDynamicSharedMemorySize, K1_SMEM);
    attr_done = true;
  }
  PfPtrs pf;
  pf.wg = (const uint8_t*)d_in[6]; pf.wu = (const uint8_t*)d_in[7]; pf.wd = (const uint8_t*)d_in[8];
  fused_kernel<<<128, 384, K1_SMEM>>>(maps.wr, maps.wi, maps.wg, maps.wu, maps.hs, maps.abs, maps.cr, maps.ci, maps.h, maps.ab, maps.wd,
                                      (const __nv_bfloat16*)d_in[0], (__nv_bfloat16*)d_out, pf);
}
```

```cpp
#include <cuda_runtime.h>
#include <cuda_bf16.h>
#include <cuda.h>
#include <stdint.h>

namespace {

__device__ __align__(1024) __nv_bfloat16 g_ab[4096 * 448];
__device__ __align__(1024) __nv_bfloat16 g_h[2048 * 1792];
__device__ uint4 g_part[32 * 4 * 14 * 256];
__device__ __align__(1024) __nv_bfloat16 g_s[2048 * 448];
__device__ unsigned int g_epoch;
__device__ unsigned int g_ab_cnt;
__device__ unsigned int g_h_cnt[16 * 4];
__device__ unsigned int g_flags[32 * 8];

#define DBG(k, i) do {} while (0)
#define DBGC(k, i) do {} while (0)

#define TIMEOUT(code) __trap()
#define SPIN_LIMIT (1 << 22)
__device__ __forceinline__ uint32_t s2u(const void* p) { return (uint32_t)__cvta_generic_to_shared(p); }
__device__ __forceinline__ void mbar_init(uint32_t b, int c) { asm volatile("mbarrier.init.shared::cta.b64 [%0], %1;" ::"r"(b), "r"(c)); }
__device__ __forceinline__ void mbar_expect(uint32_t b, uint32_t bytes) {
  asm volatile("mbarrier.arrive.expect_tx.shared::cta.b64 _, [%0], %1;" ::"r"(b), "r"(bytes) : "memory");
}
__device__ __forceinline__ void mbar_wait(uint32_t b, uint32_t ph, int code = 1) {
  uint32_t done = 0;
  int it = 0;
  while (true) {
    asm volatile("{.reg .pred p; mbarrier.try_wait.parity.shared::cta.b64 p, [%1], %2; selp.u32 %0,1,0,p;}" : "=r"(done) : "r"(b), "r"(ph) : "memory");
    if (done) break;
    if (++it > SPIN_LIMIT) { TIMEOUT(code); break; }
  }
}
__device__ __forceinline__ void mbar_arrive_cluster(uint32_t b, uint32_t cta) {
  uint32_t r;
  asm volatile("mapa.shared::cluster.u32 %0, %1, %2;" : "=r"(r) : "r"(b), "r"(cta));
  asm volatile("mbarrier.arrive.shared::cluster.b64 _, [%0];" ::"r"(r) : "memory");
}
__device__ __forceinline__ void tma2d(uint32_t dst, const CUtensorMap* m, int c0, int c1, uint32_t bar) {
  asm volatile("cp.async.bulk.tensor.2d.shared::cluster.global.mbarrier::complete_tx::bytes [%0], [%1, {%3,%4}], [%2];" ::"r"(dst), "l"(m), "r"(bar), "r"(c0), "r"(c1) : "memory");
}
__device__ __forceinline__ void tma2d_mc(uint32_t dst, const CUtensorMap* m, int c0, int c1, uint32_t bar, uint16_t mask) {
  asm volatile("cp.async.bulk.tensor.2d.shared::cluster.global.mbarrier::complete_tx::bytes.multicast::cluster [%0], [%1, {%3,%4}], [%2], %5;" ::"r"(dst), "l"(m), "r"(bar), "r"(c0), "r"(c1), "h"(mask) : "memory");
}
__device__ __forceinline__ void tma3d_mc(uint32_t dst, const CUtensorMap* m, int c0, int c1, int c2, uint32_t bar, uint16_t mask) {
  asm volatile("cp.async.bulk.tensor.3d.shared::cluster.global.mbarrier::complete_tx::bytes.multicast::cluster [%0], [%1, {%3,%4,%5}], [%2], %6;" ::"r"(dst), "l"(m), "r"(bar), "r"(c0), "r"(c1), "r"(c2), "h"(mask) : "memory");
}
__device__ __forceinline__ void tma2d_store(const CUtensorMap* m, uint32_t src, int c0, int c1) {
  asm volatile("cp.async.bulk.tensor.2d.global.shared::cta.bulk_group [%0, {%2,%3}], [%1];" ::"l"(m), "r"(src), "r"(c0), "r"(c1) : "memory");
}
__device__ __forceinline__ void bulk_load(uint32_t dst, const void* src, uint32_t bytes, uint32_t bar) {
  asm volatile("cp.async.bulk.shared::cluster.global.mbarrier::complete_tx::bytes [%0], [%1], %2, [%3];" ::"r"(dst), "l"(src), "r"(bytes), "r"(bar) : "memory");
}
__device__ __forceinline__ void tma2d_prefetch(const CUtensorMap* m, int c0, int c1) {
  asm volatile("cp.async.bulk.prefetch.tensor.2d.L2.global [%0, {%1,%2}];" ::"l"(m), "r"(c0), "r"(c1) : "memory");
}
__device__ __forceinline__ void bulk_commit() { asm volatile("cp.async.bulk.commit_group;" ::: "memory"); }
__device__ __forceinline__ void bulk_wait_read0() { asm volatile("cp.async.bulk.wait_group.read 0;" ::: "memory"); }
__device__ __forceinline__ void bulk_wait0() { asm volatile("cp.async.bulk.wait_group 0;" ::: "memory"); }
__device__ __forceinline__ void fence_async_smem() { asm volatile("fence.proxy.async.shared::cta;" ::: "memory"); }
__device__ __forceinline__ void prefetch_tmap(const CUtensorMap* m) { asm volatile("prefetch.tensormap [%0];" ::"l"(m) : "memory"); }
__device__ __forceinline__ void l2_prefetch(const void* p, uint32_t bytes) {
  asm volatile("cp.async.bulk.prefetch.L2.global [%0], %1;" ::"l"(p), "r"(bytes) : "memory");
}
__device__ __forceinline__ void cluster_arrive_relaxed() { asm volatile("barrier.cluster.arrive.relaxed.aligned;" ::: "memory"); }
__device__ __forceinline__ void cluster_wait() { asm volatile("barrier.cluster.wait.aligned;" ::: "memory"); }
__device__ __forceinline__ void wg_fence() { __syncwarp(); asm volatile("wgmma.fence.sync.aligned;" ::: "memory"); }
__device__ __forceinline__ void wg_commit() { asm volatile("wgmma.commit_group.sync.aligned;" ::: "memory"); }
template <int N> __device__ __forceinline__ void wg_wait() { __syncwarp(); asm volatile("wgmma.wait_group.sync.aligned %0;" ::"n"(N) : "memory"); }
__device__ __forceinline__ void named_bar(int id, int n) { asm volatile("bar.sync %0, %1;" ::"r"(id), "r"(n) : "memory"); }
__device__ __forceinline__ void named_arrive(int id, int n) { asm volatile("bar.arrive %0, %1;" ::"r"(id), "r"(n) : "memory"); }
template <int N> __device__ __forceinline__ void reg_inc() { asm volatile("setmaxnreg.inc.sync.aligned.u32 %0;" ::"n"(N)); }
template <int N> __device__ __forceinline__ void reg_dec() { asm volatile("setmaxnreg.dec.sync.aligned.u32 %0;" ::"n"(N)); }
__device__ __forceinline__ void pdl_wait() { asm volatile("griddepcontrol.wait;" ::: "memory"); }
__device__ __forceinline__ void pdl_launch() { asm volatile("griddepcontrol.launch_dependents;" ::: "memory"); }

__device__ __forceinline__ uint32_t make_desc(uint32_t addr, uint32_t lbo, uint32_t  ) {
  return ((addr & 0x3FFFF) >> 4) | ((lbo >> 4) << 16);
}
__device__ __forceinline__ void stmatrix_x4(uint32_t addr, uint32_t r0, uint32_t r1, uint32_t r2, uint32_t r3) {
  asm volatile("stmatrix.sync.aligned.m8n8.x4.shared.b16 [%0], {%1,%2,%3,%4};" ::"r"(addr), "r"(r0), "r"(r1), "r"(r2), "r"(r3) : "memory");
}
__device__ __forceinline__ uint4 lds128(uint32_t a) {
  uint4 v;
  asm volatile("ld.shared.v4.u32 {%0,%1,%2,%3}, [%4];" : "=r"(v.x), "=r"(v.y), "=r"(v.z), "=r"(v.w) : "r"(a) : "memory");
  return v;
}
__device__ __forceinline__ void sts128(uint32_t a, uint4 v) {
  asm volatile("st.shared.v4.u32 [%0], {%1,%2,%3,%4};" ::"r"(a), "r"(v.x), "r"(v.y), "r"(v.z), "r"(v.w) : "memory");
}
__device__ __forceinline__ void stg128(void* p, uint4 v) {
  asm volatile("st.global.v4.u32 [%0], {%1,%2,%3,%4};" ::"l"(p), "r"(v.x), "r"(v.y), "r"(v.z), "r"(v.w) : "memory");
}
__device__ __forceinline__ void cp_async16(uint32_t dst, const void* src) {
  asm volatile("cp.async.cg.shared.global [%0], [%1], 16;" ::"r"(dst), "l"(src) : "memory");
}
__device__ __forceinline__ void cp_async8(uint32_t dst, const void* src) {
  asm volatile("cp.async.ca.shared.global [%0], [%1], 8;" ::"r"(dst), "l"(src) : "memory");
}
__device__ __forceinline__ uint2 lds64(uint32_t a) {
  uint2 v;
  asm volatile("ld.shared.v2.u32 {%0,%1}, [%2];" : "=r"(v.x), "=r"(v.y) : "r"(a) : "memory");
  return v;
}
__device__ __forceinline__ void cp_async_wait_all() { asm volatile("cp.async.wait_all;" ::: "memory"); }
__device__ __forceinline__ uint32_t pack_bf16(float lo, float hi) {
  uint32_t r;
  asm("cvt.rn.bf16x2.f32 %0, %1, %2;" : "=r"(r) : "f"(hi), "f"(lo));
  return r;
}
__device__ __forceinline__ uint32_t hmul2_bf16(uint32_t a, uint32_t b) {
  uint32_t r;
  asm("mul.rn.bf16x2 %0, %1, %2;" : "=r"(r) : "r"(a), "r"(b));
  return r;
}
__device__ __forceinline__ uint32_t hsub2_bf16(uint32_t a, uint32_t b) {
  uint32_t r;
  asm("sub.rn.bf16x2 %0, %1, %2;" : "=r"(r) : "r"(a), "r"(b));
  return r;
}
__device__ __forceinline__ uint32_t hadd2_bf16(uint32_t a, uint32_t b) {
  uint32_t r;
  asm("add.rn.bf16x2 %0, %1, %2;" : "=r"(r) : "r"(a), "r"(b));
  return r;
}
__device__ __forceinline__ uint32_t hfma2_bf16(uint32_t a, uint32_t b, uint32_t c) {
  uint32_t r;
  asm("fma.rn.bf16x2 %0, %1, %2, %3;" : "=r"(r) : "r"(a), "r"(b), "r"(c));
  return r;
}
__device__ __forceinline__ bool mbar_test(uint32_t b, uint32_t ph) {
  uint32_t done;
  asm volatile("{.reg .pred p; mbarrier.test_wait.parity.shared::cta.b64 p, [%1], %2; selp.u32 %0,1,0,p;}" : "=r"(done) : "r"(b), "r"(ph) : "memory");
  return __all_sync(0xffffffffu, done != 0);
}
__device__ __forceinline__ uint4 ldg128_cg(const void* p) {
  uint4 v;
  asm volatile("ld.global.cg.v4.u32 {%0,%1,%2,%3}, [%4];" : "=r"(v.x), "=r"(v.y), "=r"(v.z), "=r"(v.w) : "l"(p) : "memory");
  return v;
}
__device__ __forceinline__ float bf_lo(uint32_t w) { return __uint_as_float(w << 16); }
__device__ __forceinline__ float bf_hi(uint32_t w) { return __uint_as_float(w & 0xffff0000u); }
__device__ __forceinline__ float rbf(float x) { return __bfloat162float(__float2bfloat16_rn(x)); }
__device__ __forceinline__ float ex2f(float x) { float r; asm("ex2.approx.ftz.f32 %0, %1;" : "=f"(r) : "f"(x)); return r; }
__device__ __forceinline__ float rcpf(float x) { float r; asm("rcp.approx.ftz.f32 %0, %1;" : "=f"(r) : "f"(x)); return r; }
__device__ __forceinline__ float tanhf_hw(float x) { float r; asm("tanh.approx.f32 %0, %1;" : "=f"(r) : "f"(x)); return r; }
__device__ __forceinline__ float gelu_tanh(float x) {
  const float c1 = 0.7978845608028654f;
  const float c2 = c1 * 0.044715f;
  const float t = tanhf_hw(x * fmaf(c2, x * x, c1));
  const float hx = 0.5f * x;
  return fmaf(hx, t, hx);
}
__device__ __forceinline__ float silu_f(float x) {
  const float hx = 0.5f * x;
  return fmaf(hx, tanhf_hw(hx), hx);
}

__device__ __forceinline__ void wgmma_n128_tb(float (&d)[64], uint32_t da, uint32_t db, int scale_d) {
  asm volatile(
    "{\n.reg .pred p;\n.reg .b64 da, db;\nsetp.ne.b32 p, %66, 0;\n"
    "mov.b64 da, {%64, 0x40000040};\nmov.b64 db, {%65, 0x40000040};\n"
    "wgmma.mma_async.sync.aligned.m64n128k16.f32.bf16.bf16 {%0, %1, %2, %3, %4, %5, %6, %7, %8, %9, %10, %11, %12, %13, %14, %15, %16, %17, %18, %19, %20, %21, %22, %23, %24, %25, %26, %27, %28, %29, %30, %31, %32, %33, %34, %35, %36, %37, %38, %39, %40, %41, %42, %43, %44, %45, %46, %47, %48, %49, %50, %51, %52, %53, %54, %55, %56, %57, %58, %59, %60, %61, %62, %63}, da, db, p, 1, 1, 0, 1;\n}\n"
    : "+f"(d[0]), "+f"(d[1]), "+f"(d[2]), "+f"(d[3]), "+f"(d[4]), "+f"(d[5]), "+f"(d[6]), "+f"(d[7]), "+f"(d[8]), "+f"(d[9]), "+f"(d[10]), "+f"(d[11]), "+f"(d[12]), "+f"(d[13]), "+f"(d[14]), "+f"(d[15]), "+f"(d[16]), "+f"(d[17]), "+f"(d[18]), "+f"(d[19]), "+f"(d[20]), "+f"(d[21]), "+f"(d[22]), "+f"(d[23]), "+f"(d[24]), "+f"(d[25]), "+f"(d[26]), "+f"(d[27]), "+f"(d[28]), "+f"(d[29]), "+f"(d[30]), "+f"(d[31]), "+f"(d[32]), "+f"(d[33]), "+f"(d[34]), "+f"(d[35]), "+f"(d[36]), "+f"(d[37]), "+f"(d[38]), "+f"(d[39]), "+f"(d[40]), "+f"(d[41]), "+f"(d[42]), "+f"(d[43]), "+f"(d[44]), "+f"(d[45]), "+f"(d[46]), "+f"(d[47]), "+f"(d[48]), "+f"(d[49]), "+f"(d[50]), "+f"(d[51]), "+f"(d[52]), "+f"(d[53]), "+f"(d[54]), "+f"(d[55]), "+f"(d[56]), "+f"(d[57]), "+f"(d[58]), "+f"(d[59]), "+f"(d[60]), "+f"(d[61]), "+f"(d[62]), "+f"(d[63])
    : "r"(da), "r"(db), "r"(scale_d));
}
__device__ __forceinline__ void wgmma_n128_tb_p(float (&d)[64], uint32_t da, uint32_t db, int scale_d, int enable) {
  asm volatile(
    "{\n.reg .pred p;\n.reg .b64 da, db;\nsetp.ne.b32 p, %66, 0;\n.reg .pred q;\nsetp.ne.b32 q, %67, 0;\n"
    "mov.b64 da, {%64, 0x40000040};\nmov.b64 db, {%65, 0x40000040};\n"
    "@q wgmma.mma_async.sync.aligned.m64n128k16.f32.bf16.bf16 {%0, %1, %2, %3, %4, %5, %6, %7, %8, %9, %10, %11, %12, %13, %14, %15, %16, %17, %18, %19, %20, %21, %22, %23, %24, %25, %26, %27, %28, %29, %30, %31, %32, %33, %34, %35, %36, %37, %38, %39, %40, %41, %42, %43, %44, %45, %46, %47, %48, %49, %50, %51, %52, %53, %54, %55, %56, %57, %58, %59, %60, %61, %62, %63}, da, db, p, 1, 1, 0, 1;\n}\n"
    : "+f"(d[0]), "+f"(d[1]), "+f"(d[2]), "+f"(d[3]), "+f"(d[4]), "+f"(d[5]), "+f"(d[6]), "+f"(d[7]), "+f"(d[8]), "+f"(d[9]), "+f"(d[10]), "+f"(d[11]), "+f"(d[12]), "+f"(d[13]), "+f"(d[14]), "+f"(d[15]), "+f"(d[16]), "+f"(d[17]), "+f"(d[18]), "+f"(d[19]), "+f"(d[20]), "+f"(d[21]), "+f"(d[22]), "+f"(d[23]), "+f"(d[24]), "+f"(d[25]), "+f"(d[26]), "+f"(d[27]), "+f"(d[28]), "+f"(d[29]), "+f"(d[30]), "+f"(d[31]), "+f"(d[32]), "+f"(d[33]), "+f"(d[34]), "+f"(d[35]), "+f"(d[36]), "+f"(d[37]), "+f"(d[38]), "+f"(d[39]), "+f"(d[40]), "+f"(d[41]), "+f"(d[42]), "+f"(d[43]), "+f"(d[44]), "+f"(d[45]), "+f"(d[46]), "+f"(d[47]), "+f"(d[48]), "+f"(d[49]), "+f"(d[50]), "+f"(d[51]), "+f"(d[52]), "+f"(d[53]), "+f"(d[54]), "+f"(d[55]), "+f"(d[56]), "+f"(d[57]), "+f"(d[58]), "+f"(d[59]), "+f"(d[60]), "+f"(d[61]), "+f"(d[62]), "+f"(d[63])
    : "r"(da), "r"(db), "r"(scale_d), "r"(enable));
}
__device__ __forceinline__ void wgmma_n112(float (&d)[56], uint32_t da, uint32_t db, int scale_d) {
  asm volatile(
    "{\n.reg .pred p;\n.reg .b64 da, db;\nsetp.ne.b32 p, %58, 0;\n"
    "mov.b64 da, {%56, 0x40000040};\nmov.b64 db, {%57, 0x40000040};\n"
    "wgmma.mma_async.sync.aligned.m64n112k16.f32.bf16.bf16 {%0, %1, %2, %3, %4, %5, %6, %7, %8, %9, %10, %11, %12, %13, %14, %15, %16, %17, %18, %19, %20, %21, %22, %23, %24, %25, %26, %27, %28, %29, %30, %31, %32, %33, %34, %35, %36, %37, %38, %39, %40, %41, %42, %43, %44, %45, %46, %47, %48, %49, %50, %51, %52, %53, %54, %55}, da, db, p, 1, 1, 0, 0;\n}\n"
    : "+f"(d[0]), "+f"(d[1]), "+f"(d[2]), "+f"(d[3]), "+f"(d[4]), "+f"(d[5]), "+f"(d[6]), "+f"(d[7]), "+f"(d[8]), "+f"(d[9]), "+f"(d[10]), "+f"(d[11]), "+f"(d[12]), "+f"(d[13]), "+f"(d[14]), "+f"(d[15]), "+f"(d[16]), "+f"(d[17]), "+f"(d[18]), "+f"(d[19]), "+f"(d[20]), "+f"(d[21]), "+f"(d[22]), "+f"(d[23]), "+f"(d[24]), "+f"(d[25]), "+f"(d[26]), "+f"(d[27]), "+f"(d[28]), "+f"(d[29]), "+f"(d[30]), "+f"(d[31]), "+f"(d[32]), "+f"(d[33]), "+f"(d[34]), "+f"(d[35]), "+f"(d[36]), "+f"(d[37]), "+f"(d[38]), "+f"(d[39]), "+f"(d[40]), "+f"(d[41]), "+f"(d[42]), "+f"(d[43]), "+f"(d[44]), "+f"(d[45]), "+f"(d[46]), "+f"(d[47]), "+f"(d[48]), "+f"(d[49]), "+f"(d[50]), "+f"(d[51]), "+f"(d[52]), "+f"(d[53]), "+f"(d[54]), "+f"(d[55])
    : "r"(da), "r"(db), "r"(scale_d));
}
__device__ __forceinline__ void wgmma_n224_tb(float (&d)[112], uint32_t da, uint32_t db, int scale_d) {
  asm volatile(
    "{\n.reg .pred p;\n.reg .b64 da, db;\nsetp.ne.b32 p, %114, 0;\n"
    "mov.b64 da, {%112, 0x40000040};\nmov.b64 db, {%113, 0x40000040};\n"
    "wgmma.mma_async.sync.aligned.m64n224k16.f32.bf16.bf16 {%0, %1, %2, %3, %4, %5, %6, %7, %8, %9, %10, %11, %12, %13, %14, %15, %16, %17, %18, %19, %20, %21, %22, %23, %24, %25, %26, %27, %28, %29, %30, %31, %32, %33, %34, %35, %36, %37, %38, %39, %40, %41, %42, %43, %44, %45, %46, %47, %48, %49, %50, %51, %52, %53, %54, %55, %56, %57, %58, %59, %60, %61, %62, %63, %64, %65, %66, %67, %68, %69, %70, %71, %72, %73, %74, %75, %76, %77, %78, %79, %80, %81, %82, %83, %84, %85, %86, %87, %88, %89, %90, %91, %92, %93, %94, %95, %96, %97, %98, %99, %100, %101, %102, %103, %104, %105, %106, %107, %108, %109, %110, %111}, da, db, p, 1, 1, 0, 1;\n}\n"
    : "+f"(d[0]), "+f"(d[1]), "+f"(d[2]), "+f"(d[3]), "+f"(d[4]), "+f"(d[5]), "+f"(d[6]), "+f"(d[7]), "+f"(d[8]), "+f"(d[9]), "+f"(d[10]), "+f"(d[11]), "+f"(d[12]), "+f"(d[13]), "+f"(d[14]), "+f"(d[15]), "+f"(d[16]), "+f"(d[17]), "+f"(d[18]), "+f"(d[19]), "+f"(d[20]), "+f"(d[21]), "+f"(d[22]), "+f"(d[23]), "+f"(d[24]), "+f"(d[25]), "+f"(d[26]), "+f"(d[27]), "+f"(d[28]), "+f"(d[29]), "+f"(d[30]), "+f"(d[31]), "+f"(d[32]), "+f"(d[33]), "+f"(d[34]), "+f"(d[35]), "+f"(d[36]), "+f"(d[37]), "+f"(d[38]), "+f"(d[39]), "+f"(d[40]), "+f"(d[41]), "+f"(d[42]), "+f"(d[43]), "+f"(d[44]), "+f"(d[45]), "+f"(d[46]), "+f"(d[47]), "+f"(d[48]), "+f"(d[49]), "+f"(d[50]), "+f"(d[51]), "+f"(d[52]), "+f"(d[53]), "+f"(d[54]), "+f"(d[55]), "+f"(d[56]), "+f"(d[57]), "+f"(d[58]), "+f"(d[59]), "+f"(d[60]), "+f"(d[61]), "+f"(d[62]), "+f"(d[63]), "+f"(d[64]), "+f"(d[65]), "+f"(d[66]), "+f"(d[67]), "+f"(d[68]), "+f"(d[69]), "+f"(d[70]), "+f"(d[71]), "+f"(d[72]), "+f"(d[73]), "+f"(d[74]), "+f"(d[75]), "+f"(d[76]), "+f"(d[77]), "+f"(d[78]), "+f"(d[79]), "+f"(d[80]), "+f"(d[81]), "+f"(d[82]), "+f"(d[83]), "+f"(d[84]), "+f"(d[85]), "+f"(d[86]), "+f"(d[87]), "+f"(d[88]), "+f"(d[89]), "+f"(d[90]), "+f"(d[91]), "+f"(d[92]), "+f"(d[93]), "+f"(d[94]), "+f"(d[95]), "+f"(d[96]), "+f"(d[97]), "+f"(d[98]), "+f"(d[99]), "+f"(d[100]), "+f"(d[101]), "+f"(d[102]), "+f"(d[103]), "+f"(d[104]), "+f"(d[105]), "+f"(d[106]), "+f"(d[107]), "+f"(d[108]), "+f"(d[109]), "+f"(d[110]), "+f"(d[111])
    : "r"(da), "r"(db), "r"(scale_d));
}

constexpr int K1_NS = 5;
constexpr int K1_A_BYTES = 7 * 16384;
constexpr int K1_B_OFF = K1_A_BYTES;
constexpr int K1_STG_OFF = K1_B_OFF + K1_NS * 16384;
constexpr int K1_BAR_OFF = K1_STG_OFF + 8 * 4096;
constexpr int K1_SMEM = K1_BAR_OFF + 256 + 1024;

struct K1Ctx {
  uint32_t sb, bar_full, rel0, rel1;
  uint32_t dA, dBk, dBn;
  bool lane0;
  uint32_t bar_sfree;
  uint32_t sphase;
};
__device__ __forceinline__ void k1_release(const K1Ctx& c, int slot) {
  if (c.lane0) {
    asm volatile("mbarrier.arrive.shared::cluster.b64 _, [%0];" ::"r"(c.rel0 + 8 * slot) : "memory");
    asm volatile("mbarrier.arrive.shared::cluster.b64 _, [%0];" ::"r"(c.rel1 + 8 * slot) : "memory");
  }
}

__device__ __forceinline__ void k1_unit_ab(K1Ctx& c, int warp, int lane, int mt, int j) {
  const int wq = warp & 3;
  const int st_row = (lane & 7) + 8 * ((lane >> 3) & 1);
  const int st_chunk = lane >> 4;
  float acc[2][56];
  int slot = 0; uint32_t ph = 0;
#pragma unroll 1
  for (int kb = 0; kb < 7; kb++) {
    const int pslot = (slot == 0) ? K1_NS - 1 : slot - 1;
    mbar_wait(c.bar_full + 8 * slot, ph, 3);
    if (kb == 6) named_arrive(2, 256);
    if (kb == 0 && (threadIdx.x & 127) == 0) DBG(0, 4);
    if ((threadIdx.x & 127) == 0) DBGC(1, 46 + kb);
    wg_fence();
    const uint32_t da = c.dA + kb * 1024;
    const uint32_t db = c.dBk + slot * 1024;
#pragma unroll
    for (int k = 0; k < 4; k++) {
      wgmma_n112(acc[0], da + k * 2, db + k * 2, (kb | k) != 0);
      wgmma_n112(acc[1], da + 512 + k * 2, db + k * 2, (kb | k) != 0);
    }
    wg_commit();
    if (kb > 0) { wg_wait<1>(); k1_release(c, pslot); }
    if (++slot == K1_NS) { slot = 0; ph ^= 1; }
  }
  wg_wait<0>();
  k1_release(c, 6 % K1_NS);
  if ((threadIdx.x & 127) == 0) DBG(0, 5);
  const uint32_t sgn = (j < 4) ? 0u : 0x80008000u;
  const uint32_t sa = c.sb + K1_STG_OFF + (wq * 16 + st_row) * 224 + st_chunk * 16;
#pragma unroll
  for (int h = 0; h < 2; h++) {
    if (h == 1) { mbar_wait(c.bar_sfree, c.sphase, 6); c.sphase ^= 1; }
#pragma unroll
    for (int g = 0; g < 14; g += 2) {
      const float* a = &acc[h][4 * g];
      stmatrix_x4(sa + g * 16, pack_bf16(a[0], a[1]) ^ sgn, pack_bf16(a[2], a[3]) ^ sgn, pack_bf16(a[4], a[5]) ^ sgn, pack_bf16(a[6], a[7]) ^ sgn);
    }
    fence_async_smem();
    named_arrive(6, 160);
  }
}

__device__ __forceinline__ void k1_unit_gu(K1Ctx& c, int warp, int lane, int mt, int unit, int fb, int hsel, int full, int nunits) {
  const int wq = warp & 3;
  float acc[2][64];
  const uint32_t dA0 = c.dA + (full ? 0 : hsel * 512);
  int slot = (unit * 7) % K1_NS; uint32_t ph = ((unit * 7) / K1_NS) & 1;
  named_bar(2 + ((unit - 1) & 1), 256);
  if (full) {
#pragma unroll 1
    for (int kb = 0; kb < 7; kb++) {
      const int pslot = (slot == 0) ? K1_NS - 1 : slot - 1;
      mbar_wait(c.bar_full + 8 * slot, ph, 4);
      if (kb == 6 && unit + 1 < nunits) named_arrive(2 + (unit & 1), 256);
      if (kb == 0 && (threadIdx.x & 127) == 0) DBG(0, 4 + 3 * unit);
      wg_fence();
      const uint32_t da = dA0 + kb * 1024;
      const uint32_t db = c.dBn + slot * 1024;
#pragma unroll
      for (int k = 0; k < 4; k++) {
        wgmma_n128_tb(acc[0], da + k * 2, db + k * 128, (kb | k) != 0);
        wgmma_n128_tb(acc[1], da + 512 + k * 2, db + k * 128, (kb | k) != 0);
      }
      wg_commit();
      if (kb > 0) { wg_wait<1>(); k1_release(c, pslot); }
      if (++slot == K1_NS) { slot = 0; ph ^= 1; }
    }
  } else {
#pragma unroll 1
    for (int kb = 0; kb < 7; kb++) {
      const int pslot = (slot == 0) ? K1_NS - 1 : slot - 1;
      mbar_wait(c.bar_full + 8 * slot, ph, 5);
      if (kb == 0 && (threadIdx.x & 127) == 0) DBG(0, 4 + 3 * unit);
      wg_fence();
      const uint32_t da = dA0 + kb * 1024;
      const uint32_t db = c.dBn + slot * 1024;
#pragma unroll
      for (int k = 0; k < 4; k++) wgmma_n128_tb(acc[0], da + k * 2, db + k * 128, (kb | k) != 0);
      wg_commit();
      if (kb > 0) { wg_wait<1>(); k1_release(c, pslot); }
      if (++slot == K1_NS) { slot = 0; ph ^= 1; }
    }
  }
  wg_wait<0>();
  k1_release(c, (slot == 0) ? K1_NS - 1 : slot - 1);
  if (unit + 2 >= nunits && lane < 4) {
    asm volatile("mbarrier.arrive.shared::cluster.b64 _, [%0];" ::"r"(c.rel0 + 8 * (K1_NS + 4 + lane)) : "memory");
    asm volatile("mbarrier.arrive.shared::cluster.b64 _, [%0];" ::"r"(c.rel1 + 8 * (K1_NS + 4 + lane)) : "memory");
  }
  if ((threadIdx.x & 127) == 0) DBG(0, 5 + 3 * unit);
  const int st_row = (lane & 7) + 8 * ((lane >> 3) & 1);
  const int st_chunk = lane >> 4;
  const uint32_t sa = c.sb + K1_STG_OFF + (warp >> 2) * 16384 + (wq * 16 + st_row) * 128;
  if (unit >= 2) { mbar_wait(c.bar_sfree, c.sphase, 7); c.sphase ^= 1; }
#pragma unroll
  for (int h = 0; h < 2; h++) {
    if (h == 1 && !full) break;
#pragma unroll
    for (int g = 0; g < 8; g += 2) {
      uint32_t pk[4];
#pragma unroll
      for (int e = 0; e < 4; e++) {
        const int i = 4 * g + 2 * e;
        const uint32_t g2 = pack_bf16(acc[h][i], acc[h][i + 1]);
        const uint32_t u2 = pack_bf16(acc[h][32 + i], acc[h][32 + i + 1]);
        pk[e] = hmul2_bf16(pack_bf16(gelu_tanh(bf_lo(g2)), gelu_tanh(bf_hi(g2))), u2);
      }
      stmatrix_x4(sa + h * 8192 + (((g + st_chunk) ^ (st_row & 7)) * 16), pk[0], pk[1], pk[2], pk[3]);
    }
  }
  fence_async_smem();
  named_arrive(6 + (warp >> 2), 160);
}

constexpr int K2_NS = 4;
constexpr int K2_STAGE = 16384 + 32768;
constexpr int K2_PITCH = 464;

__device__ __forceinline__ void spin_flag(const unsigned int* flag, unsigned int target) {
  int it = 0;
  while (true) {
    unsigned int v;
    asm volatile("ld.acquire.gpu.global.u32 %0, [%1];" : "=r"(v) : "l"(flag) : "memory");
    if ((int)(v - target) >= 0) break;
    if (++it > SPIN_LIMIT) { TIMEOUT(20); break; }
  }
}

__device__ __forceinline__ void ln_rows(const __nv_bfloat16* __restrict__ xt, uint32_t sb, int lw, int lane) {
  const int c = lane & 7;
  const int r0 = lw * 4 + (lane >> 3);
  const uint4* src = reinterpret_cast<const uint4*>(xt + (size_t)r0 * 448) + c;
  uint4 nx[7];
#pragma unroll
  for (int b = 0; b < 7; b++)
    asm volatile("ld.global.nc.v4.u32 {%0,%1,%2,%3}, [%4];" : "=r"(nx[b].x), "=r"(nx[b].y), "=r"(nx[b].z), "=r"(nx[b].w) : "l"(src + b * 8) : "memory");
  const int npass = (lw < 10) ? 3 : 2;
  if (c < 7) {
    asm volatile("prefetch.global.L2 [%0];" ::"l"(src + 44 * 56 + c * 7) : "memory");
    if (npass == 3) asm volatile("prefetch.global.L2 [%0];" ::"l"(src + 88 * 56 + c * 7) : "memory");
  }
#pragma unroll 1
  for (int pass = 0; pass < npass; pass++) {
    uint4 v[7];
#pragma unroll
    for (int b = 0; b < 7; b++) v[b] = nx[b];
    if (pass + 1 < npass) {
      const uint4* s2 = src + (pass + 1) * 44 * 56;
#pragma unroll
      for (int b = 0; b < 7; b++)
        asm volatile("ld.global.nc.v4.u32 {%0,%1,%2,%3}, [%4];" : "=r"(nx[b].x), "=r"(nx[b].y), "=r"(nx[b].z), "=r"(nx[b].w) : "l"(s2 + b * 8) : "memory");
    }
        float s0 = 0.f, s1 = 0.f, s2v = 0.f, s3 = 0.f;
#pragma unroll
        for (int b = 0; b < 7; b++) {
          s0 += bf_lo(v[b].x) + bf_hi(v[b].x); s1 += bf_lo(v[b].y) + bf_hi(v[b].y);
          s2v += bf_lo(v[b].z) + bf_hi(v[b].z); s3 += bf_lo(v[b].w) + bf_hi(v[b].w);
        }
        float m = (s0 + s1) + (s2v + s3);
        m += __shfl_xor_sync(0xffffffffu, m, 1);
        m += __shfl_xor_sync(0xffffffffu, m, 2);
        m += __shfl_xor_sync(0xffffffffu, m, 4);
        m *= (1.0f / 448.0f);
        float q0 = 0.f, q1 = 0.f, q2 = 0.f, q3 = 0.f;
#pragma unroll
        for (int b = 0; b < 7; b++) {
          float d;
          d = bf_lo(v[b].x) - m; q0 = fmaf(d, d, q0); d = bf_hi(v[b].x) - m; q1 = fmaf(d, d, q1);
          d = bf_lo(v[b].y) - m; q2 = fmaf(d, d, q2); d = bf_hi(v[b].y) - m; q3 = fmaf(d, d, q3);
          d = bf_lo(v[b].z) - m; q0 = fmaf(d, d, q0); d = bf_hi(v[b].z) - m; q1 = fmaf(d, d, q1);
          d = bf_lo(v[b].w) - m; q2 = fmaf(d, d, q2); d = bf_hi(v[b].w) - m; q3 = fmaf(d, d, q3);
        }
        float q = (q0 + q1) + (q2 + q3);
        q += __shfl_xor_sync(0xffffffffu, q, 1);
        q += __shfl_xor_sync(0xffffffffu, q, 2);
        q += __shfl_xor_sync(0xffffffffu, q, 4);
        const float var_b = rbf(q * (1.0f / 448.0f));
        const float den = rbf(sqrtf(rbf(var_b + 1e-5f)));
        const float ri = 1.0f / den;
        const float rih = rbf(ri);
        const uint32_t rhi2 = pack_bf16(rih, rih), rlo2 = pack_bf16(ri - rih, ri - rih);
        const uint32_t m2 = pack_bf16(m, m);
        const int r = r0 + pass * 44;
        const uint32_t a0 = sb + r * 128 + ((c ^ (r & 7)) * 16);
#pragma unroll
        for (int b = 0; b < 7; b++) {
          uint32_t w4[4] = {v[b].x, v[b].y, v[b].z, v[b].w};
#pragma unroll
          for (int qq = 0; qq < 4; qq++) {
            const uint32_t dw = hsub2_bf16(w4[qq], m2);
            w4[qq] = hfma2_bf16(dw, rhi2, hmul2_bf16(dw, rlo2));
          }
          sts128(a0 + b * 16384, make_uint4(w4[0], w4[1], w4[2], w4[3]));
        }
  }
}

struct PfPtrs { const uint8_t* wg; const uint8_t* wu; const uint8_t* wd; };

__global__ void __cluster_dims__(2, 1, 1) __launch_bounds__(384, 1)
fused_kernel(const __grid_constant__ CUtensorMap tm_wr, const __grid_constant__ CUtensorMap tm_wi,
             const __grid_constant__ CUtensorMap tm_wg, const __grid_constant__ CUtensorMap tm_wu,
             const __grid_constant__ CUtensorMap tm_hs, const __grid_constant__ CUtensorMap tm_abs,
             const __grid_constant__ CUtensorMap tm_cr, const __grid_constant__ CUtensorMap tm_ci, const __grid_constant__ CUtensorMap tm_h,
             const __grid_constant__ CUtensorMap tm_ab, const __grid_constant__ CUtensorMap tm_wd,
             const __nv_bfloat16* __restrict__ x, __nv_bfloat16* __restrict__ out, const PfPtrs pf) {
  extern __shared__ uint8_t smem_raw[];
  const uint32_t sb = (s2u(smem_raw) + 1023) & ~1023u;
  const int tid = threadIdx.x, warp = tid >> 5, lane = tid & 31;
  uint32_t rank;
  asm volatile("mov.u32 %0, %%cluster_ctarank;" : "=r"(rank));
  const int cid = blockIdx.x >> 1;
  const int p = cid >> 3, j = cid & 7;
  const int mt = 2 * p + (int)rank;
  const uint32_t bar_full = sb + K1_BAR_OFF;
  const uint32_t bar_empty = bar_full + 8 * K1_NS;
  const uint32_t bar_full2 = bar_empty + 8 * K1_NS;
  const uint32_t bar_empty2 = bar_full2 + 8 * K2_NS;
  const int fb_base = 7 * (j >> 1);
  const int fb0 = fb_base + ((j & 1) ? 4 : 0);
  const int fbh = fb_base + 3;
  const int q = j & 3, n = j >> 2;
  const int tile = mt * 2 + n;
  const int nkb = (q < 2) ? 22 : (q == 3 ? 28 : 20);
  const int nunits = (q == 3) ? 4 : 5;
  const int u4full = (q == 2);

  const unsigned int epoch = *reinterpret_cast<volatile unsigned int*>(&g_epoch);
  if (tid == 0) DBG(0, 0);
  if (tid == 256) {
    for (int i = 0; i < K1_NS; i++) { mbar_init(bar_full + 8 * i, 1); mbar_init(bar_empty + 8 * i, 8); }
    for (int i = 0; i < K2_NS; i++) { mbar_init(bar_full2 + 8 * i, 1); mbar_init(bar_empty2 + 8 * i, 16); }
    mbar_init(bar_empty2 + 8 * K2_NS, 1);
    mbar_init(bar_empty2 + 8 * K2_NS + 8, 1);
    mbar_init(bar_empty2 + 8 * K2_NS + 16, 1);
    asm volatile("fence.mbarrier_init.release.cluster;" ::: "memory");
    prefetch_tmap((j < 4) ? &tm_wr : &tm_wi);
    prefetch_tmap(rank ? &tm_wu : &tm_wg);
    prefetch_tmap(&tm_abs);
    prefetch_tmap(&tm_hs);
  }
  __syncwarp();
  cluster_arrive_relaxed();

  if (warp != 8) {
    ln_rows(x + (size_t)mt * 128 * 448, sb, warp < 8 ? warp : warp - 1, lane);
    asm volatile("fence.proxy.async.shared::cta;" ::: "memory");
  }
  if (warp >= 8) {
    if (warp > 8) named_arrive(8, 352);
    reg_dec<40>();
    cluster_wait();
    if (tid == 256) {
      {
        const CUtensorMap* tw = (j < 4) ? &tm_wr : &tm_wi;
        const CUtensorMap* tgu = rank ? &tm_wu : &tm_wg;
        int slot = 0; uint32_t ph = 0;
        int kb = 0, unit = 0;
#pragma unroll 1
        for (int s = 0; s < 7 * nunits; s++) {
          if (s >= K1_NS) mbar_wait(bar_empty + 8 * slot, ph ^ 1, 2);
          const uint32_t dst = sb + K1_B_OFF + slot * 16384;
          if (unit == 0) {
            mbar_expect(bar_full + 8 * slot, 14336);
            tma2d_mc(dst + rank * 7168, tw, kb * 64, (j & 3) * 112 + rank * 56, bar_full + 8 * slot, 3);
          } else {
            const int fb = (unit == 4) ? fbh : (fb0 + unit - 1);
            mbar_expect(bar_full + 8 * slot, 16384);
            tma2d_mc(dst + rank * 8192, tgu, fb * 64, kb * 64, bar_full + 8 * slot, 3);
          }
          if (s == 21) {
            l2_prefetch(pf.wd + blockIdx.x * 12544, 12544);
            if (q < 3) {
              const int g0 = q * 22;
#pragma unroll 1
              for (int i = 0; i < 6; i++) tma2d_prefetch((g0 + i < 32) ? &tm_cr : &tm_ci, ((g0 + i) & 31) * 64, mt * 128);
            }
          }
          if (++kb == 7) { kb = 0; unit++; }
          if (++slot == K1_NS) { slot = 0; ph ^= 1; }
        }
      }
      {
        const int g0 = (q == 0) ? 0 : (q == 1 ? 22 : (q == 2 ? 44 : 64));
        const CUtensorMap* tb = (q < 3) ? &tm_ab : &tm_wd;
        prefetch_tmap(tb); prefetch_tmap((q < 3) ? ((g0 < 32) ? &tm_cr : &tm_ci) : &tm_h);
        const int kb0 = (q < 3) ? g0 : 0;
        if (q < 3) { spin_flag(&g_ab_cnt, 128u * (epoch + 1)); asm volatile("fence.proxy.async;" ::: "memory"); }
        DBG(1, 31);
        int slot = 0; uint32_t ph = 0;
#pragma unroll 1
        for (int s = 0; s < nkb; s++) {
          int kblk = kb0 + s;
          const CUtensorMap* ta = (kblk < 32) ? &tm_cr : &tm_ci;
          if (q == 3) {
            if ((s & 7) == 0) { spin_flag(&g_h_cnt[mt * 4 + (s >> 3)], ((s < 24) ? 8u : 6u) * (epoch + 1)); asm volatile("fence.proxy.async;" ::: "memory"); }
            const int i = s & 7;
            kblk = (s < 24) ? (7 * (i >> 1) + ((i & 1) ? 4 : 0) + (s >> 3)) : (7 * i + 3);
            ta = &tm_h;
          }
          mbar_wait(bar_empty2 + 8 * slot, ph, 10);
          const uint32_t dst = sb + slot * K2_STAGE;
          const uint32_t fb = bar_full2 + 8 * slot;
          mbar_expect(fb, K2_STAGE);
          tma2d(dst, ta, (kblk & 31) * 64, mt * 128, fb);
          tma3d_mc(dst + 16384 + (2 * rank) * 8192, tb, (2 * rank) * 64, n, kblk * 64, fb, 3);
          tma3d_mc(dst + 16384 + (2 * rank + 1) * 8192, tb, (2 * rank + 1) * 64, n, kblk * 64, fb, 3);
          if (++slot == K2_NS) { slot = 0; ph ^= 1; }
        }
      }
    } else if (warp == 9 || warp == 10) {
      const int hw = warp - 9;
      const uint32_t stg = sb + K1_STG_OFF + hw * 16384;
      const uint32_t bar_sfree = bar_empty2 + 8 * K2_NS + 8 + 8 * hw;
      if (lane == 0) {
        const int b = blockIdx.x;
        l2_prefetch((hw ? pf.wu : pf.wg) + b * 12544, 12544);
      }
#pragma unroll 1
      for (int job = 0; job < (hw ? 2 : (nunits == 5 ? 4 : 3)); job++) {
        named_bar(6 + hw, 160);
        if (lane == 0) {
          const int unit = hw ? (1 + 2 * job) : (job < 2 ? 0 : 2 * job - 2);
          if (unit == 0) {
            tma2d_store(&tm_abs, stg, (j & 3) * 112, (j < 4 ? 0 : 2048) + mt * 128 + job * 64);
          } else {
            const int fb = (unit == 4) ? fbh : fb0 + unit - 1;
            const bool fullu = (unit < 4) || u4full;
            tma2d_store(&tm_hs, stg, fb * 64, mt * 128 + (fullu ? 0 : (j & 1) * 64));
            if (fullu) tma2d_store(&tm_hs, stg + 8192, fb * 64, mt * 128 + 64);
          }
          bulk_commit();
          bulk_wait_read0();
          asm volatile("mbarrier.arrive.shared::cta.b64 _, [%0];" ::"r"(bar_sfree) : "memory");
          if (unit != 0 || job == 1) {
            bulk_wait0();
            asm volatile("fence.proxy.async;" ::: "memory");
            __threadfence();
            if (unit == 0) {
              const unsigned int old = atomicAdd(&g_ab_cnt, 1u);
              if ((old & 127u) == 127u) *reinterpret_cast<volatile unsigned int*>(&g_epoch) = (old >> 7) + 1;
            } else {
              atomicAdd(&g_h_cnt[mt * 4 + unit - 1], 1u);
            }
          }
        }
        __syncwarp();
      }
    }
  } else {
    const int wg = warp >> 2;
    named_bar(8, 352);
    reg_inc<232>();
    cluster_wait();
    if (tid == 0) DBG(0, 3);

    uint32_t rel0, rel1, sphase_end;
    asm volatile("mapa.shared::cluster.u32 %0, %1, %2;" : "=r"(rel0) : "r"(bar_empty2), "r"(0));
    asm volatile("mapa.shared::cluster.u32 %0, %1, %2;" : "=r"(rel1) : "r"(bar_empty2), "r"(1));
    {
      K1Ctx c;
      c.sb = sb; c.bar_full = bar_full; c.lane0 = (lane == 0);
      c.rel0 = rel0 - 8 * (K1_NS + K2_NS); c.rel1 = rel1 - 8 * (K1_NS + K2_NS);
      c.bar_sfree = bar_empty2 + 8 * K2_NS + 8 + 8 * wg; c.sphase = 0;
      c.dA = make_desc(sb, 16, 1024);
      c.dBk = make_desc(sb + K1_B_OFF, 16, 1024);
      c.dBn = make_desc(sb + K1_B_OFF, 8192, 1024);
      if (wg == 0) {
        k1_unit_ab(c, warp, lane, mt, j);
        if (tid == 0) DBG(0, 6);
      }
#pragma unroll 1
      for (int unit = 2 - wg; unit < nunits; unit += 2) {
        k1_unit_gu(c, warp, lane, mt, unit, (unit == 4) ? fbh : fb0 + unit - 1, j & 1, (unit < 4) || u4full, nunits);
        if ((tid & 127) == 0) DBG(0, 6 + 3 * unit);
      }
      sphase_end = c.sphase;
    }

    float acc[112];
    const uint32_t dA0 = make_desc(sb + wg * 8192, 16, 1024);
    const uint32_t dB0 = make_desc(sb + 16384, 8192, 1024);
    int slot = 0; uint32_t ph = 0;
#pragma unroll 1
    for (int s = 0; s < nkb; s++) {
      mbar_wait(bar_full2 + 8 * slot, ph, 11);
      if (tid == 0) DBG(1, 1 + s);
      wg_fence();
      const uint32_t da = dA0 + slot * (K2_STAGE / 16);
      const uint32_t db = dB0 + slot * (K2_STAGE / 16);
#pragma unroll
      for (int k = 0; k < 4; k++) wgmma_n224_tb(acc, da + k * 2, db + k * 128, (s | k) != 0);
      wg_commit();
      if (s > 0) {
        wg_wait<1>();
        const int ps = (slot == 0) ? K2_NS - 1 : slot - 1;
        if (lane == 0) {
          asm volatile("mbarrier.arrive.shared::cluster.b64 _, [%0];" ::"r"(rel0 + 8 * ps) : "memory");
          asm volatile("mbarrier.arrive.shared::cluster.b64 _, [%0];" ::"r"(rel1 + 8 * ps) : "memory");
        }
      }
      if (++slot == K2_NS) { slot = 0; ph ^= 1; }
    }
    wg_wait<0>();
    if (tid == 0) DBG(1, 29);
    uint32_t ow[56];
#pragma unroll
    for (int i = 0; i < 56; i++) ow[i] = pack_bf16(acc[2 * i], acc[2 * i + 1]);
    if (q == 3) {
#pragma unroll
      for (int i = 0; i < 56; i++) ow[i] = pack_bf16(silu_f(bf_lo(ow[i])), silu_f(bf_hi(ow[i])));
    }
    const int P0 = (q < 2) ? 4 * q : 3 * q + 2, NP = (q < 2) ? 4 : 3;
    uint4* part = g_part + (size_t)tile * (4 * 14 * 256) + tid;
    uint4 mine[4];
#pragma unroll
    for (int g = 0; g < 14; g++) {
      const uint4 v = make_uint4(ow[4 * g], ow[4 * g + 1], ow[4 * g + 2], ow[4 * g + 3]);
      const int rel = g - P0;
      if ((unsigned)rel >= (unsigned)NP) part[(q * 14 + g) * 256] = v;
#pragma unroll
      for (int e = 0; e < 4; e++) if (rel == e) mine[e] = v;
    }
    __syncwarp();
    unsigned int* flag = &g_flags[tile * 8 + warp];
    if (lane == 0) { __threadfence(); atomicAdd(flag, 1u); }
    const int ch = lane & 7;
    const bool act = ch < 2 * NP;
    const size_t gbase = (size_t)(mt * 128 + warp * 16 + (lane >> 3)) * 448 + n * 224 + P0 * 16 + (act ? ch : 0) * 8;
    uint4 xv[4];
#pragma unroll
    for (int t = 0; t < 4; t++) xv[t] = ldg128_cg(x + gbase + t * 4 * 448);
    if (tid == 0) DBG(1, 62);
    if (lane == 0) spin_flag(flag, 4u * (epoch + 1));
    __syncwarp();
    if (tid == 0) DBG(1, 30);
    uint4 oth[3][4];
#pragma unroll
    for (int i = 0; i < 3; i++) {
      const int r = (i < q) ? i : i + 1;
#pragma unroll
      for (int e = 0; e < 4; e++) oth[i][e] = ldg128_cg(part + (r * 14 + P0 + (e < NP ? e : 0)) * 256);
    }
    const bool isf = (q == 3);
    mbar_wait(bar_empty2 + 8 * K2_NS + 8 + 8 * wg, sphase_end, 14);
    const uint32_t stg = sb + K1_STG_OFF + warp * 4096;
    const int st_row = (lane & 7) + 8 * ((lane >> 3) & 1);
    const uint32_t sa = stg + st_row * 128;
#pragma unroll
    for (int e = 0; e < 4; e++) {
      const uint32_t av[4] = {oth[0][e].x, oth[0][e].y, oth[0][e].z, oth[0][e].w};
      const uint32_t bv[4] = {oth[1][e].x, oth[1][e].y, oth[1][e].z, oth[1][e].w};
      const uint32_t cv[4] = {oth[2][e].x, oth[2][e].y, oth[2][e].z, oth[2][e].w};
      const uint32_t mv[4] = {mine[e].x, mine[e].y, mine[e].z, mine[e].w};
      uint32_t tv[4];
#pragma unroll
      for (int k = 0; k < 4; k++) {
        const uint32_t y3 = isf ? cv[k] : mv[k], gg = isf ? mv[k] : cv[k];
        tv[k] = hmul2_bf16(pack_bf16(bf_lo(av[k]) + bf_lo(bv[k]) + bf_lo(y3), bf_hi(av[k]) + bf_hi(bv[k]) + bf_hi(y3)), gg);
      }
      stmatrix_x4(sa + (((2 * e + (lane >> 4)) ^ (st_row & 7)) * 16), tv[0], tv[1], tv[2], tv[3]);
    }
    __syncwarp();
#pragma unroll
    for (int t = 0; t < 4; t++) {
      const int row = t * 4 + (lane >> 3);
      const uint4 tv = lds128(stg + row * 128 + ((ch ^ (row & 7)) * 16));
      uint4 o;
      o.x = hadd2_bf16(xv[t].x, tv.x); o.y = hadd2_bf16(xv[t].y, tv.y); o.z = hadd2_bf16(xv[t].z, tv.z); o.w = hadd2_bf16(xv[t].w, tv.w);
      if (act) stg128(out + gbase + t * 4 * 448, o);
    }
    if (tid == 0) DBG(1, 63);
  }
  __syncwarp();
  cluster_arrive_relaxed();
  cluster_wait();
}

typedef CUresult (*EncFn)(CUtensorMap*, CUtensorMapDataType, cuuint32_t, void*, const cuuint64_t*, const cuuint64_t*, const cuuint32_t*,
                          const cuuint32_t*, CUtensorMapInterleave, CUtensorMapSwizzle, CUtensorMapL2promotion, CUtensorMapFloatOOBfill);

void make2d(EncFn enc, CUtensorMap* tm, const void* ptr, uint64_t cols, uint64_t rows, uint32_t bc, uint32_t br, bool swz = true) {
  cuuint64_t gd[2] = {cols, rows};
  cuuint64_t gs[1] = {cols * 2};
  cuuint32_t bd[2] = {bc, br};
  cuuint32_t es[2] = {1, 1};
  enc(tm, CU_TENSOR_MAP_DATA_TYPE_BFLOAT16, 2, const_cast<void*>(ptr), gd, gs, bd, es, CU_TENSOR_MAP_INTERLEAVE_NONE,
      swz ? CU_TENSOR_MAP_SWIZZLE_128B : CU_TENSOR_MAP_SWIZZLE_NONE, CU_TENSOR_MAP_L2_PROMOTION_L2_128B, CU_TENSOR_MAP_FLOAT_OOB_FILL_NONE);
}
void make3d_half(EncFn enc, CUtensorMap* tm, const void* ptr, uint64_t rows) {
  cuuint64_t gd[3] = {224, 2, rows};
  cuuint64_t gs[2] = {448, 896};
  cuuint32_t bd[3] = {64, 1, 64};
  cuuint32_t es[3] = {1, 1, 1};
  enc(tm, CU_TENSOR_MAP_DATA_TYPE_BFLOAT16, 3, const_cast<void*>(ptr), gd, gs, bd, es, CU_TENSOR_MAP_INTERLEAVE_NONE,
      CU_TENSOR_MAP_SWIZZLE_128B, CU_TENSOR_MAP_L2_PROMOTION_L2_128B, CU_TENSOR_MAP_FLOAT_OOB_FILL_NONE);
}

struct Maps { CUtensorMap wr, wi, wg, wu, cr, ci, h, ab, wd, hs, abs; };

}

extern "C" void kernel_launch(void* const* d_in, const int* in_sizes, int n_in, void* d_out, int out_size) {
  (void)in_sizes; (void)n_in; (void)out_size;
  static Maps maps;
  static const void* cached[9] = {nullptr};
  static bool attr_done = false;
  bool same = true;
  for (int i = 0; i < 9; i++) same = same && (cached[i] == d_in[i]);
  if (!same) {
    void* fn = nullptr;
    cudaDriverEntryPointQueryResult qr;
    cudaGetDriverEntryPoint("cuTensorMapEncodeTiled", &fn, cudaEnableDefault, &qr);
    EncFn enc = (EncFn)fn;
    void *p_ab = nullptr, *p_h = nullptr;
    cudaGetSymbolAddress(&p_ab, g_ab);
    cudaGetSymbolAddress(&p_h, g_h);
    make2d(enc, &maps.cr, d_in[1], 2048, 2048, 64, 128);
    make2d(enc, &maps.ci, d_in[2], 2048, 2048, 64, 128);
    make2d(enc, &maps.wr, d_in[3], 448, 448, 64, 56);
    make2d(enc, &maps.wi, d_in[4], 448, 448, 64, 56);
    make2d(enc, &maps.wg, d_in[6], 1792, 448, 64, 64);
    make2d(enc, &maps.wu, d_in[7], 1792, 448, 64, 64);
    make3d_half(enc, &maps.wd, d_in[8], 1792);
    make2d(enc, &maps.h, p_h, 1792, 2048, 64, 128);
    make3d_half(enc, &maps.ab, p_ab, 4096);
    make2d(enc, &maps.hs, p_h, 1792, 2048, 64, 64);
    make2d(enc, &maps.abs, p_ab, 448, 4096, 112, 64, false);
    for (int i = 0; i < 9; i++) cached[i] = d_in[i];
  }
  if (!attr_done) {
    cudaFuncSetAttribute(fused_kernel, cudaFuncAttributeMaxDynamicSharedMemorySize, K1_SMEM);
    attr_done = true;
  }
  PfPtrs pf;
  pf.wg = (const uint8_t*)d_in[6]; pf.wu = (const uint8_t*)d_in[7]; pf.wd = (const uint8_t*)d_in[8];
  fused_kernel<<<128, 384, K1_SMEM>>>(maps.wr, maps.wi, maps.wg, maps.wu, maps.hs, maps.abs, maps.cr, maps.ci, maps.h, maps.ab, maps.wd,
                                      (const __nv_bfloat16*)d_in[0], (__nv_bfloat16*)d_out, pf);
}
```

```cpp
#include <cuda_runtime.h>
#include <cuda_bf16.h>
#include <cuda.h>
#include <stdint.h>

namespace {

__device__ __align__(1024) __nv_bfloat16 g_ab[4096 * 448];
__device__ __align__(1024) __nv_bfloat16 g_h[2048 * 1792];
__device__ uint4 g_part[32 * 4 * 14 * 256];
__device__ __align__(1024) __nv_bfloat16 g_s[2048 * 448];
__device__ unsigned int g_epoch;
__device__ unsigned int g_ab_cnt;
__device__ unsigned int g_h_cnt[16 * 4];
__device__ unsigned int g_flags[32 * 8];

#define DBG(k, i) do {} while (0)
#define DBGC(k, i) do {} while (0)

#define TIMEOUT(code) __trap()
#define SPIN_LIMIT (1 << 22)
__device__ __forceinline__ uint32_t s2u(const void* p) { return (uint32_t)__cvta_generic_to_shared(p); }
__device__ __forceinline__ void mbar_init(uint32_t b, int c) { asm volatile("mbarrier.init.shared::cta.b64 [%0], %1;" ::"r"(b), "r"(c)); }
__device__ __forceinline__ void mbar_expect(uint32_t b, uint32_t bytes) {
  asm volatile("mbarrier.arrive.expect_tx.shared::cta.b64 _, [%0], %1;" ::"r"(b), "r"(bytes) : "memory");
}
__device__ __forceinline__ void mbar_wait(uint32_t b, uint32_t ph, int code = 1) {
  uint32_t done = 0;
  int it = 0;
  while (true) {
    asm volatile("{.reg .pred p; mbarrier.try_wait.parity.shared::cta.b64 p, [%1], %2; selp.u32 %0,1,0,p;}" : "=r"(done) : "r"(b), "r"(ph) : "memory");
    if (done) break;
    if (++it > SPIN_LIMIT) { TIMEOUT(code); break; }
  }
}
__device__ __forceinline__ void mbar_arrive_cluster(uint32_t b, uint32_t cta) {
  uint32_t r;
  asm volatile("mapa.shared::cluster.u32 %0, %1, %2;" : "=r"(r) : "r"(b), "r"(cta));
  asm volatile("mbarrier.arrive.shared::cluster.b64 _, [%0];" ::"r"(r) : "memory");
}
__device__ __forceinline__ void tma2d(uint32_t dst, const CUtensorMap* m, int c0, int c1, uint32_t bar) {
  asm volatile("cp.async.bulk.tensor.2d.shared::cluster.global.mbarrier::complete_tx::bytes [%0], [%1, {%3,%4}], [%2];" ::"r"(dst), "l"(m), "r"(bar), "r"(c0), "r"(c1) : "memory");
}
__device__ __forceinline__ void tma2d_mc(uint32_t dst, const CUtensorMap* m, int c0, int c1, uint32_t bar, uint16_t mask) {
  asm volatile("cp.async.bulk.tensor.2d.shared::cluster.global.mbarrier::complete_tx::bytes.multicast::cluster [%0], [%1, {%3,%4}], [%2], %5;" ::"r"(dst), "l"(m), "r"(bar), "r"(c0), "r"(c1), "h"(mask) : "memory");
}
__device__ __forceinline__ void tma3d_mc(uint32_t dst, const CUtensorMap* m, int c0, int c1, int c2, uint32_t bar, uint16_t mask) {
  asm volatile("cp.async.bulk.tensor.3d.shared::cluster.global.mbarrier::complete_tx::bytes.multicast::cluster [%0], [%1, {%3,%4,%5}], [%2], %6;" ::"r"(dst), "l"(m), "r"(bar), "r"(c0), "r"(c1), "r"(c2), "h"(mask) : "memory");
}
__device__ __forceinline__ void tma2d_store(const CUtensorMap* m, uint32_t src, int c0, int c1) {
  asm volatile("cp.async.bulk.tensor.2d.global.shared::cta.bulk_group [%0, {%2,%3}], [%1];" ::"l"(m), "r"(src), "r"(c0), "r"(c1) : "memory");
}
__device__ __forceinline__ void bulk_load(uint32_t dst, const void* src, uint32_t bytes, uint32_t bar) {
  asm volatile("cp.async.bulk.shared::cluster.global.mbarrier::complete_tx::bytes [%0], [%1], %2, [%3];" ::"r"(dst), "l"(src), "r"(bytes), "r"(bar) : "memory");
}
__device__ __forceinline__ void tma2d_prefetch(const CUtensorMap* m, int c0, int c1) {
  asm volatile("cp.async.bulk.prefetch.tensor.2d.L2.global [%0, {%1,%2}];" ::"l"(m), "r"(c0), "r"(c1) : "memory");
}
__device__ __forceinline__ void bulk_commit() { asm volatile("cp.async.bulk.commit_group;" ::: "memory"); }
__device__ __forceinline__ void bulk_wait_read0() { asm volatile("cp.async.bulk.wait_group.read 0;" ::: "memory"); }
__device__ __forceinline__ void bulk_wait0() { asm volatile("cp.async.bulk.wait_group 0;" ::: "memory"); }
__device__ __forceinline__ void fence_async_smem() { asm volatile("fence.proxy.async.shared::cta;" ::: "memory"); }
__device__ __forceinline__ void prefetch_tmap(const CUtensorMap* m) { asm volatile("prefetch.tensormap [%0];" ::"l"(m) : "memory"); }
__device__ __forceinline__ void l2_prefetch(const void* p, uint32_t bytes) {
  asm volatile("cp.async.bulk.prefetch.L2.global [%0], %1;" ::"l"(p), "r"(bytes) : "memory");
}
__device__ __forceinline__ void cluster_arrive_relaxed() { asm volatile("barrier.cluster.arrive.relaxed.aligned;" ::: "memory"); }
__device__ __forceinline__ void cluster_wait() { asm volatile("barrier.cluster.wait.aligned;" ::: "memory"); }
__device__ __forceinline__ void wg_fence() { __syncwarp(); asm volatile("wgmma.fence.sync.aligned;" ::: "memory"); }
__device__ __forceinline__ void wg_commit() { asm volatile("wgmma.commit_group.sync.aligned;" ::: "memory"); }
template <int N> __device__ __forceinline__ void wg_wait() { __syncwarp(); asm volatile("wgmma.wait_group.sync.aligned %0;" ::"n"(N) : "memory"); }
__device__ __forceinline__ void named_bar(int id, int n) { asm volatile("bar.sync %0, %1;" ::"r"(id), "r"(n) : "memory"); }
__device__ __forceinline__ void named_arrive(int id, int n) { asm volatile("bar.arrive %0, %1;" ::"r"(id), "r"(n) : "memory"); }
template <int N> __device__ __forceinline__ void reg_inc() { asm volatile("setmaxnreg.inc.sync.aligned.u32 %0;" ::"n"(N)); }
template <int N> __device__ __forceinline__ void reg_dec() { asm volatile("setmaxnreg.dec.sync.aligned.u32 %0;" ::"n"(N)); }
__device__ __forceinline__ void pdl_wait() { asm volatile("griddepcontrol.wait;" ::: "memory"); }
__device__ __forceinline__ void pdl_launch() { asm volatile("griddepcontrol.launch_dependents;" ::: "memory"); }

__device__ __forceinline__ uint32_t make_desc(uint32_t addr, uint32_t lbo, uint32_t  ) {
  return ((addr & 0x3FFFF) >> 4) | ((lbo >> 4) << 16);
}
__device__ __forceinline__ void stmatrix_x4(uint32_t addr, uint32_t r0, uint32_t r1, uint32_t r2, uint32_t r3) {
  asm volatile("stmatrix.sync.aligned.m8n8.x4.shared.b16 [%0], {%1,%2,%3,%4};" ::"r"(addr), "r"(r0), "r"(r1), "r"(r2), "r"(r3) : "memory");
}
__device__ __forceinline__ uint4 lds128(uint32_t a) {
  uint4 v;
  asm volatile("ld.shared.v4.u32 {%0,%1,%2,%3}, [%4];" : "=r"(v.x), "=r"(v.y), "=r"(v.z), "=r"(v.w) : "r"(a) : "memory");
  return v;
}
__device__ __forceinline__ void sts128(uint32_t a, uint4 v) {
  asm volatile("st.shared.v4.u32 [%0], {%1,%2,%3,%4};" ::"r"(a), "r"(v.x), "r"(v.y), "r"(v.z), "r"(v.w) : "memory");
}
__device__ __forceinline__ void stg128(void* p, uint4 v) {
  asm volatile("st.global.v4.u32 [%0], {%1,%2,%3,%4};" ::"l"(p), "r"(v.x), "r"(v.y), "r"(v.z), "r"(v.w) : "memory");
}
__device__ __forceinline__ void cp_async16(uint32_t dst, const void* src) {
  asm volatile("cp.async.cg.shared.global [%0], [%1], 16;" ::"r"(dst), "l"(src) : "memory");
}
__device__ __forceinline__ void cp_async8(uint32_t dst, const void* src) {
  asm volatile("cp.async.ca.shared.global [%0], [%1], 8;" ::"r"(dst), "l"(src) : "memory");
}
__device__ __forceinline__ uint2 lds64(uint32_t a) {
  uint2 v;
  asm volatile("ld.shared.v2.u32 {%0,%1}, [%2];" : "=r"(v.x), "=r"(v.y) : "r"(a) : "memory");
  return v;
}
__device__ __forceinline__ void cp_async_wait_all() { asm volatile("cp.async.wait_all;" ::: "memory"); }
__device__ __forceinline__ uint32_t pack_bf16(float lo, float hi) {
  uint32_t r;
  asm("cvt.rn.bf16x2.f32 %0, %1, %2;" : "=r"(r) : "f"(hi), "f"(lo));
  return r;
}
__device__ __forceinline__ uint32_t hmul2_bf16(uint32_t a, uint32_t b) {
  uint32_t r;
  asm("mul.rn.bf16x2 %0, %1, %2;" : "=r"(r) : "r"(a), "r"(b));
  return r;
}
__device__ __forceinline__ uint32_t hsub2_bf16(uint32_t a, uint32_t b) {
  uint32_t r;
  asm("sub.rn.bf16x2 %0, %1, %2;" : "=r"(r) : "r"(a), "r"(b));
  return r;
}
__device__ __forceinline__ uint32_t hadd2_bf16(uint32_t a, uint32_t b) {
  uint32_t r;
  asm("add.rn.bf16x2 %0, %1, %2;" : "=r"(r) : "r"(a), "r"(b));
  return r;
}
__device__ __forceinline__ uint32_t hfma2_bf16(uint32_t a, uint32_t b, uint32_t c) {
  uint32_t r;
  asm("fma.rn.bf16x2 %0, %1, %2, %3;" : "=r"(r) : "r"(a), "r"(b), "r"(c));
  return r;
}
__device__ __forceinline__ bool mbar_test(uint32_t b, uint32_t ph) {
  uint32_t done;
  asm volatile("{.reg .pred p; mbarrier.test_wait.parity.shared::cta.b64 p, [%1], %2; selp.u32 %0,1,0,p;}" : "=r"(done) : "r"(b), "r"(ph) : "memory");
  return __all_sync(0xffffffffu, done != 0);
}
__device__ __forceinline__ uint4 ldg128_cg(const void* p) {
  uint4 v;
  asm volatile("ld.global.cg.v4.u32 {%0,%1,%2,%3}, [%4];" : "=r"(v.x), "=r"(v.y), "=r"(v.z), "=r"(v.w) : "l"(p) : "memory");
  return v;
}
__device__ __forceinline__ float bf_lo(uint32_t w) { return __uint_as_float(w << 16); }
__device__ __forceinline__ float bf_hi(uint32_t w) { return __uint_as_float(w & 0xffff0000u); }
__device__ __forceinline__ float rbf(float x) { return __bfloat162float(__float2bfloat16_rn(x)); }
__device__ __forceinline__ float ex2f(float x) { float r; asm("ex2.approx.ftz.f32 %0, %1;" : "=f"(r) : "f"(x)); return r; }
__device__ __forceinline__ float rcpf(float x) { float r; asm("rcp.approx.ftz.f32 %0, %1;" : "=f"(r) : "f"(x)); return r; }
__device__ __forceinline__ float tanhf_hw(float x) { float r; asm("tanh.approx.f32 %0, %1;" : "=f"(r) : "f"(x)); return r; }
__device__ __forceinline__ float gelu_tanh(float x) {
  const float c1 = 0.7978845608028654f;
  const float c2 = c1 * 0.044715f;
  const float t = tanhf_hw(x * fmaf(c2, x * x, c1));
  const float hx = 0.5f * x;
  return fmaf(hx, t, hx);
}
__device__ __forceinline__ float silu_f(float x) {
  const float hx = 0.5f * x;
  return fmaf(hx, tanhf_hw(hx), hx);
}

__device__ __forceinline__ void wgmma_n128_tb(float (&d)[64], uint32_t da, uint32_t db, int scale_d) {
  asm volatile(
    "{\n.reg .pred p;\n.reg .b64 da, db;\nsetp.ne.b32 p, %66, 0;\n"
    "mov.b64 da, {%64, 0x40000040};\nmov.b64 db, {%65, 0x40000040};\n"
    "wgmma.mma_async.sync.aligned.m64n128k16.f32.bf16.bf16 {%0, %1, %2, %3, %4, %5, %6, %7, %8, %9, %10, %11, %12, %13, %14, %15, %16, %17, %18, %19, %20, %21, %22, %23, %24, %25, %26, %27, %28, %29, %30, %31, %32, %33, %34, %35, %36, %37, %38, %39, %40, %41, %42, %43, %44, %45, %46, %47, %48, %49, %50, %51, %52, %53, %54, %55, %56, %57, %58, %59, %60, %61, %62, %63}, da, db, p, 1, 1, 0, 1;\n}\n"
    : "+f"(d[0]), "+f"(d[1]), "+f"(d[2]), "+f"(d[3]), "+f"(d[4]), "+f"(d[5]), "+f"(d[6]), "+f"(d[7]), "+f"(d[8]), "+f"(d[9]), "+f"(d[10]), "+f"(d[11]), "+f"(d[12]), "+f"(d[13]), "+f"(d[14]), "+f"(d[15]), "+f"(d[16]), "+f"(d[17]), "+f"(d[18]), "+f"(d[19]), "+f"(d[20]), "+f"(d[21]), "+f"(d[22]), "+f"(d[23]), "+f"(d[24]), "+f"(d[25]), "+f"(d[26]), "+f"(d[27]), "+f"(d[28]), "+f"(d[29]), "+f"(d[30]), "+f"(d[31]), "+f"(d[32]), "+f"(d[33]), "+f"(d[34]), "+f"(d[35]), "+f"(d[36]), "+f"(d[37]), "+f"(d[38]), "+f"(d[39]), "+f"(d[40]), "+f"(d[41]), "+f"(d[42]), "+f"(d[43]), "+f"(d[44]), "+f"(d[45]), "+f"(d[46]), "+f"(d[47]), "+f"(d[48]), "+f"(d[49]), "+f"(d[50]), "+f"(d[51]), "+f"(d[52]), "+f"(d[53]), "+f"(d[54]), "+f"(d[55]), "+f"(d[56]), "+f"(d[57]), "+f"(d[58]), "+f"(d[59]), "+f"(d[60]), "+f"(d[61]), "+f"(d[62]), "+f"(d[63])
    : "r"(da), "r"(db), "r"(scale_d));
}
__device__ __forceinline__ void wgmma_n128_tb_p(float (&d)[64], uint32_t da, uint32_t db, int scale_d, int enable) {
  asm volatile(
    "{\n.reg .pred p;\n.reg .b64 da, db;\nsetp.ne.b32 p, %66, 0;\n.reg .pred q;\nsetp.ne.b32 q, %67, 0;\n"
    "mov.b64 da, {%64, 0x40000040};\nmov.b64 db, {%65, 0x40000040};\n"
    "@q wgmma.mma_async.sync.aligned.m64n128k16.f32.bf16.bf16 {%0, %1, %2, %3, %4, %5, %6, %7, %8, %9, %10, %11, %12, %13, %14, %15, %16, %17, %18, %19, %20, %21, %22, %23, %24, %25, %26, %27, %28, %29, %30, %31, %32, %33, %34, %35, %36, %37, %38, %39, %40, %41, %42, %43, %44, %45, %46, %47, %48, %49, %50, %51, %52, %53, %54, %55, %56, %57, %58, %59, %60, %61, %62, %63}, da, db, p, 1, 1, 0, 1;\n}\n"
    : "+f"(d[0]), "+f"(d[1]), "+f"(d[2]), "+f"(d[3]), "+f"(d[4]), "+f"(d[5]), "+f"(d[6]), "+f"(d[7]), "+f"(d[8]), "+f"(d[9]), "+f"(d[10]), "+f"(d[11]), "+f"(d[12]), "+f"(d[13]), "+f"(d[14]), "+f"(d[15]), "+f"(d[16]), "+f"(d[17]), "+f"(d[18]), "+f"(d[19]), "+f"(d[20]), "+f"(d[21]), "+f"(d[22]), "+f"(d[23]), "+f"(d[24]), "+f"(d[25]), "+f"(d[26]), "+f"(d[27]), "+f"(d[28]), "+f"(d[29]), "+f"(d[30]), "+f"(d[31]), "+f"(d[32]), "+f"(d[33]), "+f"(d[34]), "+f"(d[35]), "+f"(d[36]), "+f"(d[37]), "+f"(d[38]), "+f"(d[39]), "+f"(d[40]), "+f"(d[41]), "+f"(d[42]), "+f"(d[43]), "+f"(d[44]), "+f"(d[45]), "+f"(d[46]), "+f"(d[47]), "+f"(d[48]), "+f"(d[49]), "+f"(d[50]), "+f"(d[51]), "+f"(d[52]), "+f"(d[53]), "+f"(d[54]), "+f"(d[55]), "+f"(d[56]), "+f"(d[57]), "+f"(d[58]), "+f"(d[59]), "+f"(d[60]), "+f"(d[61]), "+f"(d[62]), "+f"(d[63])
    : "r"(da), "r"(db), "r"(scale_d), "r"(enable));
}
__device__ __forceinline__ void wgmma_n112(float (&d)[56], uint32_t da, uint32_t db, int scale_d) {
  asm volatile(
    "{\n.reg .pred p;\n.reg .b64 da, db;\nsetp.ne.b32 p, %58, 0;\n"
    "mov.b64 da, {%56, 0x40000040};\nmov.b64 db, {%57, 0x40000040};\n"
    "wgmma.mma_async.sync.aligned.m64n112k16.f32.bf16.bf16 {%0, %1, %2, %3, %4, %5, %6, %7, %8, %9, %10, %11, %12, %13, %14, %15, %16, %17, %18, %19, %20, %21, %22, %23, %24, %25, %26, %27, %28, %29, %30, %31, %32, %33, %34, %35, %36, %37, %38, %39, %40, %41, %42, %43, %44, %45, %46, %47, %48, %49, %50, %51, %52, %53, %54, %55}, da, db, p, 1, 1, 0, 0;\n}\n"
    : "+f"(d[0]), "+f"(d[1]), "+f"(d[2]), "+f"(d[3]), "+f"(d[4]), "+f"(d[5]), "+f"(d[6]), "+f"(d[7]), "+f"(d[8]), "+f"(d[9]), "+f"(d[10]), "+f"(d[11]), "+f"(d[12]), "+f"(d[13]), "+f"(d[14]), "+f"(d[15]), "+f"(d[16]), "+f"(d[17]), "+f"(d[18]), "+f"(d[19]), "+f"(d[20]), "+f"(d[21]), "+f"(d[22]), "+f"(d[23]), "+f"(d[24]), "+f"(d[25]), "+f"(d[26]), "+f"(d[27]), "+f"(d[28]), "+f"(d[29]), "+f"(d[30]), "+f"(d[31]), "+f"(d[32]), "+f"(d[33]), "+f"(d[34]), "+f"(d[35]), "+f"(d[36]), "+f"(d[37]), "+f"(d[38]), "+f"(d[39]), "+f"(d[40]), "+f"(d[41]), "+f"(d[42]), "+f"(d[43]), "+f"(d[44]), "+f"(d[45]), "+f"(d[46]), "+f"(d[47]), "+f"(d[48]), "+f"(d[49]), "+f"(d[50]), "+f"(d[51]), "+f"(d[52]), "+f"(d[53]), "+f"(d[54]), "+f"(d[55])
    : "r"(da), "r"(db), "r"(scale_d));
}
__device__ __forceinline__ void wgmma_n224_tb(float (&d)[112], uint32_t da, uint32_t db, int scale_d) {
  asm volatile(
    "{\n.reg .pred p;\n.reg .b64 da, db;\nsetp.ne.b32 p, %114, 0;\n"
    "mov.b64 da, {%112, 0x40000040};\nmov.b64 db, {%113, 0x40000040};\n"
    "wgmma.mma_async.sync.aligned.m64n224k16.f32.bf16.bf16 {%0, %1, %2, %3, %4, %5, %6, %7, %8, %9, %10, %11, %12, %13, %14, %15, %16, %17, %18, %19, %20, %21, %22, %23, %24, %25, %26, %27, %28, %29, %30, %31, %32, %33, %34, %35, %36, %37, %38, %39, %40, %41, %42, %43, %44, %45, %46, %47, %48, %49, %50, %51, %52, %53, %54, %55, %56, %57, %58, %59, %60, %61, %62, %63, %64, %65, %66, %67, %68, %69, %70, %71, %72, %73, %74, %75, %76, %77, %78, %79, %80, %81, %82, %83, %84, %85, %86, %87, %88, %89, %90, %91, %92, %93, %94, %95, %96, %97, %98, %99, %100, %101, %102, %103, %104, %105, %106, %107, %108, %109, %110, %111}, da, db, p, 1, 1, 0, 1;\n}\n"
    : "+f"(d[0]), "+f"(d[1]), "+f"(d[2]), "+f"(d[3]), "+f"(d[4]), "+f"(d[5]), "+f"(d[6]), "+f"(d[7]), "+f"(d[8]), "+f"(d[9]), "+f"(d[10]), "+f"(d[11]), "+f"(d[12]), "+f"(d[13]), "+f"(d[14]), "+f"(d[15]), "+f"(d[16]), "+f"(d[17]), "+f"(d[18]), "+f"(d[19]), "+f"(d[20]), "+f"(d[21]), "+f"(d[22]), "+f"(d[23]), "+f"(d[24]), "+f"(d[25]), "+f"(d[26]), "+f"(d[27]), "+f"(d[28]), "+f"(d[29]), "+f"(d[30]), "+f"(d[31]), "+f"(d[32]), "+f"(d[33]), "+f"(d[34]), "+f"(d[35]), "+f"(d[36]), "+f"(d[37]), "+f"(d[38]), "+f"(d[39]), "+f"(d[40]), "+f"(d[41]), "+f"(d[42]), "+f"(d[43]), "+f"(d[44]), "+f"(d[45]), "+f"(d[46]), "+f"(d[47]), "+f"(d[48]), "+f"(d[49]), "+f"(d[50]), "+f"(d[51]), "+f"(d[52]), "+f"(d[53]), "+f"(d[54]), "+f"(d[55]), "+f"(d[56]), "+f"(d[57]), "+f"(d[58]), "+f"(d[59]), "+f"(d[60]), "+f"(d[61]), "+f"(d[62]), "+f"(d[63]), "+f"(d[64]), "+f"(d[65]), "+f"(d[66]), "+f"(d[67]), "+f"(d[68]), "+f"(d[69]), "+f"(d[70]), "+f"(d[71]), "+f"(d[72]), "+f"(d[73]), "+f"(d[74]), "+f"(d[75]), "+f"(d[76]), "+f"(d[77]), "+f"(d[78]), "+f"(d[79]), "+f"(d[80]), "+f"(d[81]), "+f"(d[82]), "+f"(d[83]), "+f"(d[84]), "+f"(d[85]), "+f"(d[86]), "+f"(d[87]), "+f"(d[88]), "+f"(d[89]), "+f"(d[90]), "+f"(d[91]), "+f"(d[92]), "+f"(d[93]), "+f"(d[94]), "+f"(d[95]), "+f"(d[96]), "+f"(d[97]), "+f"(d[98]), "+f"(d[99]), "+f"(d[100]), "+f"(d[101]), "+f"(d[102]), "+f"(d[103]), "+f"(d[104]), "+f"(d[105]), "+f"(d[106]), "+f"(d[107]), "+f"(d[108]), "+f"(d[109]), "+f"(d[110]), "+f"(d[111])
    : "r"(da), "r"(db), "r"(scale_d));
}

constexpr int K1_NS = 5;
constexpr int K1_A_BYTES = 7 * 16384;
constexpr int K1_B_OFF = K1_A_BYTES;
constexpr int K1_STG_OFF = K1_B_OFF + K1_NS * 16384;
constexpr int K1_BAR_OFF = K1_STG_OFF + 8 * 4096;
constexpr int K1_SMEM = K1_BAR_OFF + 256 + 1024;

struct K1Ctx {
  uint32_t sb, bar_full, rel0, rel1;
  uint32_t dA, dBk, dBn;
  bool lane0;
  uint32_t bar_sfree;
  uint32_t sphase;
};
__device__ __forceinline__ void k1_release(const K1Ctx& c, int slot) {
  if (c.lane0) {
    asm volatile("mbarrier.arrive.shared::cluster.b64 _, [%0];" ::"r"(c.rel0 + 8 * slot) : "memory");
    asm volatile("mbarrier.arrive.shared::cluster.b64 _, [%0];" ::"r"(c.rel1 + 8 * slot) : "memory");
  }
}

__device__ __forceinline__ void k1_unit_ab(K1Ctx& c, int warp, int lane, int mt, int j) {
  const int wq = warp & 3;
  const int st_row = (lane & 7) + 8 * ((lane >> 3) & 1);
  const int st_chunk = lane >> 4;
  float acc[2][56];
  int slot = 0; uint32_t ph = 0;
#pragma unroll 1
  for (int kb = 0; kb < 7; kb++) {
    const int pslot = (slot == 0) ? K1_NS - 1 : slot - 1;
    mbar_wait(c.bar_full + 8 * slot, ph, 3);
    if (kb == 6) named_arrive(2, 256);
    if (kb == 0 && (threadIdx.x & 127) == 0) DBG(0, 4);
    if ((threadIdx.x & 127) == 0) DBGC(1, 46 + kb);
    wg_fence();
    const uint32_t da = c.dA + kb * 1024;
    const uint32_t db = c.dBk + slot * 1024;
#pragma unroll
    for (int k = 0; k < 4; k++) {
      wgmma_n112(acc[0], da + k * 2, db + k * 2, (kb | k) != 0);
      wgmma_n112(acc[1], da + 512 + k * 2, db + k * 2, (kb | k) != 0);
    }
    wg_commit();
    if (kb > 0) { wg_wait<1>(); k1_release(c, pslot); }
    if (++slot == K1_NS) { slot = 0; ph ^= 1; }
  }
  wg_wait<0>();
  k1_release(c, 6 % K1_NS);
  if ((threadIdx.x & 127) == 0) DBG(0, 5);
  const uint32_t sgn = (j < 4) ? 0u : 0x80008000u;
  const uint32_t sa = c.sb + K1_STG_OFF + (wq * 16 + st_row) * 224 + st_chunk * 16;
#pragma unroll
  for (int h = 0; h < 2; h++) {
    if (h == 1) { mbar_wait(c.bar_sfree, c.sphase, 6); c.sphase ^= 1; }
#pragma unroll
    for (int g = 0; g < 14; g += 2) {
      const float* a = &acc[h][4 * g];
      stmatrix_x4(sa + g * 16, pack_bf16(a[0], a[1]) ^ sgn, pack_bf16(a[2], a[3]) ^ sgn, pack_bf16(a[4], a[5]) ^ sgn, pack_bf16(a[6], a[7]) ^ sgn);
    }
    fence_async_smem();
    named_arrive(6, 160);
  }
}

__device__ __forceinline__ void k1_unit_gu(K1Ctx& c, int warp, int lane, int mt, int unit, int fb, int hsel, int full, int nunits) {
  const int wq = warp & 3;
  float acc[2][64];
  const uint32_t dA0 = c.dA + (full ? 0 : hsel * 512);
  int slot = (unit * 7) % K1_NS; uint32_t ph = ((unit * 7) / K1_NS) & 1;
  named_bar(2 + ((unit - 1) & 1), 256);
  if (full) {
#pragma unroll 1
    for (int kb = 0; kb < 7; kb++) {
      const int pslot = (slot == 0) ? K1_NS - 1 : slot - 1;
      mbar_wait(c.bar_full + 8 * slot, ph, 4);
      if (kb == 6 && unit + 1 < nunits) named_arrive(2 + (unit & 1), 256);
      if (kb == 0 && (threadIdx.x & 127) == 0) DBG(0, 4 + 3 * unit);
      wg_fence();
      const uint32_t da = dA0 + kb * 1024;
      const uint32_t db = c.dBn + slot * 1024;
#pragma unroll
      for (int k = 0; k < 4; k++) {
        wgmma_n128_tb(acc[0], da + k * 2, db + k * 128, (kb | k) != 0);
        wgmma_n128_tb(acc[1], da + 512 + k * 2, db + k * 128, (kb | k) != 0);
      }
      wg_commit();
      if (kb > 0) { wg_wait<1>(); k1_release(c, pslot); }
      if (++slot == K1_NS) { slot = 0; ph ^= 1; }
    }
  } else {
#pragma unroll 1
    for (int kb = 0; kb < 7; kb++) {
      const int pslot = (slot == 0) ? K1_NS - 1 : slot - 1;
      mbar_wait(c.bar_full + 8 * slot, ph, 5);
      if (kb == 0 && (threadIdx.x & 127) == 0) DBG(0, 4 + 3 * unit);
      wg_fence();
      const uint32_t da = dA0 + kb * 1024;
      const uint32_t db = c.dBn + slot * 1024;
#pragma unroll
      for (int k = 0; k < 4; k++) wgmma_n128_tb(acc[0], da + k * 2, db + k * 128, (kb | k) != 0);
      wg_commit();
      if (kb > 0) { wg_wait<1>(); k1_release(c, pslot); }
      if (++slot == K1_NS) { slot = 0; ph ^= 1; }
    }
  }
  wg_wait<0>();
  k1_release(c, (slot == 0) ? K1_NS - 1 : slot - 1);
  if (unit + 2 >= nunits && lane < 4) {
    asm volatile("mbarrier.arrive.shared::cluster.b64 _, [%0];" ::"r"(c.rel0 + 8 * (K1_NS + 4 + lane)) : "memory");
    asm volatile("mbarrier.arrive.shared::cluster.b64 _, [%0];" ::"r"(c.rel1 + 8 * (K1_NS + 4 + lane)) : "memory");
  }
  if ((threadIdx.x & 127) == 0) DBG(0, 5 + 3 * unit);
  const int st_row = (lane & 7) + 8 * ((lane >> 3) & 1);
  const int st_chunk = lane >> 4;
  const uint32_t sa = c.sb + K1_STG_OFF + (warp >> 2) * 16384 + (wq * 16 + st_row) * 128;
  if (unit >= 2) { mbar_wait(c.bar_sfree, c.sphase, 7); c.sphase ^= 1; }
#pragma unroll
  for (int h = 0; h < 2; h++) {
    if (h == 1 && !full) break;
#pragma unroll
    for (int g = 0; g < 8; g += 2) {
      uint32_t pk[4];
#pragma unroll
      for (int e = 0; e < 4; e++) {
        const int i = 4 * g + 2 * e;
        const uint32_t g2 = pack_bf16(acc[h][i], acc[h][i + 1]);
        const uint32_t u2 = pack_bf16(acc[h][32 + i], acc[h][32 + i + 1]);
        pk[e] = hmul2_bf16(pack_bf16(gelu_tanh(bf_lo(g2)), gelu_tanh(bf_hi(g2))), u2);
      }
      stmatrix_x4(sa + h * 8192 + (((g + st_chunk) ^ (st_row & 7)) * 16), pk[0], pk[1], pk[2], pk[3]);
    }
  }
  fence_async_smem();
  named_arrive(6 + (warp >> 2), 160);
}

constexpr int K2_NS = 4;
constexpr int K2_STAGE = 16384 + 32768;
constexpr int K2_PITCH = 464;

__device__ __forceinline__ void spin_flag(const unsigned int* flag, unsigned int target) {
  int it = 0;
  while (true) {
    unsigned int v;
    asm volatile("ld.acquire.gpu.global.u32 %0, [%1];" : "=r"(v) : "l"(flag) : "memory");
    if ((int)(v - target) >= 0) break;
    if (++it > SPIN_LIMIT) { TIMEOUT(20); break; }
  }
}

__device__ __forceinline__ void ln_rows(const __nv_bfloat16* __restrict__ xt, uint32_t sb, int lw, int lane) {
  const int c = lane & 7;
  const int r0 = lw * 4 + (lane >> 3);
  const uint4* src = reinterpret_cast<const uint4*>(xt + (size_t)r0 * 448) + c;
  uint4 nx[7];
#pragma unroll
  for (int b = 0; b < 7; b++)
    asm volatile("ld.global.nc.v4.u32 {%0,%1,%2,%3}, [%4];" : "=r"(nx[b].x), "=r"(nx[b].y), "=r"(nx[b].z), "=r"(nx[b].w) : "l"(src + b * 8) : "memory");
  const int npass = (lw < 10) ? 3 : 2;
  if (c < 7) {
    asm volatile("prefetch.global.L2 [%0];" ::"l"(src + 44 * 56 + c * 7) : "memory");
    if (npass == 3) asm volatile("prefetch.global.L2 [%0];" ::"l"(src + 88 * 56 + c * 7) : "memory");
  }
#pragma unroll 1
  for (int pass = 0; pass < npass; pass++) {
    uint4 v[7];
#pragma unroll
    for (int b = 0; b < 7; b++) v[b] = nx[b];
    if (pass + 1 < npass) {
      const uint4* s2 = src + (pass + 1) * 44 * 56;
#pragma unroll
      for (int b = 0; b < 7; b++)
        asm volatile("ld.global.nc.v4.u32 {%0,%1,%2,%3}, [%4];" : "=r"(nx[b].x), "=r"(nx[b].y), "=r"(nx[b].z), "=r"(nx[b].w) : "l"(s2 + b * 8) : "memory");
    }
        float s0 = 0.f, s1 = 0.f, s2v = 0.f, s3 = 0.f;
#pragma unroll
        for (int b = 0; b < 7; b++) {
          s0 += bf_lo(v[b].x) + bf_hi(v[b].x); s1 += bf_lo(v[b].y) + bf_hi(v[b].y);
          s2v += bf_lo(v[b].z) + bf_hi(v[b].z); s3 += bf_lo(v[b].w) + bf_hi(v[b].w);
        }
        float m = (s0 + s1) + (s2v + s3);
        m += __shfl_xor_sync(0xffffffffu, m, 1);
        m += __shfl_xor_sync(0xffffffffu, m, 2);
        m += __shfl_xor_sync(0xffffffffu, m, 4);
        m *= (1.0f / 448.0f);
        float q0 = 0.f, q1 = 0.f, q2 = 0.f, q3 = 0.f;
#pragma unroll
        for (int b = 0; b < 7; b++) {
          float d;
          d = bf_lo(v[b].x) - m; q0 = fmaf(d, d, q0); d = bf_hi(v[b].x) - m; q1 = fmaf(d, d, q1);
          d = bf_lo(v[b].y) - m; q2 = fmaf(d, d, q2); d = bf_hi(v[b].y) - m; q3 = fmaf(d, d, q3);
          d = bf_lo(v[b].z) - m; q0 = fmaf(d, d, q0); d = bf_hi(v[b].z) - m; q1 = fmaf(d, d, q1);
          d = bf_lo(v[b].w) - m; q2 = fmaf(d, d, q2); d = bf_hi(v[b].w) - m; q3 = fmaf(d, d, q3);
        }
        float q = (q0 + q1) + (q2 + q3);
        q += __shfl_xor_sync(0xffffffffu, q, 1);
        q += __shfl_xor_sync(0xffffffffu, q, 2);
        q += __shfl_xor_sync(0xffffffffu, q, 4);
        const float var_b = rbf(q * (1.0f / 448.0f));
        const float den = rbf(sqrtf(rbf(var_b + 1e-5f)));
        const float ri = 1.0f / den;
        const float rih = rbf(ri);
        const uint32_t rhi2 = pack_bf16(rih, rih), rlo2 = pack_bf16(ri - rih, ri - rih);
        const uint32_t m2 = pack_bf16(m, m);
        const int r = r0 + pass * 44;
        const uint32_t a0 = sb + r * 128 + ((c ^ (r & 7)) * 16);
#pragma unroll
        for (int b = 0; b < 7; b++) {
          uint32_t w4[4] = {v[b].x, v[b].y, v[b].z, v[b].w};
#pragma unroll
          for (int qq = 0; qq < 4; qq++) {
            const uint32_t dw = hsub2_bf16(w4[qq], m2);
            w4[qq] = hfma2_bf16(dw, rhi2, hmul2_bf16(dw, rlo2));
          }
          sts128(a0 + b * 16384, make_uint4(w4[0], w4[1], w4[2], w4[3]));
        }
  }
}

struct PfPtrs { const uint8_t* wg; const uint8_t* wu; const uint8_t* wd; };

__global__ void __cluster_dims__(2, 1, 1) __launch_bounds__(384, 1)
fused_kernel(const __grid_constant__ CUtensorMap tm_wr, const __grid_constant__ CUtensorMap tm_wi,
             const __grid_constant__ CUtensorMap tm_wg, const __grid_constant__ CUtensorMap tm_wu,
             const __grid_constant__ CUtensorMap tm_hs, const __grid_constant__ CUtensorMap tm_abs,
             const __grid_constant__ CUtensorMap tm_cr, const __grid_constant__ CUtensorMap tm_ci, const __grid_constant__ CUtensorMap tm_h,
             const __grid_constant__ CUtensorMap tm_ab, const __grid_constant__ CUtensorMap tm_wd,
             const __nv_bfloat16* __restrict__ x, __nv_bfloat16* __restrict__ out, const PfPtrs pf) {
  extern __shared__ uint8_t smem_raw[];
  const uint32_t sb = (s2u(smem_raw) + 1023) & ~1023u;
  const int tid = threadIdx.x, warp = tid >> 5, lane = tid & 31;
  uint32_t rank;
  asm volatile("mov.u32 %0, %%cluster_ctarank;" : "=r"(rank));
  const int cid = blockIdx.x >> 1;
  const int p = cid >> 3, j = cid & 7;
  const int mt = 2 * p + (int)rank;
  const uint32_t bar_full = sb + K1_BAR_OFF;
  const uint32_t bar_empty = bar_full + 8 * K1_NS;
  const uint32_t bar_full2 = bar_empty + 8 * K1_NS;
  const uint32_t bar_empty2 = bar_full2 + 8 * K2_NS;
  const int fb_base = 7 * (j >> 1);
  const int fb0 = fb_base + ((j & 1) ? 4 : 0);
  const int fbh = fb_base + 3;
  const int q = j & 3, n = j >> 2;
  const int tile = mt * 2 + n;
  const int nkb = (q < 2) ? 22 : (q == 3 ? 28 : 20);
  const int nunits = (q == 3) ? 4 : 5;
  const int u4full = (q == 2);

  const unsigned int epoch = *reinterpret_cast<volatile unsigned int*>(&g_epoch);
  if (tid == 0) DBG(0, 0);
  if (tid == 256) {
    for (int i = 0; i < K1_NS; i++) { mbar_init(bar_full + 8 * i, 1); mbar_init(bar_empty + 8 * i, 8); }
    for (int i = 0; i < K2_NS; i++) { mbar_init(bar_full2 + 8 * i, 1); mbar_init(bar_empty2 + 8 * i, 16); }
    mbar_init(bar_empty2 + 8 * K2_NS, 1);
    mbar_init(bar_empty2 + 8 * K2_NS + 8, 1);
    mbar_init(bar_empty2 + 8 * K2_NS + 16, 1);
    asm volatile("fence.mbarrier_init.release.cluster;" ::: "memory");
    prefetch_tmap((j < 4) ? &tm_wr : &tm_wi);
    prefetch_tmap(rank ? &tm_wu : &tm_wg);
    prefetch_tmap(&tm_abs);
    prefetch_tmap(&tm_hs);
  }
  __syncwarp();
  cluster_arrive_relaxed();

  if (warp != 8) {
    ln_rows(x + (size_t)mt * 128 * 448, sb, warp < 8 ? warp : warp - 1, lane);
    asm volatile("fence.proxy.async.shared::cta;" ::: "memory");
  }
  if (warp >= 8) {
    if (warp > 8) named_arrive(8, 352);
    reg_dec<40>();
    cluster_wait();
    if (tid == 256) {
      {
        const CUtensorMap* tw = (j < 4) ? &tm_wr : &tm_wi;
        const CUtensorMap* tgu = rank ? &tm_wu : &tm_wg;
        int slot = 0; uint32_t ph = 0;
        int kb = 0, unit = 0;
#pragma unroll 1
        for (int s = 0; s < 7 * nunits; s++) {
          if (s >= K1_NS) mbar_wait(bar_empty + 8 * slot, ph ^ 1, 2);
          const uint32_t dst = sb + K1_B_OFF + slot * 16384;
          if (unit == 0) {
            mbar_expect(bar_full + 8 * slot, 14336);
            tma2d_mc(dst + rank * 7168, tw, kb * 64, (j & 3) * 112 + rank * 56, bar_full + 8 * slot, 3);
          } else {
            const int fb = (unit == 4) ? fbh : (fb0 + unit - 1);
            mbar_expect(bar_full + 8 * slot, 16384);
            tma2d_mc(dst + rank * 8192, tgu, fb * 64, kb * 64, bar_full + 8 * slot, 3);
          }
          if (s == 21) {
            l2_prefetch(pf.wd + blockIdx.x * 12544, 12544);
            if (q < 3) {
              const int g0 = q * 22;
#pragma unroll 1
              for (int i = 0; i < 6; i++) tma2d_prefetch((g0 + i < 32) ? &tm_cr : &tm_ci, ((g0 + i) & 31) * 64, mt * 128);
            }
          }
          if (++kb == 7) { kb = 0; unit++; }
          if (++slot == K1_NS) { slot = 0; ph ^= 1; }
        }
      }
      {
        const int g0 = (q == 0) ? 0 : (q == 1 ? 22 : (q == 2 ? 44 : 64));
        const CUtensorMap* tb = (q < 3) ? &tm_ab : &tm_wd;
        prefetch_tmap(tb); prefetch_tmap((q < 3) ? ((g0 < 32) ? &tm_cr : &tm_ci) : &tm_h);
        const int kb0 = (q < 3) ? g0 : 0;
        if (q < 3) { spin_flag(&g_ab_cnt, 128u * (epoch + 1)); asm volatile("fence.proxy.async;" ::: "memory"); }
        DBG(1, 31);
        int slot = 0; uint32_t ph = 0;
#pragma unroll 1
        for (int s = 0; s < nkb; s++) {
          int kblk = kb0 + s;
          const CUtensorMap* ta = (kblk < 32) ? &tm_cr : &tm_ci;
          if (q == 3) {
            if ((s & 7) == 0) { spin_flag(&g_h_cnt[mt * 4 + (s >> 3)], ((s < 24) ? 8u : 6u) * (epoch + 1)); asm volatile("fence.proxy.async;" ::: "memory"); }
            const int i = s & 7;
            kblk = (s < 24) ? (7 * (i >> 1) + ((i & 1) ? 4 : 0) + (s >> 3)) : (7 * i + 3);
            ta = &tm_h;
          }
          mbar_wait(bar_empty2 + 8 * slot, ph, 10);
          const uint32_t dst = sb + slot * K2_STAGE;
          const uint32_t fb = bar_full2 + 8 * slot;
          mbar_expect(fb, K2_STAGE);
          tma2d(dst, ta, (kblk & 31) * 64, mt * 128, fb);
          tma3d_mc(dst + 16384 + (2 * rank) * 8192, tb, (2 * rank) * 64, n, kblk * 64, fb, 3);
          tma3d_mc(dst + 16384 + (2 * rank + 1) * 8192, tb, (2 * rank + 1) * 64, n, kblk * 64, fb, 3);
          if (++slot == K2_NS) { slot = 0; ph ^= 1; }
        }
      }
    } else if (warp == 9 || warp == 10) {
      const int hw = warp - 9;
      const uint32_t stg = sb + K1_STG_OFF + hw * 16384;
      const uint32_t bar_sfree = bar_empty2 + 8 * K2_NS + 8 + 8 * hw;
      if (lane == 0) {
        const int b = blockIdx.x;
        l2_prefetch((hw ? pf.wu : pf.wg) + b * 12544, 12544);
      }
#pragma unroll 1
      for (int job = 0; job < (hw ? 2 : (nunits == 5 ? 4 : 3)); job++) {
        named_bar(6 + hw, 160);
        if (lane == 0) {
          const int unit = hw ? (1 + 2 * job) : (job < 2 ? 0 : 2 * job - 2);
          if (unit == 0) {
            tma2d_store(&tm_abs, stg, (j & 3) * 112, (j < 4 ? 0 : 2048) + mt * 128 + job * 64);
          } else {
            const int fb = (unit == 4) ? fbh : fb0 + unit - 1;
            const bool fullu = (unit < 4) || u4full;
            tma2d_store(&tm_hs, stg, fb * 64, mt * 128 + (fullu ? 0 : (j & 1) * 64));
            if (fullu) tma2d_store(&tm_hs, stg + 8192, fb * 64, mt * 128 + 64);
          }
          bulk_commit();
          bulk_wait_read0();
          asm volatile("mbarrier.arrive.shared::cta.b64 _, [%0];" ::"r"(bar_sfree) : "memory");
          if (unit != 0 || job == 1) {
            bulk_wait0();
            asm volatile("fence.proxy.async;" ::: "memory");
            __threadfence();
            if (unit == 0) {
              const unsigned int old = atomicAdd(&g_ab_cnt, 1u);
              if ((old & 127u) == 127u) *reinterpret_cast<volatile unsigned int*>(&g_epoch) = (old >> 7) + 1;
            } else {
              atomicAdd(&g_h_cnt[mt * 4 + unit - 1], 1u);
            }
          }
        }
        __syncwarp();
      }
    }
  } else {
    const int wg = warp >> 2;
    named_bar(8, 352);
    reg_inc<232>();
    cluster_wait();
    if (tid == 0) DBG(0, 3);

    uint32_t rel0, rel1, sphase_end;
    asm volatile("mapa.shared::cluster.u32 %0, %1, %2;" : "=r"(rel0) : "r"(bar_empty2), "r"(0));
    asm volatile("mapa.shared::cluster.u32 %0, %1, %2;" : "=r"(rel1) : "r"(bar_empty2), "r"(1));
    {
      K1Ctx c;
      c.sb = sb; c.bar_full = bar_full; c.lane0 = (lane == 0);
      c.rel0 = rel0 - 8 * (K1_NS + K2_NS); c.rel1 = rel1 - 8 * (K1_NS + K2_NS);
      c.bar_sfree = bar_empty2 + 8 * K2_NS + 8 + 8 * wg; c.sphase = 0;
      c.dA = make_desc(sb, 16, 1024);
      c.dBk = make_desc(sb + K1_B_OFF, 16, 1024);
      c.dBn = make_desc(sb + K1_B_OFF, 8192, 1024);
      if (wg == 0) {
        k1_unit_ab(c, warp, lane, mt, j);
        if (tid == 0) DBG(0, 6);
      }
#pragma unroll 1
      for (int unit = 2 - wg; unit < nunits; unit += 2) {
        k1_unit_gu(c, warp, lane, mt, unit, (unit == 4) ? fbh : fb0 + unit - 1, j & 1, (unit < 4) || u4full, nunits);
        if ((tid & 127) == 0) DBG(0, 6 + 3 * unit);
      }
      sphase_end = c.sphase;
    }

    float acc[112];
    const uint32_t dA0 = make_desc(sb + wg * 8192, 16, 1024);
    const uint32_t dB0 = make_desc(sb + 16384, 8192, 1024);
    int slot = 0; uint32_t ph = 0;
#pragma unroll 1
    for (int s = 0; s < nkb; s++) {
      mbar_wait(bar_full2 + 8 * slot, ph, 11);
      if (tid == 0) DBG(1, 1 + s);
      wg_fence();
      const uint32_t da = dA0 + slot * (K2_STAGE / 16);
      const uint32_t db = dB0 + slot * (K2_STAGE / 16);
#pragma unroll
      for (int k = 0; k < 4; k++) wgmma_n224_tb(acc, da + k * 2, db + k * 128, (s | k) != 0);
      wg_commit();
      if (s > 0) {
        wg_wait<1>();
        const int ps = (slot == 0) ? K2_NS - 1 : slot - 1;
        if (lane == 0) {
          asm volatile("mbarrier.arrive.shared::cluster.b64 _, [%0];" ::"r"(rel0 + 8 * ps) : "memory");
          asm volatile("mbarrier.arrive.shared::cluster.b64 _, [%0];" ::"r"(rel1 + 8 * ps) : "memory");
        }
      }
      if (++slot == K2_NS) { slot = 0; ph ^= 1; }
    }
    wg_wait<0>();
    if (tid == 0) DBG(1, 29);
    uint32_t ow[56];
#pragma unroll
    for (int i = 0; i < 56; i++) ow[i] = pack_bf16(acc[2 * i], acc[2 * i + 1]);
    const int P0 = (q < 2) ? 4 * q : 3 * q + 2, NP = (q < 2) ? 4 : 3;
    uint4* part = g_part + (size_t)tile * (4 * 14 * 256) + tid;
    mbar_wait(bar_empty2 + 8 * K2_NS + 8 + 8 * wg, sphase_end, 14);
    const uint32_t stg = sb + K1_STG_OFF + warp * 4096;
    const uint32_t stash = stg + 2048 + lane * 16 - P0 * 512;
#pragma unroll
    for (int g = 0; g < 14; g++) {
      const uint4 v = make_uint4(ow[4 * g], ow[4 * g + 1], ow[4 * g + 2], ow[4 * g + 3]);
      if ((unsigned)(g - P0) >= (unsigned)NP) part[(q * 14 + g) * 256] = v;
      else sts128(stash + g * 512, v);
    }
    __syncwarp();
    unsigned int* flag = &g_flags[tile * 8 + warp];
    if (lane == 0) { __threadfence(); atomicAdd(flag, 1u); }
    const int ch = lane & 7;
    const bool act = ch < 2 * NP;
    const size_t gbase = (size_t)(mt * 128 + warp * 16 + (lane >> 3)) * 448 + n * 224 + P0 * 16 + (act ? ch : 0) * 8;
    uint4 xv[4];
#pragma unroll
    for (int t = 0; t < 4; t++) xv[t] = ldg128_cg(x + gbase + t * 4 * 448);
    if (tid == 0) DBG(1, 62);
    if (lane == 0) spin_flag(flag, 4u * (epoch + 1));
    __syncwarp();
    if (tid == 0) DBG(1, 30);
    uint4 oth[3][4];
#pragma unroll
    for (int i = 0; i < 3; i++) {
      const int r = (i < q) ? i : i + 1;
#pragma unroll
      for (int e = 0; e < 4; e++) oth[i][e] = ldg128_cg(part + (r * 14 + P0 + (e < NP ? e : 0)) * 256);
    }
    const bool isf = (q == 3);
    const int st_row = (lane & 7) + 8 * ((lane >> 3) & 1);
    const uint32_t sa = stg + st_row * 128;
#pragma unroll
    for (int e = 0; e < 4; e++) {
      const uint32_t av[4] = {oth[0][e].x, oth[0][e].y, oth[0][e].z, oth[0][e].w};
      const uint32_t bv[4] = {oth[1][e].x, oth[1][e].y, oth[1][e].z, oth[1][e].w};
      const uint32_t cv[4] = {oth[2][e].x, oth[2][e].y, oth[2][e].z, oth[2][e].w};
      const uint4 mine = lds128(stg + 2048 + lane * 16 + (e < NP ? e : 0) * 512);
      const uint32_t mv[4] = {mine.x, mine.y, mine.z, mine.w};
      uint32_t tv[4];
#pragma unroll
      for (int k = 0; k < 4; k++) {
        const uint32_t y3 = isf ? cv[k] : mv[k], ff = isf ? mv[k] : cv[k];
        const uint32_t gg = pack_bf16(silu_f(bf_lo(ff)), silu_f(bf_hi(ff)));
        tv[k] = hmul2_bf16(pack_bf16(bf_lo(av[k]) + bf_lo(bv[k]) + bf_lo(y3), bf_hi(av[k]) + bf_hi(bv[k]) + bf_hi(y3)), gg);
      }
      stmatrix_x4(sa + (((2 * e + (lane >> 4)) ^ (st_row & 7)) * 16), tv[0], tv[1], tv[2], tv[3]);
    }
    __syncwarp();
#pragma unroll
    for (int t = 0; t < 4; t++) {
      const int row = t * 4 + (lane >> 3);
      const uint4 tv = lds128(stg + row * 128 + ((ch ^ (row & 7)) * 16));
      uint4 o;
      o.x = hadd2_bf16(xv[t].x, tv.x); o.y = hadd2_bf16(xv[t].y, tv.y); o.z = hadd2_bf16(xv[t].z, tv.z); o.w = hadd2_bf16(xv[t].w, tv.w);
      if (act) stg128(out + gbase + t * 4 * 448, o);
    }
    if (tid == 0) DBG(1, 63);
  }
  __syncwarp();
  cluster_arrive_relaxed();
  cluster_wait();
}

typedef CUresult (*EncFn)(CUtensorMap*, CUtensorMapDataType, cuuint32_t, void*, const cuuint64_t*, const cuuint64_t*, const cuuint32_t*,
                          const cuuint32_t*, CUtensorMapInterleave, CUtensorMapSwizzle, CUtensorMapL2promotion, CUtensorMapFloatOOBfill);

void make2d(EncFn enc, CUtensorMap* tm, const void* ptr, uint64_t cols, uint64_t rows, uint32_t bc, uint32_t br, bool swz = true) {
  cuuint64_t gd[2] = {cols, rows};
  cuuint64_t gs[1] = {cols * 2};
  cuuint32_t bd[2] = {bc, br};
  cuuint32_t es[2] = {1, 1};
  enc(tm, CU_TENSOR_MAP_DATA_TYPE_BFLOAT16, 2, const_cast<void*>(ptr), gd, gs, bd, es, CU_TENSOR_MAP_INTERLEAVE_NONE,
      swz ? CU_TENSOR_MAP_SWIZZLE_128B : CU_TENSOR_MAP_SWIZZLE_NONE, CU_TENSOR_MAP_L2_PROMOTION_L2_128B, CU_TENSOR_MAP_FLOAT_OOB_FILL_NONE);
}
void make3d_half(EncFn enc, CUtensorMap* tm, const void* ptr, uint64_t rows) {
  cuuint64_t gd[3] = {224, 2, rows};
  cuuint64_t gs[2] = {448, 896};
  cuuint32_t bd[3] = {64, 1, 64};
  cuuint32_t es[3] = {1, 1, 1};
  enc(tm, CU_TENSOR_MAP_DATA_TYPE_BFLOAT16, 3, const_cast<void*>(ptr), gd, gs, bd, es, CU_TENSOR_MAP_INTERLEAVE_NONE,
      CU_TENSOR_MAP_SWIZZLE_128B, CU_TENSOR_MAP_L2_PROMOTION_L2_128B, CU_TENSOR_MAP_FLOAT_OOB_FILL_NONE);
}

struct Maps { CUtensorMap wr, wi, wg, wu, cr, ci, h, ab, wd, hs, abs; };

}

extern "C" void kernel_launch(void* const* d_in, const int* in_sizes, int n_in, void* d_out, int out_size) {
  (void)in_sizes; (void)n_in; (void)out_size;
  static Maps maps;
  static const void* cached[9] = {nullptr};
  static bool attr_done = false;
  bool same = true;
  for (int i = 0; i < 9; i++) same = same && (cached[i] == d_in[i]);
  if (!same) {
    void* fn = nullptr;
    cudaDriverEntryPointQueryResult qr;
    cudaGetDriverEntryPoint("cuTensorMapEncodeTiled", &fn, cudaEnableDefault, &qr);
    EncFn enc = (EncFn)fn;
    void *p_ab = nullptr, *p_h = nullptr;
    cudaGetSymbolAddress(&p_ab, g_ab);
    cudaGetSymbolAddress(&p_h, g_h);
    make2d(enc, &maps.cr, d_in[1], 2048, 2048, 64, 128);
    make2d(enc, &maps.ci, d_in[2], 2048, 2048, 64, 128);
    make2d(enc, &maps.wr, d_in[3], 448, 448, 64, 56);
    make2d(enc, &maps.wi, d_in[4], 448, 448, 64, 56);
    make2d(enc, &maps.wg, d_in[6], 1792, 448, 64, 64);
    make2d(enc, &maps.wu, d_in[7], 1792, 448, 64, 64);
    make3d_half(enc, &maps.wd, d_in[8], 1792);
    make2d(enc, &maps.h, p_h, 1792, 2048, 64, 128);
    make3d_half(enc, &maps.ab, p_ab, 4096);
    make2d(enc, &maps.hs, p_h, 1792, 2048, 64, 64);
    make2d(enc, &maps.abs, p_ab, 448, 4096, 112, 64, false);
    for (int i = 0; i < 9; i++) cached[i] = d_in[i];
  }
  if (!attr_done) {
    cudaFuncSetAttribute(fused_kernel, cudaFuncAttributeMaxDynamicSharedMemorySize, K1_SMEM);
    attr_done = true;
  }
  PfPtrs pf;
  pf.wg = (const uint8_t*)d_in[6]; pf.wu = (const uint8_t*)d_in[7]; pf.wd = (const uint8_t*)d_in[8];
  fused_kernel<<<128, 384, K1_SMEM>>>(maps.wr, maps.wi, maps.wg, maps.wu, maps.hs, maps.abs, maps.cr, maps.ci, maps.h, maps.ab, maps.wd,
                                      (const __nv_bfloat16*)d_in[0], (__nv_bfloat16*)d_out, pf);
}
```

```cpp
#include <cuda_runtime.h>
#include <cuda_bf16.h>
#include <cuda.h>
#include <stdint.h>

namespace {

__device__ __align__(1024) __nv_bfloat16 g_ab[4096 * 448];
__device__ __align__(1024) __nv_bfloat16 g_h[2048 * 1792];
__device__ uint4 g_part[32 * 4 * 14 * 256];
__device__ __align__(1024) __nv_bfloat16 g_s[2048 * 448];
__device__ unsigned int g_epoch;
__device__ unsigned int g_ab_cnt;
__device__ unsigned int g_h_cnt[16 * 8];
__constant__ unsigned char c_forder[28] = {0, 4, 7, 12, 14, 18, 21, 26, 1, 5, 8, 13, 15, 19, 22, 27, 2, 6, 9, 16, 20, 23, 3, 10, 17, 24, 11, 25};
__device__ unsigned int g_flags[32 * 8];

#define DBG(k, i) do {} while (0)
#define DBGC(k, i) do {} while (0)

#define TIMEOUT(code) __trap()
#define SPIN_LIMIT (1 << 22)
__device__ __forceinline__ uint32_t s2u(const void* p) { return (uint32_t)__cvta_generic_to_shared(p); }
__device__ __forceinline__ void mbar_init(uint32_t b, int c) { asm volatile("mbarrier.init.shared::cta.b64 [%0], %1;" ::"r"(b), "r"(c)); }
__device__ __forceinline__ void mbar_expect(uint32_t b, uint32_t bytes) {
  asm volatile("mbarrier.arrive.expect_tx.shared::cta.b64 _, [%0], %1;" ::"r"(b), "r"(bytes) : "memory");
}
__device__ __forceinline__ void mbar_wait(uint32_t b, uint32_t ph, int code = 1) {
  uint32_t done = 0;
  int it = 0;
  while (true) {
    asm volatile("{.reg .pred p; mbarrier.try_wait.parity.shared::cta.b64 p, [%1], %2; selp.u32 %0,1,0,p;}" : "=r"(done) : "r"(b), "r"(ph) : "memory");
    if (done) break;
    if (++it > SPIN_LIMIT) { TIMEOUT(code); break; }
  }
}
__device__ __forceinline__ void mbar_arrive_cluster(uint32_t b, uint32_t cta) {
  uint32_t r;
  asm volatile("mapa.shared::cluster.u32 %0, %1, %2;" : "=r"(r) : "r"(b), "r"(cta));
  asm volatile("mbarrier.arrive.shared::cluster.b64 _, [%0];" ::"r"(r) : "memory");
}
__device__ __forceinline__ void tma2d(uint32_t dst, const CUtensorMap* m, int c0, int c1, uint32_t bar) {
  asm volatile("cp.async.bulk.tensor.2d.shared::cluster.global.mbarrier::complete_tx::bytes [%0], [%1, {%3,%4}], [%2];" ::"r"(dst), "l"(m), "r"(bar), "r"(c0), "r"(c1) : "memory");
}
__device__ __forceinline__ void tma2d_mc(uint32_t dst, const CUtensorMap* m, int c0, int c1, uint32_t bar, uint16_t mask) {
  asm volatile("cp.async.bulk.tensor.2d.shared::cluster.global.mbarrier::complete_tx::bytes.multicast::cluster [%0], [%1, {%3,%4}], [%2], %5;" ::"r"(dst), "l"(m), "r"(bar), "r"(c0), "r"(c1), "h"(mask) : "memory");
}
__device__ __forceinline__ void tma3d_mc(uint32_t dst, const CUtensorMap* m, int c0, int c1, int c2, uint32_t bar, uint16_t mask) {
  asm volatile("cp.async.bulk.tensor.3d.shared::cluster.global.mbarrier::complete_tx::bytes.multicast::cluster [%0], [%1, {%3,%4,%5}], [%2], %6;" ::"r"(dst), "l"(m), "r"(bar), "r"(c0), "r"(c1), "r"(c2), "h"(mask) : "memory");
}
__device__ __forceinline__ void tma2d_store(const CUtensorMap* m, uint32_t src, int c0, int c1) {
  asm volatile("cp.async.bulk.tensor.2d.global.shared::cta.bulk_group [%0, {%2,%3}], [%1];" ::"l"(m), "r"(src), "r"(c0), "r"(c1) : "memory");
}
__device__ __forceinline__ void bulk_load(uint32_t dst, const void* src, uint32_t bytes, uint32_t bar) {
  asm volatile("cp.async.bulk.shared::cluster.global.mbarrier::complete_tx::bytes [%0], [%1], %2, [%3];" ::"r"(dst), "l"(src), "r"(bytes), "r"(bar) : "memory");
}
__device__ __forceinline__ void tma2d_prefetch(const CUtensorMap* m, int c0, int c1) {
  asm volatile("cp.async.bulk.prefetch.tensor.2d.L2.global [%0, {%1,%2}];" ::"l"(m), "r"(c0), "r"(c1) : "memory");
}
__device__ __forceinline__ void bulk_commit() { asm volatile("cp.async.bulk.commit_group;" ::: "memory"); }
__device__ __forceinline__ void bulk_wait_read0() { asm volatile("cp.async.bulk.wait_group.read 0;" ::: "memory"); }
__device__ __forceinline__ void bulk_wait0() { asm volatile("cp.async.bulk.wait_group 0;" ::: "memory"); }
__device__ __forceinline__ void fence_async_smem() { asm volatile("fence.proxy.async.shared::cta;" ::: "memory"); }
__device__ __forceinline__ void prefetch_tmap(const CUtensorMap* m) { asm volatile("prefetch.tensormap [%0];" ::"l"(m) : "memory"); }
__device__ __forceinline__ void l2_prefetch(const void* p, uint32_t bytes) {
  asm volatile("cp.async.bulk.prefetch.L2.global [%0], %1;" ::"l"(p), "r"(bytes) : "memory");
}
__device__ __forceinline__ void cluster_arrive_relaxed() { asm volatile("barrier.cluster.arrive.relaxed.aligned;" ::: "memory"); }
__device__ __forceinline__ void cluster_wait() { asm volatile("barrier.cluster.wait.aligned;" ::: "memory"); }
__device__ __forceinline__ void wg_fence() { __syncwarp(); asm volatile("wgmma.fence.sync.aligned;" ::: "memory"); }
__device__ __forceinline__ void wg_commit() { asm volatile("wgmma.commit_group.sync.aligned;" ::: "memory"); }
template <int N> __device__ __forceinline__ void wg_wait() { __syncwarp(); asm volatile("wgmma.wait_group.sync.aligned %0;" ::"n"(N) : "memory"); }
__device__ __forceinline__ void named_bar(int id, int n) { asm volatile("bar.sync %0, %1;" ::"r"(id), "r"(n) : "memory"); }
__device__ __forceinline__ void named_arrive(int id, int n) { asm volatile("bar.arrive %0, %1;" ::"r"(id), "r"(n) : "memory"); }
template <int N> __device__ __forceinline__ void reg_inc() { asm volatile("setmaxnreg.inc.sync.aligned.u32 %0;" ::"n"(N)); }
template <int N> __device__ __forceinline__ void reg_dec() { asm volatile("setmaxnreg.dec.sync.aligned.u32 %0;" ::"n"(N)); }
__device__ __forceinline__ void pdl_wait() { asm volatile("griddepcontrol.wait;" ::: "memory"); }
__device__ __forceinline__ void pdl_launch() { asm volatile("griddepcontrol.launch_dependents;" ::: "memory"); }

__device__ __forceinline__ uint32_t make_desc(uint32_t addr, uint32_t lbo, uint32_t  ) {
  return ((addr & 0x3FFFF) >> 4) | ((lbo >> 4) << 16);
}
__device__ __forceinline__ void stmatrix_x4(uint32_t addr, uint32_t r0, uint32_t r1, uint32_t r2, uint32_t r3) {
  asm volatile("stmatrix.sync.aligned.m8n8.x4.shared.b16 [%0], {%1,%2,%3,%4};" ::"r"(addr), "r"(r0), "r"(r1), "r"(r2), "r"(r3) : "memory");
}
__device__ __forceinline__ uint4 lds128(uint32_t a) {
  uint4 v;
  asm volatile("ld.shared.v4.u32 {%0,%1,%2,%3}, [%4];" : "=r"(v.x), "=r"(v.y), "=r"(v.z), "=r"(v.w) : "r"(a) : "memory");
  return v;
}
__device__ __forceinline__ void sts128(uint32_t a, uint4 v) {
  asm volatile("st.shared.v4.u32 [%0], {%1,%2,%3,%4};" ::"r"(a), "r"(v.x), "r"(v.y), "r"(v.z), "r"(v.w) : "memory");
}
__device__ __forceinline__ void stg128(void* p, uint4 v) {
  asm volatile("st.global.v4.u32 [%0], {%1,%2,%3,%4};" ::"l"(p), "r"(v.x), "r"(v.y), "r"(v.z), "r"(v.w) : "memory");
}
__device__ __forceinline__ void cp_async16(uint32_t dst, const void* src) {
  asm volatile("cp.async.cg.shared.global [%0], [%1], 16;" ::"r"(dst), "l"(src) : "memory");
}
__device__ __forceinline__ void cp_async8(uint32_t dst, const void* src) {
  asm volatile("cp.async.ca.shared.global [%0], [%1], 8;" ::"r"(dst), "l"(src) : "memory");
}
__device__ __forceinline__ uint2 lds64(uint32_t a) {
  uint2 v;
  asm volatile("ld.shared.v2.u32 {%0,%1}, [%2];" : "=r"(v.x), "=r"(v.y) : "r"(a) : "memory");
  return v;
}
__device__ __forceinline__ void cp_async_wait_all() { asm volatile("cp.async.wait_all;" ::: "memory"); }
__device__ __forceinline__ uint32_t pack_bf16(float lo, float hi) {
  uint32_t r;
  asm("cvt.rn.bf16x2.f32 %0, %1, %2;" : "=r"(r) : "f"(hi), "f"(lo));
  return r;
}
__device__ __forceinline__ uint32_t hmul2_bf16(uint32_t a, uint32_t b) {
  uint32_t r;
  asm("mul.rn.bf16x2 %0, %1, %2;" : "=r"(r) : "r"(a), "r"(b));
  return r;
}
__device__ __forceinline__ uint32_t hsub2_bf16(uint32_t a, uint32_t b) {
  uint32_t r;
  asm("sub.rn.bf16x2 %0, %1, %2;" : "=r"(r) : "r"(a), "r"(b));
  return r;
}
__device__ __forceinline__ uint32_t hadd2_bf16(uint32_t a, uint32_t b) {
  uint32_t r;
  asm("add.rn.bf16x2 %0, %1, %2;" : "=r"(r) : "r"(a), "r"(b));
  return r;
}
__device__ __forceinline__ uint32_t hfma2_bf16(uint32_t a, uint32_t b, uint32_t c) {
  uint32_t r;
  asm("fma.rn.bf16x2 %0, %1, %2, %3;" : "=r"(r) : "r"(a), "r"(b), "r"(c));
  return r;
}
__device__ __forceinline__ bool mbar_test(uint32_t b, uint32_t ph) {
  uint32_t done;
  asm volatile("{.reg .pred p; mbarrier.test_wait.parity.shared::cta.b64 p, [%1], %2; selp.u32 %0,1,0,p;}" : "=r"(done) : "r"(b), "r"(ph) : "memory");
  return __all_sync(0xffffffffu, done != 0);
}
__device__ __forceinline__ uint4 ldg128_cg(const void* p) {
  uint4 v;
  asm volatile("ld.global.cg.v4.u32 {%0,%1,%2,%3}, [%4];" : "=r"(v.x), "=r"(v.y), "=r"(v.z), "=r"(v.w) : "l"(p) : "memory");
  return v;
}
__device__ __forceinline__ float bf_lo(uint32_t w) { return __uint_as_float(w << 16); }
__device__ __forceinline__ float bf_hi(uint32_t w) { return __uint_as_float(w & 0xffff0000u); }
__device__ __forceinline__ float rbf(float x) { return __bfloat162float(__float2bfloat16_rn(x)); }
__device__ __forceinline__ float ex2f(float x) { float r; asm("ex2.approx.ftz.f32 %0, %1;" : "=f"(r) : "f"(x)); return r; }
__device__ __forceinline__ float rcpf(float x) { float r; asm("rcp.approx.ftz.f32 %0, %1;" : "=f"(r) : "f"(x)); return r; }
__device__ __forceinline__ float tanhf_hw(float x) { float r; asm("tanh.approx.f32 %0, %1;" : "=f"(r) : "f"(x)); return r; }
__device__ __forceinline__ float gelu_tanh(float x) {
  const float c1 = 0.7978845608028654f;
  const float c2 = c1 * 0.044715f;
  const float t = tanhf_hw(x * fmaf(c2, x * x, c1));
  const float hx = 0.5f * x;
  return fmaf(hx, t, hx);
}
__device__ __forceinline__ float silu_f(float x) {
  const float hx = 0.5f * x;
  return fmaf(hx, tanhf_hw(hx), hx);
}

__device__ __forceinline__ void wgmma_n128_tb(float (&d)[64], uint32_t da, uint32_t db, int scale_d) {
  asm volatile(
    "{\n.reg .pred p;\n.reg .b64 da, db;\nsetp.ne.b32 p, %66, 0;\n"
    "mov.b64 da, {%64, 0x40000040};\nmov.b64 db, {%65, 0x40000040};\n"
    "wgmma.mma_async.sync.aligned.m64n128k16.f32.bf16.bf16 {%0, %1, %2, %3, %4, %5, %6, %7, %8, %9, %10, %11, %12, %13, %14, %15, %16, %17, %18, %19, %20, %21, %22, %23, %24, %25, %26, %27, %28, %29, %30, %31, %32, %33, %34, %35, %36, %37, %38, %39, %40, %41, %42, %43, %44, %45, %46, %47, %48, %49, %50, %51, %52, %53, %54, %55, %56, %57, %58, %59, %60, %61, %62, %63}, da, db, p, 1, 1, 0, 1;\n}\n"
    : "+f"(d[0]), "+f"(d[1]), "+f"(d[2]), "+f"(d[3]), "+f"(d[4]), "+f"(d[5]), "+f"(d[6]), "+f"(d[7]), "+f"(d[8]), "+f"(d[9]), "+f"(d[10]), "+f"(d[11]), "+f"(d[12]), "+f"(d[13]), "+f"(d[14]), "+f"(d[15]), "+f"(d[16]), "+f"(d[17]), "+f"(d[18]), "+f"(d[19]), "+f"(d[20]), "+f"(d[21]), "+f"(d[22]), "+f"(d[23]), "+f"(d[24]), "+f"(d[25]), "+f"(d[26]), "+f"(d[27]), "+f"(d[28]), "+f"(d[29]), "+f"(d[30]), "+f"(d[31]), "+f"(d[32]), "+f"(d[33]), "+f"(d[34]), "+f"(d[35]), "+f"(d[36]), "+f"(d[37]), "+f"(d[38]), "+f"(d[39]), "+f"(d[40]), "+f"(d[41]), "+f"(d[42]), "+f"(d[43]), "+f"(d[44]), "+f"(d[45]), "+f"(d[46]), "+f"(d[47]), "+f"(d[48]), "+f"(d[49]), "+f"(d[50]), "+f"(d[51]), "+f"(d[52]), "+f"(d[53]), "+f"(d[54]), "+f"(d[55]), "+f"(d[56]), "+f"(d[57]), "+f"(d[58]), "+f"(d[59]), "+f"(d[60]), "+f"(d[61]), "+f"(d[62]), "+f"(d[63])
    : "r"(da), "r"(db), "r"(scale_d));
}
__device__ __forceinline__ void wgmma_n128_tb_p(float (&d)[64], uint32_t da, uint32_t db, int scale_d, int enable) {
  asm volatile(
    "{\n.reg .pred p;\n.reg .b64 da, db;\nsetp.ne.b32 p, %66, 0;\n.reg .pred q;\nsetp.ne.b32 q, %67, 0;\n"
    "mov.b64 da, {%64, 0x40000040};\nmov.b64 db, {%65, 0x40000040};\n"
    "@q wgmma.mma_async.sync.aligned.m64n128k16.f32.bf16.bf16 {%0, %1, %2, %3, %4, %5, %6, %7, %8, %9, %10, %11, %12, %13, %14, %15, %16, %17, %18, %19, %20, %21, %22, %23, %24, %25, %26, %27, %28, %29, %30, %31, %32, %33, %34, %35, %36, %37, %38, %39, %40, %41, %42, %43, %44, %45, %46, %47, %48, %49, %50, %51, %52, %53, %54, %55, %56, %57, %58, %59, %60, %61, %62, %63}, da, db, p, 1, 1, 0, 1;\n}\n"
    : "+f"(d[0]), "+f"(d[1]), "+f"(d[2]), "+f"(d[3]), "+f"(d[4]), "+f"(d[5]), "+f"(d[6]), "+f"(d[7]), "+f"(d[8]), "+f"(d[9]), "+f"(d[10]), "+f"(d[11]), "+f"(d[12]), "+f"(d[13]), "+f"(d[14]), "+f"(d[15]), "+f"(d[16]), "+f"(d[17]), "+f"(d[18]), "+f"(d[19]), "+f"(d[20]), "+f"(d[21]), "+f"(d[22]), "+f"(d[23]), "+f"(d[24]), "+f"(d[25]), "+f"(d[26]), "+f"(d[27]), "+f"(d[28]), "+f"(d[29]), "+f"(d[30]), "+f"(d[31]), "+f"(d[32]), "+f"(d[33]), "+f"(d[34]), "+f"(d[35]), "+f"(d[36]), "+f"(d[37]), "+f"(d[38]), "+f"(d[39]), "+f"(d[40]), "+f"(d[41]), "+f"(d[42]), "+f"(d[43]), "+f"(d[44]), "+f"(d[45]), "+f"(d[46]), "+f"(d[47]), "+f"(d[48]), "+f"(d[49]), "+f"(d[50]), "+f"(d[51]), "+f"(d[52]), "+f"(d[53]), "+f"(d[54]), "+f"(d[55]), "+f"(d[56]), "+f"(d[57]), "+f"(d[58]), "+f"(d[59]), "+f"(d[60]), "+f"(d[61]), "+f"(d[62]), "+f"(d[63])
    : "r"(da), "r"(db), "r"(scale_d), "r"(enable));
}
__device__ __forceinline__ void wgmma_n112(float (&d)[56], uint32_t da, uint32_t db, int scale_d) {
  asm volatile(
    "{\n.reg .pred p;\n.reg .b64 da, db;\nsetp.ne.b32 p, %58, 0;\n"
    "mov.b64 da, {%56, 0x40000040};\nmov.b64 db, {%57, 0x40000040};\n"
    "wgmma.mma_async.sync.aligned.m64n112k16.f32.bf16.bf16 {%0, %1, %2, %3, %4, %5, %6, %7, %8, %9, %10, %11, %12, %13, %14, %15, %16, %17, %18, %19, %20, %21, %22, %23, %24, %25, %26, %27, %28, %29, %30, %31, %32, %33, %34, %35, %36, %37, %38, %39, %40, %41, %42, %43, %44, %45, %46, %47, %48, %49, %50, %51, %52, %53, %54, %55}, da, db, p, 1, 1, 0, 0;\n}\n"
    : "+f"(d[0]), "+f"(d[1]), "+f"(d[2]), "+f"(d[3]), "+f"(d[4]), "+f"(d[5]), "+f"(d[6]), "+f"(d[7]), "+f"(d[8]), "+f"(d[9]), "+f"(d[10]), "+f"(d[11]), "+f"(d[12]), "+f"(d[13]), "+f"(d[14]), "+f"(d[15]), "+f"(d[16]), "+f"(d[17]), "+f"(d[18]), "+f"(d[19]), "+f"(d[20]), "+f"(d[21]), "+f"(d[22]), "+f"(d[23]), "+f"(d[24]), "+f"(d[25]), "+f"(d[26]), "+f"(d[27]), "+f"(d[28]), "+f"(d[29]), "+f"(d[30]), "+f"(d[31]), "+f"(d[32]), "+f"(d[33]), "+f"(d[34]), "+f"(d[35]), "+f"(d[36]), "+f"(d[37]), "+f"(d[38]), "+f"(d[39]), "+f"(d[40]), "+f"(d[41]), "+f"(d[42]), "+f"(d[43]), "+f"(d[44]), "+f"(d[45]), "+f"(d[46]), "+f"(d[47]), "+f"(d[48]), "+f"(d[49]), "+f"(d[50]), "+f"(d[51]), "+f"(d[52]), "+f"(d[53]), "+f"(d[54]), "+f"(d[55])
    : "r"(da), "r"(db), "r"(scale_d));
}
__device__ __forceinline__ void wgmma_n224_tb(float (&d)[112], uint32_t da, uint32_t db, int scale_d) {
  asm volatile(
    "{\n.reg .pred p;\n.reg .b64 da, db;\nsetp.ne.b32 p, %114, 0;\n"
    "mov.b64 da, {%112, 0x40000040};\nmov.b64 db, {%113, 0x40000040};\n"
    "wgmma.mma_async.sync.aligned.m64n224k16.f32.bf16.bf16 {%0, %1, %2, %3, %4, %5, %6, %7, %8, %9, %10, %11, %12, %13, %14, %15, %16, %17, %18, %19, %20, %21, %22, %23, %24, %25, %26, %27, %28, %29, %30, %31, %32, %33, %34, %35, %36, %37, %38, %39, %40, %41, %42, %43, %44, %45, %46, %47, %48, %49, %50, %51, %52, %53, %54, %55, %56, %57, %58, %59, %60, %61, %62, %63, %64, %65, %66, %67, %68, %69, %70, %71, %72, %73, %74, %75, %76, %77, %78, %79, %80, %81, %82, %83, %84, %85, %86, %87, %88, %89, %90, %91, %92, %93, %94, %95, %96, %97, %98, %99, %100, %101, %102, %103, %104, %105, %106, %107, %108, %109, %110, %111}, da, db, p, 1, 1, 0, 1;\n}\n"
    : "+f"(d[0]), "+f"(d[1]), "+f"(d[2]), "+f"(d[3]), "+f"(d[4]), "+f"(d[5]), "+f"(d[6]), "+f"(d[7]), "+f"(d[8]), "+f"(d[9]), "+f"(d[10]), "+f"(d[11]), "+f"(d[12]), "+f"(d[13]), "+f"(d[14]), "+f"(d[15]), "+f"(d[16]), "+f"(d[17]), "+f"(d[18]), "+f"(d[19]), "+f"(d[20]), "+f"(d[21]), "+f"(d[22]), "+f"(d[23]), "+f"(d[24]), "+f"(d[25]), "+f"(d[26]), "+f"(d[27]), "+f"(d[28]), "+f"(d[29]), "+f"(d[30]), "+f"(d[31]), "+f"(d[32]), "+f"(d[33]), "+f"(d[34]), "+f"(d[35]), "+f"(d[36]), "+f"(d[37]), "+f"(d[38]), "+f"(d[39]), "+f"(d[40]), "+f"(d[41]), "+f"(d[42]), "+f"(d[43]), "+f"(d[44]), "+f"(d[45]), "+f"(d[46]), "+f"(d[47]), "+f"(d[48]), "+f"(d[49]), "+f"(d[50]), "+f"(d[51]), "+f"(d[52]), "+f"(d[53]), "+f"(d[54]), "+f"(d[55]), "+f"(d[56]), "+f"(d[57]), "+f"(d[58]), "+f"(d[59]), "+f"(d[60]), "+f"(d[61]), "+f"(d[62]), "+f"(d[63]), "+f"(d[64]), "+f"(d[65]), "+f"(d[66]), "+f"(d[67]), "+f"(d[68]), "+f"(d[69]), "+f"(d[70]), "+f"(d[71]), "+f"(d[72]), "+f"(d[73]), "+f"(d[74]), "+f"(d[75]), "+f"(d[76]), "+f"(d[77]), "+f"(d[78]), "+f"(d[79]), "+f"(d[80]), "+f"(d[81]), "+f"(d[82]), "+f"(d[83]), "+f"(d[84]), "+f"(d[85]), "+f"(d[86]), "+f"(d[87]), "+f"(d[88]), "+f"(d[89]), "+f"(d[90]), "+f"(d[91]), "+f"(d[92]), "+f"(d[93]), "+f"(d[94]), "+f"(d[95]), "+f"(d[96]), "+f"(d[97]), "+f"(d[98]), "+f"(d[99]), "+f"(d[100]), "+f"(d[101]), "+f"(d[102]), "+f"(d[103]), "+f"(d[104]), "+f"(d[105]), "+f"(d[106]), "+f"(d[107]), "+f"(d[108]), "+f"(d[109]), "+f"(d[110]), "+f"(d[111])
    : "r"(da), "r"(db), "r"(scale_d));
}

constexpr int K1_NS = 5;
constexpr int K1_A_BYTES = 7 * 16384;
constexpr int K1_B_OFF = K1_A_BYTES;
constexpr int K1_STG_OFF = K1_B_OFF + K1_NS * 16384;
constexpr int K1_BAR_OFF = K1_STG_OFF + 8 * 4096;
constexpr int K1_SMEM = K1_BAR_OFF + 256 + 1024;

struct K1Ctx {
  uint32_t sb, bar_full, rel0, rel1;
  uint32_t dA, dBk, dBn;
  bool lane0;
  uint32_t bar_sfree;
  uint32_t sphase;
};
__device__ __forceinline__ void k1_release(const K1Ctx& c, int slot) {
  if (c.lane0) {
    asm volatile("mbarrier.arrive.shared::cluster.b64 _, [%0];" ::"r"(c.rel0 + 8 * slot) : "memory");
    asm volatile("mbarrier.arrive.shared::cluster.b64 _, [%0];" ::"r"(c.rel1 + 8 * slot) : "memory");
  }
}

__device__ __forceinline__ void k1_unit_ab(K1Ctx& c, int warp, int lane, int mt, int j) {
  const int wq = warp & 3;
  const int st_row = (lane & 7) + 8 * ((lane >> 3) & 1);
  const int st_chunk = lane >> 4;
  float acc[2][56];
  int slot = 0; uint32_t ph = 0;
#pragma unroll 1
  for (int kb = 0; kb < 7; kb++) {
    const int pslot = (slot == 0) ? K1_NS - 1 : slot - 1;
    mbar_wait(c.bar_full + 8 * slot, ph, 3);
    if (kb == 6) named_arrive(2, 256);
    if (kb == 0 && (threadIdx.x & 127) == 0) DBG(0, 4);
    if ((threadIdx.x & 127) == 0) DBGC(1, 46 + kb);
    wg_fence();
    const uint32_t da = c.dA + kb * 1024;
    const uint32_t db = c.dBk + slot * 1024;
#pragma unroll
    for (int k = 0; k < 4; k++) {
      wgmma_n112(acc[0], da + k * 2, db + k * 2, (kb | k) != 0);
      wgmma_n112(acc[1], da + 512 + k * 2, db + k * 2, (kb | k) != 0);
    }
    wg_commit();
    if (kb > 0) { wg_wait<1>(); k1_release(c, pslot); }
    if (++slot == K1_NS) { slot = 0; ph ^= 1; }
  }
  wg_wait<0>();
  k1_release(c, 6 % K1_NS);
  if ((threadIdx.x & 127) == 0) DBG(0, 5);
  const uint32_t sgn = (j < 4) ? 0u : 0x80008000u;
  const uint32_t sa = c.sb + K1_STG_OFF + (wq * 16 + st_row) * 224 + st_chunk * 16;
#pragma unroll
  for (int h = 0; h < 2; h++) {
    if (h == 1) { mbar_wait(c.bar_sfree, c.sphase, 6); c.sphase ^= 1; }
#pragma unroll
    for (int g = 0; g < 14; g += 2) {
      const float* a = &acc[h][4 * g];
      stmatrix_x4(sa + g * 16, pack_bf16(a[0], a[1]) ^ sgn, pack_bf16(a[2], a[3]) ^ sgn, pack_bf16(a[4], a[5]) ^ sgn, pack_bf16(a[6], a[7]) ^ sgn);
    }
    fence_async_smem();
    named_arrive(6, 160);
  }
}

__device__ __forceinline__ void k1_unit_gu(K1Ctx& c, int warp, int lane, int mt, int unit, int fb, int hsel, int full, int nunits) {
  const int wq = warp & 3;
  float acc[2][64];
  const uint32_t dA0 = c.dA + (full ? 0 : hsel * 512);
  int slot = (unit * 7) % K1_NS; uint32_t ph = ((unit * 7) / K1_NS) & 1;
  named_bar(2 + ((unit - 1) & 1), 256);
  if (full) {
#pragma unroll 1
    for (int kb = 0; kb < 7; kb++) {
      const int pslot = (slot == 0) ? K1_NS - 1 : slot - 1;
      mbar_wait(c.bar_full + 8 * slot, ph, 4);
      if (kb == 6 && unit + 1 < nunits) named_arrive(2 + (unit & 1), 256);
      if (kb == 0 && (threadIdx.x & 127) == 0) DBG(0, (4 + 3 * unit) % 20);
      wg_fence();
      const uint32_t da = dA0 + kb * 1024;
      const uint32_t db = c.dBn + slot * 1024;
#pragma unroll
      for (int k = 0; k < 4; k++) {
        wgmma_n128_tb(acc[0], da + k * 2, db + k * 128, (kb | k) != 0);
        wgmma_n128_tb(acc[1], da + 512 + k * 2, db + k * 128, (kb | k) != 0);
      }
      wg_commit();
      if (kb > 0) { wg_wait<1>(); k1_release(c, pslot); }
      if (++slot == K1_NS) { slot = 0; ph ^= 1; }
    }
  } else {
#pragma unroll 1
    for (int kb = 0; kb < 7; kb++) {
      const int pslot = (slot == 0) ? K1_NS - 1 : slot - 1;
      mbar_wait(c.bar_full + 8 * slot, ph, 5);
      if (kb == 0 && (threadIdx.x & 127) == 0) DBG(0, (4 + 3 * unit) % 20);
      wg_fence();
      const uint32_t da = dA0 + kb * 1024;
      const uint32_t db = c.dBn + slot * 1024;
#pragma unroll
      for (int k = 0; k < 4; k++) wgmma_n128_tb(acc[0], da + k * 2, db + k * 128, (kb | k) != 0);
      wg_commit();
      if (kb > 0) { wg_wait<1>(); k1_release(c, pslot); }
      if (++slot == K1_NS) { slot = 0; ph ^= 1; }
    }
  }
  wg_wait<0>();
  k1_release(c, (slot == 0) ? K1_NS - 1 : slot - 1);
  if (unit + 2 >= nunits && lane < 4) {
    asm volatile("mbarrier.arrive.shared::cluster.b64 _, [%0];" ::"r"(c.rel0 + 8 * (K1_NS + 4 + lane)) : "memory");
    asm volatile("mbarrier.arrive.shared::cluster.b64 _, [%0];" ::"r"(c.rel1 + 8 * (K1_NS + 4 + lane)) : "memory");
  }
  if ((threadIdx.x & 127) == 0) DBG(0, (5 + 3 * unit) % 20 == 0 ? 19 : (5 + 3 * unit));
  const int st_row = (lane & 7) + 8 * ((lane >> 3) & 1);
  const int st_chunk = lane >> 4;
  const uint32_t sa = c.sb + K1_STG_OFF + (warp >> 2) * 16384 + (wq * 16 + st_row) * 128;
  if (unit >= 2) { mbar_wait(c.bar_sfree, c.sphase, 7); c.sphase ^= 1; }
#pragma unroll
  for (int h = 0; h < 2; h++) {
    if (h == 1 && !full) break;
#pragma unroll
    for (int g = 0; g < 8; g += 2) {
      uint32_t pk[4];
#pragma unroll
      for (int e = 0; e < 4; e++) {
        const int i = 4 * g + 2 * e;
        const uint32_t g2 = pack_bf16(acc[h][i], acc[h][i + 1]);
        const uint32_t u2 = pack_bf16(acc[h][32 + i], acc[h][32 + i + 1]);
        pk[e] = hmul2_bf16(pack_bf16(gelu_tanh(bf_lo(g2)), gelu_tanh(bf_hi(g2))), u2);
      }
      stmatrix_x4(sa + h * 8192 + (((g + st_chunk) ^ (st_row & 7)) * 16), pk[0], pk[1], pk[2], pk[3]);
    }
  }
  fence_async_smem();
  named_arrive(6 + (warp >> 2), 160);
}

constexpr int K2_NS = 4;
constexpr int K2_STAGE = 16384 + 32768;
constexpr int K2_PITCH = 464;

__device__ __forceinline__ void spin_flag(const unsigned int* flag, unsigned int target) {
  int it = 0;
  while (true) {
    unsigned int v;
    asm volatile("ld.acquire.gpu.global.u32 %0, [%1];" : "=r"(v) : "l"(flag) : "memory");
    if ((int)(v - target) >= 0) break;
    if (++it > SPIN_LIMIT) { TIMEOUT(20); break; }
  }
}

__device__ __forceinline__ void ln_rows(const __nv_bfloat16* __restrict__ xt, uint32_t sb, int lw, int lane) {
  const int c = lane & 7;
  const int r0 = lw * 4 + (lane >> 3);
  const uint4* src = reinterpret_cast<const uint4*>(xt + (size_t)r0 * 448) + c;
  uint4 nx[7];
#pragma unroll
  for (int b = 0; b < 7; b++)
    asm volatile("ld.global.nc.v4.u32 {%0,%1,%2,%3}, [%4];" : "=r"(nx[b].x), "=r"(nx[b].y), "=r"(nx[b].z), "=r"(nx[b].w) : "l"(src + b * 8) : "memory");
  const int npass = (lw < 10) ? 3 : 2;
  if (c < 7) {
    asm volatile("prefetch.global.L2 [%0];" ::"l"(src + 44 * 56 + c * 7) : "memory");
    if (npass == 3) asm volatile("prefetch.global.L2 [%0];" ::"l"(src + 88 * 56 + c * 7) : "memory");
  }
#pragma unroll 1
  for (int pass = 0; pass < npass; pass++) {
    uint4 v[7];
#pragma unroll
    for (int b = 0; b < 7; b++) v[b] = nx[b];
    if (pass + 1 < npass) {
      const uint4* s2 = src + (pass + 1) * 44 * 56;
#pragma unroll
      for (int b = 0; b < 7; b++)
        asm volatile("ld.global.nc.v4.u32 {%0,%1,%2,%3}, [%4];" : "=r"(nx[b].x), "=r"(nx[b].y), "=r"(nx[b].z), "=r"(nx[b].w) : "l"(s2 + b * 8) : "memory");
    }
        float s0 = 0.f, s1 = 0.f, s2v = 0.f, s3 = 0.f;
#pragma unroll
        for (int b = 0; b < 7; b++) {
          s0 += bf_lo(v[b].x) + bf_hi(v[b].x); s1 += bf_lo(v[b].y) + bf_hi(v[b].y);
          s2v += bf_lo(v[b].z) + bf_hi(v[b].z); s3 += bf_lo(v[b].w) + bf_hi(v[b].w);
        }
        float m = (s0 + s1) + (s2v + s3);
        m += __shfl_xor_sync(0xffffffffu, m, 1);
        m += __shfl_xor_sync(0xffffffffu, m, 2);
        m += __shfl_xor_sync(0xffffffffu, m, 4);
        m *= (1.0f / 448.0f);
        float q0 = 0.f, q1 = 0.f, q2 = 0.f, q3 = 0.f;
#pragma unroll
        for (int b = 0; b < 7; b++) {
          float d;
          d = bf_lo(v[b].x) - m; q0 = fmaf(d, d, q0); d = bf_hi(v[b].x) - m; q1 = fmaf(d, d, q1);
          d = bf_lo(v[b].y) - m; q2 = fmaf(d, d, q2); d = bf_hi(v[b].y) - m; q3 = fmaf(d, d, q3);
          d = bf_lo(v[b].z) - m; q0 = fmaf(d, d, q0); d = bf_hi(v[b].z) - m; q1 = fmaf(d, d, q1);
          d = bf_lo(v[b].w) - m; q2 = fmaf(d, d, q2); d = bf_hi(v[b].w) - m; q3 = fmaf(d, d, q3);
        }
        float q = (q0 + q1) + (q2 + q3);
        q += __shfl_xor_sync(0xffffffffu, q, 1);
        q += __shfl_xor_sync(0xffffffffu, q, 2);
        q += __shfl_xor_sync(0xffffffffu, q, 4);
        const float var_b = rbf(q * (1.0f / 448.0f));
        const float den = rbf(sqrtf(rbf(var_b + 1e-5f)));
        const float ri = 1.0f / den;
        const float rih = rbf(ri);
        const uint32_t rhi2 = pack_bf16(rih, rih), rlo2 = pack_bf16(ri - rih, ri - rih);
        const uint32_t m2 = pack_bf16(m, m);
        const int r = r0 + pass * 44;
        const uint32_t a0 = sb + r * 128 + ((c ^ (r & 7)) * 16);
#pragma unroll
        for (int b = 0; b < 7; b++) {
          uint32_t w4[4] = {v[b].x, v[b].y, v[b].z, v[b].w};
#pragma unroll
          for (int qq = 0; qq < 4; qq++) {
            const uint32_t dw = hsub2_bf16(w4[qq], m2);
            w4[qq] = hfma2_bf16(dw, rhi2, hmul2_bf16(dw, rlo2));
          }
          sts128(a0 + b * 16384, make_uint4(w4[0], w4[1], w4[2], w4[3]));
        }
  }
}

struct PfPtrs { const uint8_t* wg; const uint8_t* wu; const uint8_t* wd; };

__global__ void __cluster_dims__(2, 1, 1) __launch_bounds__(384, 1)
fused_kernel(const __grid_constant__ CUtensorMap tm_wr, const __grid_constant__ CUtensorMap tm_wi,
             const __grid_constant__ CUtensorMap tm_wg, const __grid_constant__ CUtensorMap tm_wu,
             const __grid_constant__ CUtensorMap tm_hs, const __grid_constant__ CUtensorMap tm_abs,
             const __grid_constant__ CUtensorMap tm_cr, const __grid_constant__ CUtensorMap tm_ci, const __grid_constant__ CUtensorMap tm_h,
             const __grid_constant__ CUtensorMap tm_ab, const __grid_constant__ CUtensorMap tm_wd,
             const __nv_bfloat16* __restrict__ x, __nv_bfloat16* __restrict__ out, const PfPtrs pf) {
  extern __shared__ uint8_t smem_raw[];
  const uint32_t sb = (s2u(smem_raw) + 1023) & ~1023u;
  const int tid = threadIdx.x, warp = tid >> 5, lane = tid & 31;
  uint32_t rank;
  asm volatile("mov.u32 %0, %%cluster_ctarank;" : "=r"(rank));
  const int cid = blockIdx.x >> 1;
  const int p = cid >> 3, j = cid & 7;
  const int mt = 2 * p + (int)rank;
  const uint32_t bar_full = sb + K1_BAR_OFF;
  const uint32_t bar_empty = bar_full + 8 * K1_NS;
  const uint32_t bar_full2 = bar_empty + 8 * K1_NS;
  const uint32_t bar_empty2 = bar_full2 + 8 * K2_NS;
  const int q = j & 3, n = j >> 2;
  const int tile = mt * 2 + n;
  const int nkb = (q < 2) ? 23 : (q == 3 ? 28 : 18);
  const int fb_base = 7 * (j >> 1);
  const int ngu = (q < 2) ? 4 : (q == 2 ? 5 : 3);
  const int nunits = ngu + 1;
  const int fb0 = fb_base + ((q == 1) ? 4 : (q == 3 ? 5 : 0)) - 1;
  const int fbh = fb_base + ((q < 2) ? 3 : 4);
  const unsigned int epoch = *reinterpret_cast<volatile unsigned int*>(&g_epoch);
  if (tid == 0) DBG(0, 0);
  if (tid == 256) {
    for (int i = 0; i < K1_NS; i++) { mbar_init(bar_full + 8 * i, 1); mbar_init(bar_empty + 8 * i, 8); }
    for (int i = 0; i < K2_NS; i++) { mbar_init(bar_full2 + 8 * i, 1); mbar_init(bar_empty2 + 8 * i, 16); }
    mbar_init(bar_empty2 + 8 * K2_NS, 1);
    mbar_init(bar_empty2 + 8 * K2_NS + 8, 1);
    mbar_init(bar_empty2 + 8 * K2_NS + 16, 1);
    asm volatile("fence.mbarrier_init.release.cluster;" ::: "memory");
    prefetch_tmap((j < 4) ? &tm_wr : &tm_wi);
    prefetch_tmap(rank ? &tm_wu : &tm_wg);
    prefetch_tmap(&tm_abs);
    prefetch_tmap(&tm_hs);
  }
  __syncwarp();
  cluster_arrive_relaxed();

  if (warp != 8) {
    ln_rows(x + (size_t)mt * 128 * 448, sb, warp < 8 ? warp : warp - 1, lane);
    asm volatile("fence.proxy.async.shared::cta;" ::: "memory");
  }
  if (warp >= 8) {
    if (warp > 8) named_arrive(8, 352);
    reg_dec<40>();
    cluster_wait();
    if (tid == 256) {
      {
        const CUtensorMap* tw = (j < 4) ? &tm_wr : &tm_wi;
        const CUtensorMap* tgu = rank ? &tm_wu : &tm_wg;
        int slot = 0; uint32_t ph = 0;
        int kb = 0, unit = 0;
#pragma unroll 1
        for (int s = 0; s < 7 * nunits; s++) {
          if (s >= K1_NS) mbar_wait(bar_empty + 8 * slot, ph ^ 1, 2);
          const uint32_t dst = sb + K1_B_OFF + slot * 16384;
          if (unit == 0) {
            mbar_expect(bar_full + 8 * slot, 14336);
            tma2d_mc(dst + rank * 7168, tw, kb * 64, (j & 3) * 112 + rank * 56, bar_full + 8 * slot, 3);
          } else {
            const int fb = (unit == ngu) ? fbh : (fb0 + unit);
            mbar_expect(bar_full + 8 * slot, 16384);
            tma2d_mc(dst + rank * 8192, tgu, fb * 64, kb * 64, bar_full + 8 * slot, 3);
          }
          if (s == 7 * nunits - 12) {
            l2_prefetch(pf.wd + blockIdx.x * 12544, 12544);
            if (q < 3) {
              const int g0 = q * 23;
#pragma unroll 1
              for (int i = 0; i < 6; i++) tma2d_prefetch((g0 + i < 32) ? &tm_cr : &tm_ci, ((g0 + i) & 31) * 64, mt * 128);
            }
          }
          if (++kb == 7) { kb = 0; unit++; }
          if (++slot == K1_NS) { slot = 0; ph ^= 1; }
        }
      }
      {
        const int g0 = (q < 3) ? q * 23 : 64;
        const CUtensorMap* tb = (q < 3) ? &tm_ab : &tm_wd;
        prefetch_tmap(tb); prefetch_tmap((q < 3) ? ((g0 < 32) ? &tm_cr : &tm_ci) : &tm_h);
        const int kb0 = (q < 3) ? g0 : 0;
        if (q < 3) { spin_flag(&g_ab_cnt, 128u * (epoch + 1)); asm volatile("fence.proxy.async;" ::: "memory"); }
        DBG(1, 31);
        int slot = 0; uint32_t ph = 0;
#pragma unroll 1
        for (int s = 0; s < nkb; s++) {
          int kblk = kb0 + s;
          const CUtensorMap* ta = (kblk < 32) ? &tm_cr : &tm_ci;
          if (q == 3) {
            const int cls = (s == 0) ? 0 : (s == 8 ? 1 : (s == 16 ? 2 : (s == 22 ? 3 : (s == 26 ? 4 : -1))));
            if (cls >= 0) { spin_flag(&g_h_cnt[mt * 8 + cls], ((cls < 3) ? 8u : (cls == 3 ? 6u : 2u)) * (epoch + 1)); asm volatile("fence.proxy.async;" ::: "memory"); }
            kblk = c_forder[s];
            ta = &tm_h;
          }
          mbar_wait(bar_empty2 + 8 * slot, ph, 10);
          const uint32_t dst = sb + slot * K2_STAGE;
          const uint32_t fb = bar_full2 + 8 * slot;
          mbar_expect(fb, K2_STAGE);
          tma2d(dst, ta, (kblk & 31) * 64, mt * 128, fb);
          tma3d_mc(dst + 16384 + (2 * rank) * 8192, tb, (2 * rank) * 64, n, kblk * 64, fb, 3);
          tma3d_mc(dst + 16384 + (2 * rank + 1) * 8192, tb, (2 * rank + 1) * 64, n, kblk * 64, fb, 3);
          if (++slot == K2_NS) { slot = 0; ph ^= 1; }
        }
      }
    } else if (warp == 9 || warp == 10) {
      const int hw = warp - 9;
      const uint32_t stg = sb + K1_STG_OFF + hw * 16384;
      const uint32_t bar_sfree = bar_empty2 + 8 * K2_NS + 8 + 8 * hw;
      if (lane == 0) {
        const int b = blockIdx.x;
        l2_prefetch((hw ? pf.wu : pf.wg) + b * 12544, 12544);
      }
#pragma unroll 1
      for (int job = 0; job < (hw ? (ngu + 1) / 2 : 2 + ngu / 2); job++) {
        named_bar(6 + hw, 160);
        if (lane == 0) {
          const int unit = hw ? (1 + 2 * job) : (job < 2 ? 0 : 2 * job - 2);
          if (unit == 0) {
            tma2d_store(&tm_abs, stg, (j & 3) * 112, (j < 4 ? 0 : 2048) + mt * 128 + job * 64);
          } else {
            const int fb = (unit == ngu) ? fbh : fb0 + unit;
            const bool fullu = (unit < ngu);
            tma2d_store(&tm_hs, stg, fb * 64, mt * 128 + (fullu ? 0 : (j & 1) * 64));
            if (fullu) tma2d_store(&tm_hs, stg + 8192, fb * 64, mt * 128 + 64);
          }
          bulk_commit();
          bulk_wait_read0();
          asm volatile("mbarrier.arrive.shared::cta.b64 _, [%0];" ::"r"(bar_sfree) : "memory");
          if (unit != 0 || job == 1) {
            bulk_wait0();
            asm volatile("fence.proxy.async;" ::: "memory");
            __threadfence();
            if (unit == 0) {
              const unsigned int old = atomicAdd(&g_ab_cnt, 1u);
              if ((old & 127u) == 127u) *reinterpret_cast<volatile unsigned int*>(&g_epoch) = (old >> 7) + 1;
            } else {
              atomicAdd(&g_h_cnt[mt * 8 + unit - 1], 1u);
            }
          }
        }
        __syncwarp();
      }
    }
  } else {
    const int wg = warp >> 2;
    named_bar(8, 352);
    reg_inc<232>();
    cluster_wait();
    if (tid == 0) DBG(0, 3);

    uint32_t rel0, rel1, sphase_end;
    asm volatile("mapa.shared::cluster.u32 %0, %1, %2;" : "=r"(rel0) : "r"(bar_empty2), "r"(0));
    asm volatile("mapa.shared::cluster.u32 %0, %1, %2;" : "=r"(rel1) : "r"(bar_empty2), "r"(1));
    {
      K1Ctx c;
      c.sb = sb; c.bar_full = bar_full; c.lane0 = (lane == 0);
      c.rel0 = rel0 - 8 * (K1_NS + K2_NS); c.rel1 = rel1 - 8 * (K1_NS + K2_NS);
      c.bar_sfree = bar_empty2 + 8 * K2_NS + 8 + 8 * wg; c.sphase = 0;
      c.dA = make_desc(sb, 16, 1024);
      c.dBk = make_desc(sb + K1_B_OFF, 16, 1024);
      c.dBn = make_desc(sb + K1_B_OFF, 8192, 1024);
      if (wg == 0) {
        k1_unit_ab(c, warp, lane, mt, j);
        if (tid == 0) DBG(0, 6);
      }
#pragma unroll 1
      for (int unit = 2 - wg; unit < nunits; unit += 2) {
        k1_unit_gu(c, warp, lane, mt, unit, (unit == ngu) ? fbh : fb0 + unit, j & 1, unit < ngu, nunits);
        if ((tid & 127) == 0 && unit < 5) DBG(0, 6 + 3 * unit);
      }
      sphase_end = c.sphase;
    }

    float acc[112];
    const uint32_t dA0 = make_desc(sb + wg * 8192, 16, 1024);
    const uint32_t dB0 = make_desc(sb + 16384, 8192, 1024);
    int slot = 0; uint32_t ph = 0;
#pragma unroll 1
    for (int s = 0; s < nkb; s++) {
      mbar_wait(bar_full2 + 8 * slot, ph, 11);
      if (tid == 0) DBG(1, 1 + s);
      wg_fence();
      const uint32_t da = dA0 + slot * (K2_STAGE / 16);
      const uint32_t db = dB0 + slot * (K2_STAGE / 16);
#pragma unroll
      for (int k = 0; k < 4; k++) wgmma_n224_tb(acc, da + k * 2, db + k * 128, (s | k) != 0);
      wg_commit();
      if (s > 0) {
        wg_wait<1>();
        const int ps = (slot == 0) ? K2_NS - 1 : slot - 1;
        if (lane == 0) {
          asm volatile("mbarrier.arrive.shared::cluster.b64 _, [%0];" ::"r"(rel0 + 8 * ps) : "memory");
          asm volatile("mbarrier.arrive.shared::cluster.b64 _, [%0];" ::"r"(rel1 + 8 * ps) : "memory");
        }
      }
      if (++slot == K2_NS) { slot = 0; ph ^= 1; }
    }
    wg_wait<0>();
    if (tid == 0) DBG(1, 29);
    uint32_t ow[56];
#pragma unroll
    for (int i = 0; i < 56; i++) ow[i] = pack_bf16(acc[2 * i], acc[2 * i + 1]);
    const int P0 = (q < 2) ? 4 * q : 3 * q + 2, NP = (q < 2) ? 4 : 3;
    uint4* part = g_part + (size_t)tile * (4 * 14 * 256) + tid;
    mbar_wait(bar_empty2 + 8 * K2_NS + 8 + 8 * wg, sphase_end, 14);
    const uint32_t stg = sb + K1_STG_OFF + warp * 4096;
    const uint32_t stash = stg + 2048 + lane * 16 - P0 * 512;
#pragma unroll
    for (int g = 0; g < 14; g++) {
      const uint4 v = make_uint4(ow[4 * g], ow[4 * g + 1], ow[4 * g + 2], ow[4 * g + 3]);
      if ((unsigned)(g - P0) >= (unsigned)NP) part[(q * 14 + g) * 256] = v;
      else sts128(stash + g * 512, v);
    }
    __syncwarp();
    unsigned int* flag = &g_flags[tile * 8 + warp];
    if (lane == 0) { __threadfence(); atomicAdd(flag, 1u); }
    const int ch = lane & 7;
    const bool act = ch < 2 * NP;
    const size_t gbase = (size_t)(mt * 128 + warp * 16 + (lane >> 3)) * 448 + n * 224 + P0 * 16 + (act ? ch : 0) * 8;
    uint4 xv[4];
#pragma unroll
    for (int t = 0; t < 4; t++) xv[t] = ldg128_cg(x + gbase + t * 4 * 448);
    if (tid == 0) DBG(1, 62);
    if (lane == 0) spin_flag(flag, 4u * (epoch + 1));
    __syncwarp();
    if (tid == 0) DBG(1, 30);
    uint4 oth[3][4];
#pragma unroll
    for (int i = 0; i < 3; i++) {
      const int r = (i < q) ? i : i + 1;
#pragma unroll
      for (int e = 0; e < 4; e++) oth[i][e] = ldg128_cg(part + (r * 14 + P0 + (e < NP ? e : 0)) * 256);
    }
    const bool isf = (q == 3);
    const int st_row = (lane & 7) + 8 * ((lane >> 3) & 1);
    const uint32_t sa = stg + st_row * 128;
#pragma unroll
    for (int e = 0; e < 4; e++) {
      const uint32_t av[4] = {oth[0][e].x, oth[0][e].y, oth[0][e].z, oth[0][e].w};
      const uint32_t bv[4] = {oth[1][e].x, oth[1][e].y, oth[1][e].z, oth[1][e].w};
      const uint32_t cv[4] = {oth[2][e].x, oth[2][e].y, oth[2][e].z, oth[2][e].w};
      const uint4 mine = lds128(stg + 2048 + lane * 16 + (e < NP ? e : 0) * 512);
      const uint32_t mv[4] = {mine.x, mine.y, mine.z, mine.w};
      uint32_t tv[4];
#pragma unroll
      for (int k = 0; k < 4; k++) {
        const uint32_t y3 = isf ? cv[k] : mv[k], ff = isf ? mv[k] : cv[k];
        const uint32_t gg = pack_bf16(silu_f(bf_lo(ff)), silu_f(bf_hi(ff)));
        tv[k] = hmul2_bf16(pack_bf16(bf_lo(av[k]) + bf_lo(bv[k]) + bf_lo(y3), bf_hi(av[k]) + bf_hi(bv[k]) + bf_hi(y3)), gg);
      }
      stmatrix_x4(sa + (((2 * e + (lane >> 4)) ^ (st_row & 7)) * 16), tv[0], tv[1], tv[2], tv[3]);
    }
    __syncwarp();
#pragma unroll
    for (int t = 0; t < 4; t++) {
      const int row = t * 4 + (lane >> 3);
      const uint4 tv = lds128(stg + row * 128 + ((ch ^ (row & 7)) * 16));
      uint4 o;
      o.x = hadd2_bf16(xv[t].x, tv.x); o.y = hadd2_bf16(xv[t].y, tv.y); o.z = hadd2_bf16(xv[t].z, tv.z); o.w = hadd2_bf16(xv[t].w, tv.w);
      if (act) stg128(out + gbase + t * 4 * 448, o);
    }
    if (tid == 0) DBG(1, 63);
  }
  __syncwarp();
  cluster_arrive_relaxed();
  cluster_wait();
}

typedef CUresult (*EncFn)(CUtensorMap*, CUtensorMapDataType, cuuint32_t, void*, const cuuint64_t*, const cuuint64_t*, const cuuint32_t*,
                          const cuuint32_t*, CUtensorMapInterleave, CUtensorMapSwizzle, CUtensorMapL2promotion, CUtensorMapFloatOOBfill);

void make2d(EncFn enc, CUtensorMap* tm, const void* ptr, uint64_t cols, uint64_t rows, uint32_t bc, uint32_t br, bool swz = true) {
  cuuint64_t gd[2] = {cols, rows};
  cuuint64_t gs[1] = {cols * 2};
  cuuint32_t bd[2] = {bc, br};
  cuuint32_t es[2] = {1, 1};
  enc(tm, CU_TENSOR_MAP_DATA_TYPE_BFLOAT16, 2, const_cast<void*>(ptr), gd, gs, bd, es, CU_TENSOR_MAP_INTERLEAVE_NONE,
      swz ? CU_TENSOR_MAP_SWIZZLE_128B : CU_TENSOR_MAP_SWIZZLE_NONE, CU_TENSOR_MAP_L2_PROMOTION_L2_128B, CU_TENSOR_MAP_FLOAT_OOB_FILL_NONE);
}
void make3d_half(EncFn enc, CUtensorMap* tm, const void* ptr, uint64_t rows) {
  cuuint64_t gd[3] = {224, 2, rows};
  cuuint64_t gs[2] = {448, 896};
  cuuint32_t bd[3] = {64, 1, 64};
  cuuint32_t es[3] = {1, 1, 1};
  enc(tm, CU_TENSOR_MAP_DATA_TYPE_BFLOAT16, 3, const_cast<void*>(ptr), gd, gs, bd, es, CU_TENSOR_MAP_INTERLEAVE_NONE,
      CU_TENSOR_MAP_SWIZZLE_128B, CU_TENSOR_MAP_L2_PROMOTION_L2_128B, CU_TENSOR_MAP_FLOAT_OOB_FILL_NONE);
}

struct Maps { CUtensorMap wr, wi, wg, wu, cr, ci, h, ab, wd, hs, abs; };

}

extern "C" void kernel_launch(void* const* d_in, const int* in_sizes, int n_in, void* d_out, int out_size) {
  (void)in_sizes; (void)n_in; (void)out_size;
  static Maps maps;
  static const void* cached[9] = {nullptr};
  static bool attr_done = false;
  bool same = true;
  for (int i = 0; i < 9; i++) same = same && (cached[i] == d_in[i]);
  if (!same) {
    void* fn = nullptr;
    cudaDriverEntryPointQueryResult qr;
    cudaGetDriverEntryPoint("cuTensorMapEncodeTiled", &fn, cudaEnableDefault, &qr);
    EncFn enc = (EncFn)fn;
    void *p_ab = nullptr, *p_h = nullptr;
    cudaGetSymbolAddress(&p_ab, g_ab);
    cudaGetSymbolAddress(&p_h, g_h);
    make2d(enc, &maps.cr, d_in[1], 2048, 2048, 64, 128);
    make2d(enc, &maps.ci, d_in[2], 2048, 2048, 64, 128);
    make2d(enc, &maps.wr, d_in[3], 448, 448, 64, 56);
    make2d(enc, &maps.wi, d_in[4], 448, 448, 64, 56);
    make2d(enc, &maps.wg, d_in[6], 1792, 448, 64, 64);
    make2d(enc, &maps.wu, d_in[7], 1792, 448, 64, 64);
    make3d_half(enc, &maps.wd, d_in[8], 1792);
    make2d(enc, &maps.h, p_h, 1792, 2048, 64, 128);
    make3d_half(enc, &maps.ab, p_ab, 4096);
    make2d(enc, &maps.hs, p_h, 1792, 2048, 64, 64);
    make2d(enc, &maps.abs, p_ab, 448, 4096, 112, 64, false);
    for (int i = 0; i < 9; i++) cached[i] = d_in[i];
  }
  if (!attr_done) {
    cudaFuncSetAttribute(fused_kernel, cudaFuncAttributeMaxDynamicSharedMemorySize, K1_SMEM);
    attr_done = true;
  }
  PfPtrs pf;
  pf.wg = (const uint8_t*)d_in[6]; pf.wu = (const uint8_t*)d_in[7]; pf.wd = (const uint8_t*)d_in[8];
  fused_kernel<<<128, 384, K1_SMEM>>>(maps.wr, maps.wi, maps.wg, maps.wu, maps.hs, maps.abs, maps.cr, maps.ci, maps.h, maps.ab, maps.wd,
                                      (const __nv_bfloat16*)d_in[0], (__nv_bfloat16*)d_out, pf);
}
```

```cpp
#include <cuda_runtime.h>
#include <cuda_bf16.h>
#include <cuda.h>
#include <stdint.h>

namespace {

__device__ __align__(1024) __nv_bfloat16 g_ab[4096 * 448];
__device__ __align__(1024) __nv_bfloat16 g_h[2048 * 1792];
__device__ uint4 g_part[32 * 4 * 14 * 256];
__device__ unsigned int g_epoch;
__device__ unsigned int g_ab_cnt;
__device__ unsigned int g_h_cnt[16 * 8];
__constant__ unsigned char c_forder[28] = {0, 4, 7, 12, 14, 18, 21, 26, 1, 5, 8, 13, 15, 19, 22, 27, 2, 6, 9, 16, 20, 23, 3, 10, 17, 24, 11, 25};
__device__ unsigned int g_flags[32 * 8];

#define SPIN_LIMIT (1 << 22)

__device__ __forceinline__ uint32_t s2u(const void* p) { return (uint32_t)__cvta_generic_to_shared(p); }
__device__ __forceinline__ void mbar_init(uint32_t b, int c) { asm volatile("mbarrier.init.shared::cta.b64 [%0], %1;" ::"r"(b), "r"(c)); }
__device__ __forceinline__ void mbar_expect(uint32_t b, uint32_t bytes) {
  asm volatile("mbarrier.arrive.expect_tx.shared::cta.b64 _, [%0], %1;" ::"r"(b), "r"(bytes) : "memory");
}
__device__ __forceinline__ void mbar_wait(uint32_t b, uint32_t ph, int code = 1) {
  uint32_t done = 0;
  int it = 0;
  while (true) {
    asm volatile("{.reg .pred p; mbarrier.try_wait.parity.shared::cta.b64 p, [%1], %2; selp.u32 %0,1,0,p;}" : "=r"(done) : "r"(b), "r"(ph) : "memory");
    if (done) break;
    if (++it > SPIN_LIMIT) break;
  }
}
__device__ __forceinline__ void tma2d(uint32_t dst, const CUtensorMap* m, int c0, int c1, uint32_t bar) {
  asm volatile("cp.async.bulk.tensor.2d.shared::cluster.global.mbarrier::complete_tx::bytes [%0], [%1, {%3,%4}], [%2];" ::"r"(dst), "l"(m), "r"(bar), "r"(c0), "r"(c1) : "memory");
}
__device__ __forceinline__ void tma2d_mc(uint32_t dst, const CUtensorMap* m, int c0, int c1, uint32_t bar, uint16_t mask) {
  asm volatile("cp.async.bulk.tensor.2d.shared::cluster.global.mbarrier::complete_tx::bytes.multicast::cluster [%0], [%1, {%3,%4}], [%2], %5;" ::"r"(dst), "l"(m), "r"(bar), "r"(c0), "r"(c1), "h"(mask) : "memory");
}
__device__ __forceinline__ void tma3d_mc(uint32_t dst, const CUtensorMap* m, int c0, int c1, int c2, uint32_t bar, uint16_t mask) {
  asm volatile("cp.async.bulk.tensor.3d.shared::cluster.global.mbarrier::complete_tx::bytes.multicast::cluster [%0], [%1, {%3,%4,%5}], [%2], %6;" ::"r"(dst), "l"(m), "r"(bar), "r"(c0), "r"(c1), "r"(c2), "h"(mask) : "memory");
}
__device__ __forceinline__ void tma2d_store(const CUtensorMap* m, uint32_t src, int c0, int c1) {
  asm volatile("cp.async.bulk.tensor.2d.global.shared::cta.bulk_group [%0, {%2,%3}], [%1];" ::"l"(m), "r"(src), "r"(c0), "r"(c1) : "memory");
}
__device__ __forceinline__ void tma2d_prefetch(const CUtensorMap* m, int c0, int c1) {
  asm volatile("cp.async.bulk.prefetch.tensor.2d.L2.global [%0, {%1,%2}];" ::"l"(m), "r"(c0), "r"(c1) : "memory");
}
__device__ __forceinline__ void bulk_commit() { asm volatile("cp.async.bulk.commit_group;" ::: "memory"); }
__device__ __forceinline__ void bulk_wait_read0() { asm volatile("cp.async.bulk.wait_group.read 0;" ::: "memory"); }
__device__ __forceinline__ void bulk_wait0() { asm volatile("cp.async.bulk.wait_group 0;" ::: "memory"); }
__device__ __forceinline__ void fence_async_smem() { asm volatile("fence.proxy.async.shared::cta;" ::: "memory"); }
__device__ __forceinline__ void prefetch_tmap(const CUtensorMap* m) { asm volatile("prefetch.tensormap [%0];" ::"l"(m) : "memory"); }
__device__ __forceinline__ void l2_prefetch(const void* p, uint32_t bytes) {
  asm volatile("cp.async.bulk.prefetch.L2.global [%0], %1;" ::"l"(p), "r"(bytes) : "memory");
}
__device__ __forceinline__ void cluster_arrive_relaxed() { asm volatile("barrier.cluster.arrive.relaxed.aligned;" ::: "memory"); }
__device__ __forceinline__ void cluster_wait() { asm volatile("barrier.cluster.wait.aligned;" ::: "memory"); }
__device__ __forceinline__ void wg_fence() { __syncwarp(); asm volatile("wgmma.fence.sync.aligned;" ::: "memory"); }
__device__ __forceinline__ void wg_commit() { asm volatile("wgmma.commit_group.sync.aligned;" ::: "memory"); }
template <int N> __device__ __forceinline__ void wg_wait() { __syncwarp(); asm volatile("wgmma.wait_group.sync.aligned %0;" ::"n"(N) : "memory"); }
__device__ __forceinline__ void named_bar(int id, int n) { asm volatile("bar.sync %0, %1;" ::"r"(id), "r"(n) : "memory"); }
__device__ __forceinline__ void named_arrive(int id, int n) { asm volatile("bar.arrive %0, %1;" ::"r"(id), "r"(n) : "memory"); }
template <int N> __device__ __forceinline__ void reg_inc() { asm volatile("setmaxnreg.inc.sync.aligned.u32 %0;" ::"n"(N)); }
template <int N> __device__ __forceinline__ void reg_dec() { asm volatile("setmaxnreg.dec.sync.aligned.u32 %0;" ::"n"(N)); }

__device__ __forceinline__ uint32_t make_desc(uint32_t addr, uint32_t lbo, uint32_t  ) {
  return ((addr & 0x3FFFF) >> 4) | ((lbo >> 4) << 16);
}
__device__ __forceinline__ void stmatrix_x4(uint32_t addr, uint32_t r0, uint32_t r1, uint32_t r2, uint32_t r3) {
  asm volatile("stmatrix.sync.aligned.m8n8.x4.shared.b16 [%0], {%1,%2,%3,%4};" ::"r"(addr), "r"(r0), "r"(r1), "r"(r2), "r"(r3) : "memory");
}
__device__ __forceinline__ uint4 lds128(uint32_t a) {
  uint4 v;
  asm volatile("ld.shared.v4.u32 {%0,%1,%2,%3}, [%4];" : "=r"(v.x), "=r"(v.y), "=r"(v.z), "=r"(v.w) : "r"(a) : "memory");
  return v;
}
__device__ __forceinline__ void sts128(uint32_t a, uint4 v) {
  asm volatile("st.shared.v4.u32 [%0], {%1,%2,%3,%4};" ::"r"(a), "r"(v.x), "r"(v.y), "r"(v.z), "r"(v.w) : "memory");
}
__device__ __forceinline__ void stg128(void* p, uint4 v) {
  asm volatile("st.global.v4.u32 [%0], {%1,%2,%3,%4};" ::"l"(p), "r"(v.x), "r"(v.y), "r"(v.z), "r"(v.w) : "memory");
}
__device__ __forceinline__ void cp_async16(uint32_t dst, const void* src) {
  asm volatile("cp.async.cg.shared.global [%0], [%1], 16;" ::"r"(dst), "l"(src) : "memory");
}
__device__ __forceinline__ void cp_async_wait_all() { asm volatile("cp.async.wait_all;" ::: "memory"); }
__device__ __forceinline__ uint32_t pack_bf16(float lo, float hi) {
  uint32_t r;
  asm("cvt.rn.bf16x2.f32 %0, %1, %2;" : "=r"(r) : "f"(hi), "f"(lo));
  return r;
}
__device__ __forceinline__ uint32_t hmul2_bf16(uint32_t a, uint32_t b) {
  uint32_t r;
  asm("mul.rn.bf16x2 %0, %1, %2;" : "=r"(r) : "r"(a), "r"(b));
  return r;
}
__device__ __forceinline__ uint32_t hsub2_bf16(uint32_t a, uint32_t b) {
  uint32_t r;
  asm("sub.rn.bf16x2 %0, %1, %2;" : "=r"(r) : "r"(a), "r"(b));
  return r;
}
__device__ __forceinline__ uint32_t hadd2_bf16(uint32_t a, uint32_t b) {
  uint32_t r;
  asm("add.rn.bf16x2 %0, %1, %2;" : "=r"(r) : "r"(a), "r"(b));
  return r;
}
__device__ __forceinline__ uint32_t hfma2_bf16(uint32_t a, uint32_t b, uint32_t c) {
  uint32_t r;
  asm("fma.rn.bf16x2 %0, %1, %2, %3;" : "=r"(r) : "r"(a), "r"(b), "r"(c));
  return r;
}
__device__ __forceinline__ uint4 ldg128_cg(const void* p) {
  uint4 v;
  asm volatile("ld.global.cg.v4.u32 {%0,%1,%2,%3}, [%4];" : "=r"(v.x), "=r"(v.y), "=r"(v.z), "=r"(v.w) : "l"(p) : "memory");
  return v;
}
__device__ __forceinline__ float bf_lo(uint32_t w) { return __uint_as_float(w << 16); }
__device__ __forceinline__ float bf_hi(uint32_t w) { return __uint_as_float(w & 0xffff0000u); }
__device__ __forceinline__ float rbf(float x) { return __bfloat162float(__float2bfloat16_rn(x)); }
__device__ __forceinline__ float tanhf_hw(float x) { float r; asm("tanh.approx.f32 %0, %1;" : "=f"(r) : "f"(x)); return r; }
__device__ __forceinline__ float gelu_tanh(float x) {
  const float c1 = 0.7978845608028654f;
  const float c2 = c1 * 0.044715f;
  const float t = tanhf_hw(x * fmaf(c2, x * x, c1));
  const float hx = 0.5f * x;
  return fmaf(hx, t, hx);
}
__device__ __forceinline__ float silu_f(float x) {
  const float hx = 0.5f * x;
  return fmaf(hx, tanhf_hw(hx), hx);
}

__device__ __forceinline__ void wgmma_rs_n128_tb(float (&d)[64], const uint32_t* a, uint32_t db, int scale_d) {
  asm volatile(
    "{\n.reg .pred p;\n.reg .b64 db;\nsetp.ne.b32 p, %69, 0;\n"
    "mov.b64 db, {%68, 0x40000040};\n"
    "wgmma.mma_async.sync.aligned.m64n128k16.f32.bf16.bf16 {%0, %1, %2, %3, %4, %5, %6, %7, %8, %9, %10, %11, %12, %13, %14, %15, %16, %17, %18, %19, %20, %21, %22, %23, %24, %25, %26, %27, %28, %29, %30, %31, %32, %33, %34, %35, %36, %37, %38, %39, %40, %41, %42, %43, %44, %45, %46, %47, %48, %49, %50, %51, %52, %53, %54, %55, %56, %57, %58, %59, %60, %61, %62, %63}, {%64, %65, %66, %67}, db, p, 1, 1, 1;\n}\n"
    : "+f"(d[0]), "+f"(d[1]), "+f"(d[2]), "+f"(d[3]), "+f"(d[4]), "+f"(d[5]), "+f"(d[6]), "+f"(d[7]), "+f"(d[8]), "+f"(d[9]), "+f"(d[10]), "+f"(d[11]), "+f"(d[12]), "+f"(d[13]), "+f"(d[14]), "+f"(d[15]), "+f"(d[16]), "+f"(d[17]), "+f"(d[18]), "+f"(d[19]), "+f"(d[20]), "+f"(d[21]), "+f"(d[22]), "+f"(d[23]), "+f"(d[24]), "+f"(d[25]), "+f"(d[26]), "+f"(d[27]), "+f"(d[28]), "+f"(d[29]), "+f"(d[30]), "+f"(d[31]), "+f"(d[32]), "+f"(d[33]), "+f"(d[34]), "+f"(d[35]), "+f"(d[36]), "+f"(d[37]), "+f"(d[38]), "+f"(d[39]), "+f"(d[40]), "+f"(d[41]), "+f"(d[42]), "+f"(d[43]), "+f"(d[44]), "+f"(d[45]), "+f"(d[46]), "+f"(d[47]), "+f"(d[48]), "+f"(d[49]), "+f"(d[50]), "+f"(d[51]), "+f"(d[52]), "+f"(d[53]), "+f"(d[54]), "+f"(d[55]), "+f"(d[56]), "+f"(d[57]), "+f"(d[58]), "+f"(d[59]), "+f"(d[60]), "+f"(d[61]), "+f"(d[62]), "+f"(d[63])
    : "r"(a[0]), "r"(a[1]), "r"(a[2]), "r"(a[3]), "r"(db), "r"(scale_d));
}
__device__ __forceinline__ void wgmma_rs_n112(float (&d)[56], const uint32_t* a, uint32_t db, int scale_d) {
  asm volatile(
    "{\n.reg .pred p;\n.reg .b64 db;\nsetp.ne.b32 p, %61, 0;\n"
    "mov.b64 db, {%60, 0x40000040};\n"
    "wgmma.mma_async.sync.aligned.m64n112k16.f32.bf16.bf16 {%0, %1, %2, %3, %4, %5, %6, %7, %8, %9, %10, %11, %12, %13, %14, %15, %16, %17, %18, %19, %20, %21, %22, %23, %24, %25, %26, %27, %28, %29, %30, %31, %32, %33, %34, %35, %36, %37, %38, %39, %40, %41, %42, %43, %44, %45, %46, %47, %48, %49, %50, %51, %52, %53, %54, %55}, {%56, %57, %58, %59}, db, p, 1, 1, 0;\n}\n"
    : "+f"(d[0]), "+f"(d[1]), "+f"(d[2]), "+f"(d[3]), "+f"(d[4]), "+f"(d[5]), "+f"(d[6]), "+f"(d[7]), "+f"(d[8]), "+f"(d[9]), "+f"(d[10]), "+f"(d[11]), "+f"(d[12]), "+f"(d[13]), "+f"(d[14]), "+f"(d[15]), "+f"(d[16]), "+f"(d[17]), "+f"(d[18]), "+f"(d[19]), "+f"(d[20]), "+f"(d[21]), "+f"(d[22]), "+f"(d[23]), "+f"(d[24]), "+f"(d[25]), "+f"(d[26]), "+f"(d[27]), "+f"(d[28]), "+f"(d[29]), "+f"(d[30]), "+f"(d[31]), "+f"(d[32]), "+f"(d[33]), "+f"(d[34]), "+f"(d[35]), "+f"(d[36]), "+f"(d[37]), "+f"(d[38]), "+f"(d[39]), "+f"(d[40]), "+f"(d[41]), "+f"(d[42]), "+f"(d[43]), "+f"(d[44]), "+f"(d[45]), "+f"(d[46]), "+f"(d[47]), "+f"(d[48]), "+f"(d[49]), "+f"(d[50]), "+f"(d[51]), "+f"(d[52]), "+f"(d[53]), "+f"(d[54]), "+f"(d[55])
    : "r"(a[0]), "r"(a[1]), "r"(a[2]), "r"(a[3]), "r"(db), "r"(scale_d));
}
__device__ __forceinline__ void wgmma_n224_tb(float (&d)[112], uint32_t da, uint32_t db, int scale_d) {
  asm volatile(
    "{\n.reg .pred p;\n.reg .b64 da, db;\nsetp.ne.b32 p, %114, 0;\n"
    "mov.b64 da, {%112, 0x40000040};\nmov.b64 db, {%113, 0x40000040};\n"
    "wgmma.mma_async.sync.aligned.m64n224k16.f32.bf16.bf16 {%0, %1, %2, %3, %4, %5, %6, %7, %8, %9, %10, %11, %12, %13, %14, %15, %16, %17, %18, %19, %20, %21, %22, %23, %24, %25, %26, %27, %28, %29, %30, %31, %32, %33, %34, %35, %36, %37, %38, %39, %40, %41, %42, %43, %44, %45, %46, %47, %48, %49, %50, %51, %52, %53, %54, %55, %56, %57, %58, %59, %60, %61, %62, %63, %64, %65, %66, %67, %68, %69, %70, %71, %72, %73, %74, %75, %76, %77, %78, %79, %80, %81, %82, %83, %84, %85, %86, %87, %88, %89, %90, %91, %92, %93, %94, %95, %96, %97, %98, %99, %100, %101, %102, %103, %104, %105, %106, %107, %108, %109, %110, %111}, da, db, p, 1, 1, 0, 1;\n}\n"
    : "+f"(d[0]), "+f"(d[1]), "+f"(d[2]), "+f"(d[3]), "+f"(d[4]), "+f"(d[5]), "+f"(d[6]), "+f"(d[7]), "+f"(d[8]), "+f"(d[9]), "+f"(d[10]), "+f"(d[11]), "+f"(d[12]), "+f"(d[13]), "+f"(d[14]), "+f"(d[15]), "+f"(d[16]), "+f"(d[17]), "+f"(d[18]), "+f"(d[19]), "+f"(d[20]), "+f"(d[21]), "+f"(d[22]), "+f"(d[23]), "+f"(d[24]), "+f"(d[25]), "+f"(d[26]), "+f"(d[27]), "+f"(d[28]), "+f"(d[29]), "+f"(d[30]), "+f"(d[31]), "+f"(d[32]), "+f"(d[33]), "+f"(d[34]), "+f"(d[35]), "+f"(d[36]), "+f"(d[37]), "+f"(d[38]), "+f"(d[39]), "+f"(d[40]), "+f"(d[41]), "+f"(d[42]), "+f"(d[43]), "+f"(d[44]), "+f"(d[45]), "+f"(d[46]), "+f"(d[47]), "+f"(d[48]), "+f"(d[49]), "+f"(d[50]), "+f"(d[51]), "+f"(d[52]), "+f"(d[53]), "+f"(d[54]), "+f"(d[55]), "+f"(d[56]), "+f"(d[57]), "+f"(d[58]), "+f"(d[59]), "+f"(d[60]), "+f"(d[61]), "+f"(d[62]), "+f"(d[63]), "+f"(d[64]), "+f"(d[65]), "+f"(d[66]), "+f"(d[67]), "+f"(d[68]), "+f"(d[69]), "+f"(d[70]), "+f"(d[71]), "+f"(d[72]), "+f"(d[73]), "+f"(d[74]), "+f"(d[75]), "+f"(d[76]), "+f"(d[77]), "+f"(d[78]), "+f"(d[79]), "+f"(d[80]), "+f"(d[81]), "+f"(d[82]), "+f"(d[83]), "+f"(d[84]), "+f"(d[85]), "+f"(d[86]), "+f"(d[87]), "+f"(d[88]), "+f"(d[89]), "+f"(d[90]), "+f"(d[91]), "+f"(d[92]), "+f"(d[93]), "+f"(d[94]), "+f"(d[95]), "+f"(d[96]), "+f"(d[97]), "+f"(d[98]), "+f"(d[99]), "+f"(d[100]), "+f"(d[101]), "+f"(d[102]), "+f"(d[103]), "+f"(d[104]), "+f"(d[105]), "+f"(d[106]), "+f"(d[107]), "+f"(d[108]), "+f"(d[109]), "+f"(d[110]), "+f"(d[111])
    : "r"(da), "r"(db), "r"(scale_d));
}


constexpr int K1_NS = 12;
constexpr int K1_A_BYTES = 7 * 16384;
constexpr int K1_B_OFF = K1_A_BYTES;
constexpr int K1_STG_OFF = K1_B_OFF + 5 * 16384;
constexpr int K1_BAR_OFF = K1_STG_OFF + 8 * 4096;
constexpr int K1_SMEM = K1_BAR_OFF + 512 + 1024;
__device__ __forceinline__ uint32_t k1_slot_off(int slot) { return (slot < 5) ? K1_B_OFF + slot * 16384 : (slot - 5) * 16384; }

struct K1Ctx {
  uint32_t sb, bar_full, rel0, rel1;
  uint32_t dB;
  bool lane0;
  uint32_t bar_sfree;
  uint32_t sphase;
  int slot; uint32_t ph;
};
__device__ __forceinline__ void k1_release(const K1Ctx& c, int slot) {
  if (c.lane0) {
    asm volatile("mbarrier.arrive.shared::cluster.b64 _, [%0];" ::"r"(c.rel0 + 8 * slot) : "memory");
    asm volatile("mbarrier.arrive.shared::cluster.b64 _, [%0];" ::"r"(c.rel1 + 8 * slot) : "memory");
  }
}

template <bool AB, int NACC>
__device__ __forceinline__ void k1_mainloop(K1Ctx& c, const uint32_t (&af)[112], float (&acc)[NACC], int wg, bool last_of_cta) {
  int pslot = 0;
#pragma unroll
  for (int kb = 0; kb < 7; kb++) {
    mbar_wait(c.bar_full + 8 * c.slot, c.ph, 3);
    wg_fence();
    const uint32_t db = c.dB + (k1_slot_off(c.slot) >> 4) + (AB ? (1u << 16) : (512u << 16));
#pragma unroll
    for (int k = 0; k < 4; k++) {
      if constexpr (AB) wgmma_rs_n112(acc, &af[16 * kb + 4 * k], db + k * 2, (kb | k) != 0);
      else wgmma_rs_n128_tb(acc, &af[16 * kb + 4 * k], db + k * 128, (kb | k) != 0);
    }
    wg_commit();
    if (kb == 6 && !last_of_cta) named_arrive(3 - wg, 256);
    if (kb > 0) { wg_wait<1>(); k1_release(c, pslot); }
    pslot = c.slot;
    if (++c.slot == K1_NS) { c.slot = 0; c.ph ^= 1; }
  }
  wg_wait<0>();
  k1_release(c, pslot);
}

constexpr int K2_NS = 4;
constexpr int K2_STAGE = 16384 + 32768;

__device__ __forceinline__ void spin_flag(const unsigned int* flag, unsigned int target) {
  int it = 0;
  while (true) {
    unsigned int v;
    asm volatile("ld.acquire.gpu.global.u32 %0, [%1];" : "=r"(v) : "l"(flag) : "memory");
    if ((int)(v - target) >= 0) break;
    if (++it > SPIN_LIMIT) break;
  }
}


__device__ __forceinline__ void mma16816(float (&d)[4], const uint32_t* a, uint32_t b0, uint32_t b1) {
  asm volatile("mma.sync.aligned.m16n8k16.row.col.f32.bf16.bf16.f32 {%0,%1,%2,%3}, {%4,%5,%6,%7}, {%8,%9}, {%0,%1,%2,%3};"
               : "+f"(d[0]), "+f"(d[1]), "+f"(d[2]), "+f"(d[3]) : "r"(a[0]), "r"(a[1]), "r"(a[2]), "r"(a[3]), "r"(b0), "r"(b1));
}
__device__ __forceinline__ void ln_consts(float sum, float sq, uint32_t& m2, uint32_t& rhi2, uint32_t& rlo2) {
  const float m = sum * (1.0f / 448.0f);
  const float var = fmaxf(fmaf(-m, m, sq * (1.0f / 448.0f)), 0.0f);
  const float den = rbf(sqrtf(rbf(rbf(var) + 1e-5f)));
  const float ri = 1.0f / den;
  const float rih = rbf(ri);
  m2 = pack_bf16(m, m); rhi2 = pack_bf16(rih, rih); rlo2 = pack_bf16(ri - rih, ri - rih);
}

struct PfPtrs { const uint8_t* wg; const uint8_t* wu; const uint8_t* wd; };

__global__ void __cluster_dims__(2, 1, 1) __launch_bounds__(384, 1)
fused_kernel(const __grid_constant__ CUtensorMap tm_wr, const __grid_constant__ CUtensorMap tm_wi,
             const __grid_constant__ CUtensorMap tm_wg, const __grid_constant__ CUtensorMap tm_wu,
             const __grid_constant__ CUtensorMap tm_hs, const __grid_constant__ CUtensorMap tm_abs,
             const __grid_constant__ CUtensorMap tm_cr, const __grid_constant__ CUtensorMap tm_ci, const __grid_constant__ CUtensorMap tm_h,
             const __grid_constant__ CUtensorMap tm_ab, const __grid_constant__ CUtensorMap tm_wd,
             const __nv_bfloat16* __restrict__ x, __nv_bfloat16* __restrict__ out, const PfPtrs pf) {
  extern __shared__ uint8_t smem_raw[];
  const uint32_t sb = (s2u(smem_raw) + 1023) & ~1023u;
  const int tid = threadIdx.x, warp = tid >> 5, lane = tid & 31;
  uint32_t rank;
  asm volatile("mov.u32 %0, %%cluster_ctarank;" : "=r"(rank));
  const int cid = blockIdx.x >> 1;
  const int p = cid >> 3, j = cid & 7;
  const int mt = 2 * p + (int)rank;
  const uint32_t bar_full = sb + K1_BAR_OFF;
  const uint32_t bar_empty = bar_full + 8 * K1_NS;
  const uint32_t bar_full2 = bar_empty + 8 * K1_NS;
  const uint32_t bar_empty2 = bar_full2 + 8 * K2_NS;
  const int q = j & 3, n = j >> 2;
  const int tile = mt * 2 + n;
  const int nkb = (q == 0) ? 22 : (q == 1 ? 26 : (q == 2 ? 16 : 28));
  const int ngu = (q == 0) ? 4 : (q == 1 ? 3 : (q == 2 ? 5 : 2));
  const int nunits = ngu + 1;
  const int fb0 = 7 * (j >> 1) + ((q == 1) ? 4 : (q == 3 ? 5 : 0)) - 1;
  const unsigned int epoch = *reinterpret_cast<volatile unsigned int*>(&g_epoch);
  if (warp < 8) {
    const int r0 = warp * 16 + (lane >> 3), cc = lane & 7;
    const __nv_bfloat16* xs = x + (size_t)(mt * 128 + r0) * 448 + cc * 8;
#pragma unroll 1
    for (int rg = 0; rg < 4; rg++) {
      const int r = r0 + rg * 4;
      const uint32_t d = sb + r * 128 + ((cc ^ (r & 7)) * 16);
#pragma unroll
      for (int b = 0; b < 7; b++) cp_async16(d + b * 16384, xs + rg * 4 * 448 + b * 64);
    }
  }
  if (tid == 256) {
    for (int i = 0; i < K1_NS; i++) { mbar_init(bar_full + 8 * i, 1); mbar_init(bar_empty + 8 * i, 16); }
    for (int i = 0; i < K2_NS; i++) { mbar_init(bar_full2 + 8 * i, 1); mbar_init(bar_empty2 + 8 * i, 16); }
    mbar_init(bar_empty2 + 8 * K2_NS, 1);
    mbar_init(bar_empty2 + 8 * K2_NS + 8, 1);
    mbar_init(bar_empty2 + 8 * K2_NS + 16, 1);
    asm volatile("fence.mbarrier_init.release.cluster;" ::: "memory");
    prefetch_tmap((j < 4) ? &tm_wr : &tm_wi);
    prefetch_tmap(rank ? &tm_wu : &tm_wg);
    prefetch_tmap(&tm_abs);
    prefetch_tmap(&tm_hs);
  }
  __syncwarp();
  cluster_arrive_relaxed();

  if (warp >= 8) {
    reg_dec<40>();
    cluster_wait();
    if (tid == 256) {
      {
        const CUtensorMap* tw = (j < 4) ? &tm_wr : &tm_wi;
        const CUtensorMap* tgu = rank ? &tm_wu : &tm_wg;
        int slot = 0, use = 0;
        int kb = 0, unit = 0;
#pragma unroll 1
        for (int s = 0; s < 7 * nunits; s++) {
          if (slot >= 5) mbar_wait(bar_empty + 8 * slot, use & 1, 2);
          else if (use > 0) mbar_wait(bar_empty + 8 * slot, (use - 1) & 1, 2);
          const uint32_t dst = sb + k1_slot_off(slot);
          if (unit == 0) {
            mbar_expect(bar_full + 8 * slot, 14336);
            tma2d_mc(dst + rank * 7168, tw, kb * 64, (j & 3) * 112 + rank * 56, bar_full + 8 * slot, 3);
          } else {
            mbar_expect(bar_full + 8 * slot, 16384);
            tma2d_mc(dst + rank * 8192, tgu, (fb0 + unit) * 64, kb * 64, bar_full + 8 * slot, 3);
          }
          if (s == 7 * nunits - 4) {
            l2_prefetch(pf.wd + blockIdx.x * 12544, 12544);
            if (q < 3) {
              const int g0 = (q == 0) ? 0 : (q == 1 ? 22 : 48);
#pragma unroll 1
              for (int i = 0; i < 6; i++) tma2d_prefetch((g0 + i < 32) ? &tm_cr : &tm_ci, ((g0 + i) & 31) * 64, mt * 128);
            }
          }
          if (++kb == 7) { kb = 0; unit++; }
          if (++slot == K1_NS) { slot = 0; use++; }
        }
      }
      {
        const int g0 = (q == 0) ? 0 : (q == 1 ? 22 : (q == 2 ? 48 : 64));
        const CUtensorMap* tb = (q < 3) ? &tm_ab : &tm_wd;
        prefetch_tmap(tb); prefetch_tmap((q < 3) ? ((g0 < 32) ? &tm_cr : &tm_ci) : &tm_h);
        const int kb0 = (q < 3) ? g0 : 0;
        if (q < 3) { spin_flag(&g_ab_cnt, 256u * (epoch + 1)); asm volatile("fence.proxy.async;" ::: "memory"); }
        int slot = 0; uint32_t ph = 0;
#pragma unroll 1
        for (int s = 0; s < nkb; s++) {
          int kblk = kb0 + s;
          const CUtensorMap* ta = (kblk < 32) ? &tm_cr : &tm_ci;
          if (q == 3) {
            const int cls = (s == 0) ? 0 : (s == 8 ? 1 : (s == 16 ? 2 : (s == 22 ? 3 : (s == 26 ? 4 : -1))));
            if (cls >= 0) { spin_flag(&g_h_cnt[mt * 8 + cls], ((cls < 2) ? 16u : (cls == 2 ? 12u : (cls == 3 ? 8u : 4u))) * (epoch + 1)); asm volatile("fence.proxy.async;" ::: "memory"); }
            kblk = c_forder[s];
            ta = &tm_h;
          }
          mbar_wait(bar_empty2 + 8 * slot, ph, 10);
          const uint32_t dst = sb + slot * K2_STAGE;
          const uint32_t fb = bar_full2 + 8 * slot;
          mbar_expect(fb, K2_STAGE);
          tma2d(dst, ta, (kblk & 31) * 64, mt * 128, fb);
          tma3d_mc(dst + 16384 + (2 * rank) * 8192, tb, (2 * rank) * 64, n, kblk * 64, fb, 3);
          tma3d_mc(dst + 16384 + (2 * rank + 1) * 8192, tb, (2 * rank + 1) * 64, n, kblk * 64, fb, 3);
          if (++slot == K2_NS) { slot = 0; ph ^= 1; }
        }
      }
    } else if (warp == 9 || warp == 10) {
      const int hw = warp - 9;
      const uint32_t stg = sb + K1_STG_OFF + hw * 16384;
      const uint32_t bar_sfree = bar_empty2 + 8 * K2_NS + 8 + 8 * hw;
      if (lane == 0) {
        const int b = blockIdx.x;
        l2_prefetch((hw ? pf.wu : pf.wg) + b * 12544, 12544);
      }
#pragma unroll 1
      for (int unit = 0; unit < nunits; unit++) {
        named_bar(6 + hw, 160);
        if (lane == 0) {
          if (unit == 0) tma2d_store(&tm_abs, stg, (j & 3) * 112, (j < 4 ? 0 : 2048) + mt * 128 + hw * 64);
          else tma2d_store(&tm_hs, stg, (fb0 + unit) * 64, mt * 128 + hw * 64);
          bulk_commit();
          bulk_wait_read0();
          asm volatile("mbarrier.arrive.shared::cta.b64 _, [%0];" ::"r"(bar_sfree) : "memory");
          bulk_wait0();
          asm volatile("fence.proxy.async;" ::: "memory");
          asm volatile("fence.acq_rel.gpu;" ::: "memory");
          if (unit == 0) {
            const unsigned int old = atomicAdd(&g_ab_cnt, 1u);
            if ((old & 255u) == 255u) *reinterpret_cast<volatile unsigned int*>(&g_epoch) = (old >> 8) + 1;
          } else {
            atomicAdd(&g_h_cnt[mt * 8 + unit - 1], 1u);
          }
        }
        __syncwarp();
      }
    }
  } else {
    const int wg = warp >> 2;
    reg_inc<232>();
    cluster_wait();

    uint32_t rel0, rel1, sphase_end;
    asm volatile("mapa.shared::cluster.u32 %0, %1, %2;" : "=r"(rel0) : "r"(bar_empty2), "r"(0));
    asm volatile("mapa.shared::cluster.u32 %0, %1, %2;" : "=r"(rel1) : "r"(bar_empty2), "r"(1));
    {
      K1Ctx c;
      c.sb = sb; c.bar_full = bar_full; c.lane0 = (lane == 0);
      c.rel0 = rel0 - 8 * (K1_NS + K2_NS); c.rel1 = rel1 - 8 * (K1_NS + K2_NS);
      c.bar_sfree = bar_empty2 + 8 * K2_NS + 8 + 8 * wg; c.sphase = 0;
      c.dB = (sb & 0x3FFFF) >> 4;
      c.slot = 0; c.ph = 0;
      const int wq = warp & 3;
      const int st_row = (lane & 7) + 8 * ((lane >> 3) & 1);
      const int st_chunk = lane >> 4;
      uint32_t af[112];
      {
        cp_async_wait_all();
        __syncwarp();
        const int r = warp * 16 + st_row;
        const uint32_t ra = sb + r * 128;
#pragma unroll
        for (int t = 0; t < 28; t++) {
          const uint32_t ad = ra + (t >> 2) * 16384 + (((2 * (t & 3) + st_chunk) ^ (r & 7)) * 16);
          asm volatile("ldmatrix.sync.aligned.m8n8.x4.shared.b16 {%0,%1,%2,%3}, [%4];"
                       : "=r"(af[4 * t]), "=r"(af[4 * t + 1]), "=r"(af[4 * t + 2]), "=r"(af[4 * t + 3]) : "r"(ad) : "memory");
        }
        __syncwarp();
        if (lane >= 5 && lane < K1_NS) {
          asm volatile("mbarrier.arrive.shared::cluster.b64 _, [%0];" ::"r"(c.rel0 + 8 * lane) : "memory");
          asm volatile("mbarrier.arrive.shared::cluster.b64 _, [%0];" ::"r"(c.rel1 + 8 * lane) : "memory");
        }
        float sS[4] = {0.f, 0.f, 0.f, 0.f}, q1[4] = {0.f, 0.f, 0.f, 0.f}, q2[4] = {0.f, 0.f, 0.f, 0.f};
#pragma unroll
        for (int t = 0; t < 28; t++) {
          mma16816(sS, &af[4 * t], 0x3F803F80u, 0x3F803F80u);
          mma16816(q1, &af[4 * t], af[4 * t], af[4 * t + 2]);
          mma16816(q2, &af[4 * t], af[4 * t + 1], af[4 * t + 3]);
        }
        const int g = lane >> 2;
        const int src_lane = g * 4 + (g >> 1);
        const float sqa = __shfl_sync(0xffffffffu, (g & 1) ? q1[1] : q1[0], src_lane);
        const float sqb = __shfl_sync(0xffffffffu, (g & 1) ? q2[3] : q2[2], src_lane);
        uint32_t ma, ha, la, mb, hb, lb;
        ln_consts(sS[0], sqa, ma, ha, la);
        ln_consts(sS[2], sqb, mb, hb, lb);
#pragma unroll
        for (int i = 0; i < 112; i++) {
          const uint32_t d = hsub2_bf16(af[i], (i & 1) ? mb : ma);
          af[i] = hfma2_bf16(d, (i & 1) ? hb : ha, hmul2_bf16(d, (i & 1) ? lb : la));
        }
      }
      const uint32_t stg = sb + K1_STG_OFF + wg * 16384;
      {
        float acc[56];
        if (wg == 1) named_bar(3, 256);
        k1_mainloop<true, 56>(c, af, acc, wg, false);
        const uint32_t sgn = (j < 4) ? 0u : 0x80008000u;
        const uint32_t sa = stg + (wq * 16 + st_row) * 224 + st_chunk * 16;
#pragma unroll
        for (int g = 0; g < 14; g += 2) {
          const float* a = &acc[4 * g];
          stmatrix_x4(sa + g * 16, pack_bf16(a[0], a[1]) ^ sgn, pack_bf16(a[2], a[3]) ^ sgn, pack_bf16(a[4], a[5]) ^ sgn, pack_bf16(a[6], a[7]) ^ sgn);
        }
        fence_async_smem();
        named_arrive(6 + wg, 160);
      }
#pragma unroll 1
      for (int unit = 1; unit < nunits; unit++) {
        float acc[64];
        named_bar(2 + wg, 256);
        k1_mainloop<false, 64>(c, af, acc, wg, (unit == nunits - 1) && (wg == 1));
        if (unit == nunits - 1 && lane < 4) {
          asm volatile("mbarrier.arrive.shared::cluster.b64 _, [%0];" ::"r"(rel0 + 8 * lane) : "memory");
          asm volatile("mbarrier.arrive.shared::cluster.b64 _, [%0];" ::"r"(rel1 + 8 * lane) : "memory");
        }
        mbar_wait(c.bar_sfree, c.sphase, 7); c.sphase ^= 1;
        const uint32_t sa = stg + (wq * 16 + st_row) * 128;
#pragma unroll
        for (int g = 0; g < 8; g += 2) {
          uint32_t pk[4];
#pragma unroll
          for (int e = 0; e < 4; e++) {
            const int i = 4 * g + 2 * e;
            const uint32_t g2 = pack_bf16(acc[i], acc[i + 1]);
            const uint32_t u2 = pack_bf16(acc[32 + i], acc[32 + i + 1]);
            pk[e] = hmul2_bf16(pack_bf16(gelu_tanh(bf_lo(g2)), gelu_tanh(bf_hi(g2))), u2);
          }
          stmatrix_x4(sa + (((g + st_chunk) ^ (st_row & 7)) * 16), pk[0], pk[1], pk[2], pk[3]);
        }
        fence_async_smem();
        named_arrive(6 + wg, 160);
      }
      sphase_end = c.sphase;
    }

    float acc[112];
    const uint32_t dA0 = make_desc(sb + wg * 8192, 16, 1024);
    const uint32_t dB0 = make_desc(sb + 16384, 8192, 1024);
    int slot = 0; uint32_t ph = 0;
#pragma unroll 1
    for (int s = 0; s < nkb; s++) {
      mbar_wait(bar_full2 + 8 * slot, ph, 11);
      wg_fence();
      const uint32_t da = dA0 + slot * (K2_STAGE / 16);
      const uint32_t db = dB0 + slot * (K2_STAGE / 16);
#pragma unroll
      for (int k = 0; k < 4; k++) wgmma_n224_tb(acc, da + k * 2, db + k * 128, (s | k) != 0);
      wg_commit();
      if (s > 0) {
        wg_wait<1>();
        const int ps = (slot == 0) ? K2_NS - 1 : slot - 1;
        if (lane == 0) {
          asm volatile("mbarrier.arrive.shared::cluster.b64 _, [%0];" ::"r"(rel0 + 8 * ps) : "memory");
          asm volatile("mbarrier.arrive.shared::cluster.b64 _, [%0];" ::"r"(rel1 + 8 * ps) : "memory");
        }
      }
      if (++slot == K2_NS) { slot = 0; ph ^= 1; }
    }
    wg_wait<0>();
    uint32_t ow[56];
#pragma unroll
    for (int i = 0; i < 56; i++) ow[i] = pack_bf16(acc[2 * i], acc[2 * i + 1]);
    const int P0 = (q < 2) ? 4 * q : 3 * q + 2, NP = (q < 2) ? 4 : 3;
    uint4* part = g_part + (size_t)tile * (4 * 14 * 256) + tid;
    mbar_wait(bar_empty2 + 8 * K2_NS + 8 + 8 * wg, sphase_end, 14);
    const uint32_t stg = sb + K1_STG_OFF + warp * 4096;
    const uint32_t stash = stg + 2048 + lane * 16 - P0 * 512;
#pragma unroll
    for (int g = 0; g < 14; g++) {
      const uint4 v = make_uint4(ow[4 * g], ow[4 * g + 1], ow[4 * g + 2], ow[4 * g + 3]);
      if ((unsigned)(g - P0) >= (unsigned)NP) part[(q * 14 + g) * 256] = v;
      else sts128(stash + g * 512, v);
    }
    __syncwarp();
    unsigned int* flag = &g_flags[tile * 8 + warp];
    if (lane == 0) { asm volatile("fence.acq_rel.gpu;" ::: "memory"); atomicAdd(flag, 1u); }
    const int ch = lane & 7;
    const bool act = ch < 2 * NP;
    const size_t gbase = (size_t)(mt * 128 + warp * 16 + (lane >> 3)) * 448 + n * 224 + P0 * 16 + (act ? ch : 0) * 8;
    uint4 xv[4];
#pragma unroll
    for (int t = 0; t < 4; t++) xv[t] = ldg128_cg(x + gbase + t * 4 * 448);
    if (lane == 0) spin_flag(flag, 4u * (epoch + 1));
    __syncwarp();
    uint4 oth[3][4];
#pragma unroll
    for (int i = 0; i < 3; i++) {
      const int r = (i < q) ? i : i + 1;
#pragma unroll
      for (int e = 0; e < 4; e++) oth[i][e] = ldg128_cg(part + (r * 14 + P0 + (e < NP ? e : 0)) * 256);
    }
    const bool isf = (q == 3);
    const int st_row = (lane & 7) + 8 * ((lane >> 3) & 1);
    const uint32_t sa = stg + st_row * 128;
#pragma unroll
    for (int e = 0; e < 4; e++) {
      const uint32_t av[4] = {oth[0][e].x, oth[0][e].y, oth[0][e].z, oth[0][e].w};
      const uint32_t bv[4] = {oth[1][e].x, oth[1][e].y, oth[1][e].z, oth[1][e].w};
      const uint32_t cv[4] = {oth[2][e].x, oth[2][e].y, oth[2][e].z, oth[2][e].w};
      const uint4 mine = lds128(stg + 2048 + lane * 16 + (e < NP ? e : 0) * 512);
      const uint32_t mv[4] = {mine.x, mine.y, mine.z, mine.w};
      uint32_t tv[4];
#pragma unroll
      for (int k = 0; k < 4; k++) {
        const uint32_t y3 = isf ? cv[k] : mv[k], ff = isf ? mv[k] : cv[k];
        const uint32_t gg = pack_bf16(silu_f(bf_lo(ff)), silu_f(bf_hi(ff)));
        tv[k] = hmul2_bf16(pack_bf16(bf_lo(av[k]) + bf_lo(bv[k]) + bf_lo(y3), bf_hi(av[k]) + bf_hi(bv[k]) + bf_hi(y3)), gg);
      }
      stmatrix_x4(sa + (((2 * e + (lane >> 4)) ^ (st_row & 7)) * 16), tv[0], tv[1], tv[2], tv[3]);
    }
    __syncwarp();
#pragma unroll
    for (int t = 0; t < 4; t++) {
      const int row = t * 4 + (lane >> 3);
      const uint4 tv = lds128(stg + row * 128 + ((ch ^ (row & 7)) * 16));
      uint4 o;
      o.x = hadd2_bf16(xv[t].x, tv.x); o.y = hadd2_bf16(xv[t].y, tv.y); o.z = hadd2_bf16(xv[t].z, tv.z); o.w = hadd2_bf16(xv[t].w, tv.w);
      if (act) stg128(out + gbase + t * 4 * 448, o);
    }
  }
  __syncwarp();
  cluster_arrive_relaxed();
  cluster_wait();
}

typedef CUresult (*EncFn)(CUtensorMap*, CUtensorMapDataType, cuuint32_t, void*, const cuuint64_t*, const cuuint64_t*, const cuuint32_t*,
                          const cuuint32_t*, CUtensorMapInterleave, CUtensorMapSwizzle, CUtensorMapL2promotion, CUtensorMapFloatOOBfill);

void make2d(EncFn enc, CUtensorMap* tm, const void* ptr, uint64_t cols, uint64_t rows, uint32_t bc, uint32_t br, bool swz = true) {
  cuuint64_t gd[2] = {cols, rows};
  cuuint64_t gs[1] = {cols * 2};
  cuuint32_t bd[2] = {bc, br};
  cuuint32_t es[2] = {1, 1};
  enc(tm, CU_TENSOR_MAP_DATA_TYPE_BFLOAT16, 2, const_cast<void*>(ptr), gd, gs, bd, es, CU_TENSOR_MAP_INTERLEAVE_NONE,
      swz ? CU_TENSOR_MAP_SWIZZLE_128B : CU_TENSOR_MAP_SWIZZLE_NONE, CU_TENSOR_MAP_L2_PROMOTION_L2_128B, CU_TENSOR_MAP_FLOAT_OOB_FILL_NONE);
}
void make3d_half(EncFn enc, CUtensorMap* tm, const void* ptr, uint64_t rows) {
  cuuint64_t gd[3] = {224, 2, rows};
  cuuint64_t gs[2] = {448, 896};
  cuuint32_t bd[3] = {64, 1, 64};
  cuuint32_t es[3] = {1, 1, 1};
  enc(tm, CU_TENSOR_MAP_DATA_TYPE_BFLOAT16, 3, const_cast<void*>(ptr), gd, gs, bd, es, CU_TENSOR_MAP_INTERLEAVE_NONE,
      CU_TENSOR_MAP_SWIZZLE_128B, CU_TENSOR_MAP_L2_PROMOTION_L2_128B, CU_TENSOR_MAP_FLOAT_OOB_FILL_NONE);
}

struct Maps { CUtensorMap x, wr, wi, wg, wu, cr, ci, h, ab, wd, hs, abs; };

}

extern "C" void kernel_launch(void* const* d_in, const int* in_sizes, int n_in, void* d_out, int out_size) {
  (void)in_sizes; (void)n_in; (void)out_size;
  static Maps maps;
  static const void* cached[9] = {nullptr};
  static bool attr_done = false;
  bool same = true;
  for (int i = 0; i < 9; i++) same = same && (cached[i] == d_in[i]);
  if (!same) {
    void* fn = nullptr;
    cudaDriverEntryPointQueryResult qr;
    cudaGetDriverEntryPoint("cuTensorMapEncodeTiled", &fn, cudaEnableDefault, &qr);
    EncFn enc = (EncFn)fn;
    void *p_ab = nullptr, *p_h = nullptr;
    cudaGetSymbolAddress(&p_ab, g_ab);
    cudaGetSymbolAddress(&p_h, g_h);
    make2d(enc, &maps.cr, d_in[1], 2048, 2048, 64, 128);
    make2d(enc, &maps.ci, d_in[2], 2048, 2048, 64, 128);
    make2d(enc, &maps.wr, d_in[3], 448, 448, 64, 56);
    make2d(enc, &maps.wi, d_in[4], 448, 448, 64, 56);
    make2d(enc, &maps.wg, d_in[6], 1792, 448, 64, 64);
    make2d(enc, &maps.wu, d_in[7], 1792, 448, 64, 64);
    make3d_half(enc, &maps.wd, d_in[8], 1792);
    make2d(enc, &maps.h, p_h, 1792, 2048, 64, 128);
    make3d_half(enc, &maps.ab, p_ab, 4096);
    make2d(enc, &maps.hs, p_h, 1792, 2048, 64, 64);
    make2d(enc, &maps.abs, p_ab, 448, 4096, 112, 64, false);
    for (int i = 0; i < 9; i++) cached[i] = d_in[i];
  }
  if (!attr_done) {
    cudaFuncSetAttribute(fused_kernel, cudaFuncAttributeMaxDynamicSharedMemorySize, K1_SMEM);
    attr_done = true;
  }
  PfPtrs pf;
  pf.wg = (const uint8_t*)d_in[6]; pf.wu = (const uint8_t*)d_in[7]; pf.wd = (const uint8_t*)d_in[8];
  fused_kernel<<<128, 384, K1_SMEM>>>(maps.wr, maps.wi, maps.wg, maps.wu, maps.hs, maps.abs, maps.cr, maps.ci, maps.h, maps.ab, maps.wd,
                                      (const __nv_bfloat16*)d_in[0], (__nv_bfloat16*)d_out, pf);
}
```
